```python
import torch

def _softmax(x, axis=-1):
    return torch.softmax(x, dim=axis)
def _gelu(x):
    return torch.nn.functional.gelu(x, approximate="tanh")
def _silu(x):
    return torch.nn.functional.silu(x)
def _sigmoid(x):
    return torch.sigmoid(x)
def _layernorm(x, axis=-1, eps=1e-5):
    m = x.mean(dim=axis, keepdim=True)
    v = x.var(dim=axis, keepdim=True, unbiased=False)
    return (x - m) / torch.sqrt(v + eps)
def _scatter_add(tgt, idx, src, axis=0):
    return tgt.clone().index_add_(axis, idx, src)
def _segment_sum(src, seg, n):
    out = torch.zeros((n,) + src.shape[1:], dtype=src.dtype)
    return out.index_add_(0, seg, src)
def _pad(x, pw):
    flat = tuple(v for pair in reversed(pw) for v in pair)
    return torch.nn.functional.pad(x, flat)

kernel_name = 'sequential_preLN__softmax_full_mha__glu_gated_reglu__prompt'

def setup_inputs():

    _w = (lambda a: (lambda t: t.to(torch.bfloat16) if t.is_floating_point() else t)(torch.as_tensor(a)))
    def _A_setup():
        B, S, D = 1, 2048, 640
        return {
            "x": _w((lambda *s: torch.randn(*s, dtype=torch.bfloat16) * 0.05)(B, S, D)),
            "wqkv": _w((lambda *s: torch.randn(*s, dtype=torch.bfloat16) * 0.05)(D, 3 * D)),
            "wo": _w((lambda *s: torch.randn(*s, dtype=torch.bfloat16) * 0.05)(D, D)),
        }
    _A_in = _A_setup()

    def _B_setup():
        B, S, D, F = 1, 2048, 640, 1536
        return {
            "x": _w((lambda *s: torch.randn(*s, dtype=torch.bfloat16) * 0.05)(B, S, D)),
            "W_gate": _w((lambda *s: torch.randn(*s, dtype=torch.bfloat16) * 0.4)(D, F) * (2.0 / D) ** 0.5),
            "W_up": _w((lambda *s: torch.randn(*s, dtype=torch.bfloat16) * 0.4)(D, F) * (2.0 / D) ** 0.5),
            "W_down": _w((lambda *s: torch.randn(*s, dtype=torch.bfloat16) * 0.4)(F, D) * (1.0 / F) ** 0.5),
        }
    _B_in = _B_setup()

    return {
        "A_x": _A_in["x"],
        "A_wqkv": _A_in["wqkv"],
        "A_wo": _A_in["wo"],
        "B_x": _B_in["x"],
        "B_W_gate": _B_in["W_gate"],
        "B_W_up": _B_in["W_up"],
        "B_W_down": _B_in["W_down"],
    }

def reference(A_x, A_wqkv, A_wo, B_x, B_W_gate, B_W_up, B_W_down):
    def _A_ref(x, wqkv, wo):
        B, S, D = x.shape
        H = 32; Dh = D // H
        qkv = (lambda x, *d: x.permute(*d))((x @ wqkv).reshape(B, S, 3, H, Dh), 2, 0, 3, 1, 4)
        q, k, v = qkv[0], qkv[1], qkv[2]
        scale = Dh ** -0.5
        scores = torch.einsum("bhqd,bhkd->bhqk", q, k) * scale
        p = _softmax(scores, axis=-1)
        o = torch.einsum("bhqk,bhkd->bhqd", p, v)
        return (lambda x, *d: x.permute(*d))(o, 0, 2, 1, 3).reshape(B, S, D) @ wo

    def _B_ref(x, W_gate, W_up, W_down):
        gate = torch.einsum("bsd,df->bsf", x, W_gate)
        up = torch.einsum("bsd,df->bsf", x, W_up)
        gate = gate * (lambda x, dt: x.to(dt))(gate > 0, gate.dtype)
        h = gate * up
        return torch.einsum("bsf,fd->bsd", h, W_down)

    x = A_x
    h = x + _A_ref(_layernorm(x, axis=-1), A_wqkv, A_wo)
    h2 = h + _B_ref(_layernorm(h, axis=-1), B_W_gate, B_W_up, B_W_down)
    return h2
```

```cpp
#include <cuda_runtime.h>
#include <cuda_bf16.h>
#include <cuda.h>
#include <stdint.h>

typedef __nv_bfloat16 bf16;

constexpr int SEQ = 2048, DM = 640, NH = 32, DH = 20, FF = 1536;
constexpr int IMG_HEAD_ELEMS = (SEQ / 8) * 192;

__device__ __align__(1024) bf16 g_q[SEQ * DM];
__device__ __align__(1024) bf16 g_kimg[NH * IMG_HEAD_ELEMS];
__device__ __align__(1024) bf16 g_vimg[NH * IMG_HEAD_ELEMS];
__device__ __align__(1024) bf16 g_o[SEQ * DM];
__device__ __align__(1024) bf16 g_h[SEQ * DM];
__device__ __align__(1024) bf16 g_hh[SEQ * FF];

__device__ __forceinline__ uint32_t smem_u32(const void* p) { return (uint32_t)__cvta_generic_to_shared(p); }
__device__ __forceinline__ void mbar_init(uint32_t bar, uint32_t cnt) {
  asm volatile("mbarrier.init.shared::cta.b64 [%0], %1;" ::"r"(bar), "r"(cnt) : "memory");
}
__device__ __forceinline__ void mbar_expect_tx(uint32_t bar, uint32_t bytes) {
  asm volatile("mbarrier.arrive.expect_tx.shared::cta.b64 _, [%0], %1;" ::"r"(bar), "r"(bytes) : "memory");
}
__device__ __forceinline__ void mbar_arrive(uint32_t bar) {
  asm volatile("mbarrier.arrive.shared::cta.b64 _, [%0];" ::"r"(bar) : "memory");
}
__device__ __forceinline__ void mbar_arrive_cluster(uint32_t bar, uint32_t cta) {
  asm volatile(
      "{\n.reg .b32 r;\nmapa.shared::cluster.u32 r, %0, %1;\n"
      "mbarrier.arrive.shared::cluster.b64 _, [r];\n}\n" ::"r"(bar), "r"(cta)
      : "memory");
}
__device__ __forceinline__ void mbar_wait(uint32_t bar, uint32_t parity) {
  asm volatile(
      "{\n.reg .pred p;\nLAB_WAIT:\n"
      "mbarrier.try_wait.parity.shared::cta.b64 p, [%0], %1;\n"
      "@p bra DONE;\nbra LAB_WAIT;\nDONE:\n}\n" ::"r"(bar), "r"(parity)
      : "memory");
}
__device__ __forceinline__ void mbar_wait_cluster(uint32_t bar, uint32_t parity) {
  asm volatile(
      "{\n.reg .pred p;\nLAB_WAIT:\n"
      "mbarrier.try_wait.parity.acquire.cluster.shared::cta.b64 p, [%0], %1;\n"
      "@p bra DONE;\nbra LAB_WAIT;\nDONE:\n}\n" ::"r"(bar), "r"(parity)
      : "memory");
}
__device__ __forceinline__ void fence_mbar_init() { asm volatile("fence.mbarrier_init.release.cluster;" ::: "memory"); }
__device__ __forceinline__ void fence_proxy_async() { asm volatile("fence.proxy.async.shared::cta;" ::: "memory"); }
__device__ __forceinline__ void cluster_sync_all() {
  asm volatile("barrier.cluster.arrive.release.aligned;\nbarrier.cluster.wait.acquire.aligned;" ::: "memory");
}
__device__ __forceinline__ void cluster_sync_relaxed() {
  asm volatile("barrier.cluster.arrive.relaxed.aligned;\nbarrier.cluster.wait.aligned;" ::: "memory");
}
__device__ __forceinline__ void named_bar_sync(int id, int n) { asm volatile("bar.sync %0, %1;" ::"r"(id), "r"(n) : "memory"); }
__device__ __forceinline__ void pdl_launch() { asm volatile("griddepcontrol.launch_dependents;" ::: "memory"); }
__device__ __forceinline__ void pdl_wait() { asm volatile("griddepcontrol.wait;" ::: "memory"); }

__device__ __forceinline__ void tma_load_2d(uint32_t dst, const CUtensorMap* tm, int c0, int c1, uint32_t bar) {
  asm volatile(
      "cp.async.bulk.tensor.2d.shared::cluster.global.mbarrier::complete_tx::bytes [%0], [%1, {%3, %4}], [%2];" ::"r"(dst),
      "l"((uint64_t)tm), "r"(bar), "r"(c0), "r"(c1)
      : "memory");
}
__device__ __forceinline__ void tma_load_2d_mc(uint32_t dst, const CUtensorMap* tm, int c0, int c1, uint32_t bar, uint16_t mask) {
  asm volatile(
      "cp.async.bulk.tensor.2d.shared::cluster.global.mbarrier::complete_tx::bytes.multicast::cluster [%0], [%1, {%3, %4}], [%2], %5;" ::"r"(dst),
      "l"((uint64_t)tm), "r"(bar), "r"(c0), "r"(c1), "h"(mask)
      : "memory");
}
__device__ __forceinline__ void bulk_g2s(uint32_t dst, const void* src, uint32_t bytes, uint32_t bar) {
  asm volatile("cp.async.bulk.shared::cluster.global.mbarrier::complete_tx::bytes [%0], [%1], %2, [%3];" ::"r"(dst), "l"(src),
               "r"(bytes), "r"(bar)
               : "memory");
}
__device__ __forceinline__ void prefetch_tmap(const CUtensorMap* tm) {
  asm volatile("prefetch.tensormap [%0];" ::"l"((uint64_t)tm) : "memory");
}
__device__ __forceinline__ void wgmma_fence() { asm volatile("wgmma.fence.sync.aligned;" ::: "memory"); }
__device__ __forceinline__ void wgmma_commit() { asm volatile("wgmma.commit_group.sync.aligned;" ::: "memory"); }
template <int N>
__device__ __forceinline__ void wgmma_wait() { asm volatile("wgmma.wait_group.sync.aligned %0;" ::"n"(N) : "memory"); }

__device__ __forceinline__ uint64_t make_desc(uint32_t addr, uint32_t lbo, uint32_t sbo, uint32_t layout) {
  return (uint64_t)((addr & 0x3FFFF) >> 4) | ((uint64_t)((lbo & 0x3FFFF) >> 4) << 16) | ((uint64_t)((sbo & 0x3FFFF) >> 4) << 32) |
         ((uint64_t)layout << 62);
}
__device__ __forceinline__ uint32_t pack_bf16(float lo, float hi) {
  uint32_t r;
  asm("cvt.rn.bf16x2.f32 %0, %1, %2;" : "=r"(r) : "f"(hi), "f"(lo));
  return r;
}
__device__ __forceinline__ float bf16_round(float x) { return __bfloat162float(__float2bfloat16_rn(x)); }
__device__ __forceinline__ float bf_lo(uint32_t u) { return __uint_as_float(u << 16); }
__device__ __forceinline__ float bf_hi(uint32_t u) { return __uint_as_float(u & 0xffff0000u); }
__device__ __forceinline__ float ex2(float x) {
  float y;
  asm("ex2.approx.ftz.f32 %0, %1;" : "=f"(y) : "f"(x));
  return y;
}

__device__ __forceinline__ void wgmma_ss_n240_tb(float (&d)[120], uint64_t descA, uint64_t descB, int scaleD) {
  asm volatile("{\n.reg .pred p;\nsetp.ne.b32 p, %122, 0;\n"
    "wgmma.mma_async.sync.aligned.m64n240k16.f32.bf16.bf16 {%0, %1, %2, %3, %4, %5, %6, %7, %8, %9, %10, %11, %12, %13, %14, %15, %16, %17, %18, %19, %20, %21, %22, %23, %24, %25, %26, %27, %28, %29, %30, %31, %32, %33, %34, %35, %36, %37, %38, %39, %40, %41, %42, %43, %44, %45, %46, %47, %48, %49, %50, %51, %52, %53, %54, %55, %56, %57, %58, %59, %60, %61, %62, %63, %64, %65, %66, %67, %68, %69, %70, %71, %72, %73, %74, %75, %76, %77, %78, %79, %80, %81, %82, %83, %84, %85, %86, %87, %88, %89, %90, %91, %92, %93, %94, %95, %96, %97, %98, %99, %100, %101, %102, %103, %104, %105, %106, %107, %108, %109, %110, %111, %112, %113, %114, %115, %116, %117, %118, %119}, %120, %121, p, 1, 1, 0, 1;\n}\n"
    : "+f"(d[0]), "+f"(d[1]), "+f"(d[2]), "+f"(d[3]), "+f"(d[4]), "+f"(d[5]), "+f"(d[6]), "+f"(d[7]), "+f"(d[8]), "+f"(d[9]), "+f"(d[10]), "+f"(d[11]), "+f"(d[12]), "+f"(d[13]), "+f"(d[14]), "+f"(d[15]), "+f"(d[16]), "+f"(d[17]), "+f"(d[18]), "+f"(d[19]), "+f"(d[20]), "+f"(d[21]), "+f"(d[22]), "+f"(d[23]), "+f"(d[24]), "+f"(d[25]), "+f"(d[26]), "+f"(d[27]), "+f"(d[28]), "+f"(d[29]), "+f"(d[30]), "+f"(d[31]), "+f"(d[32]), "+f"(d[33]), "+f"(d[34]), "+f"(d[35]), "+f"(d[36]), "+f"(d[37]), "+f"(d[38]), "+f"(d[39]), "+f"(d[40]), "+f"(d[41]), "+f"(d[42]), "+f"(d[43]), "+f"(d[44]), "+f"(d[45]), "+f"(d[46]), "+f"(d[47]), "+f"(d[48]), "+f"(d[49]), "+f"(d[50]), "+f"(d[51]), "+f"(d[52]), "+f"(d[53]), "+f"(d[54]), "+f"(d[55]), "+f"(d[56]), "+f"(d[57]), "+f"(d[58]), "+f"(d[59]), "+f"(d[60]), "+f"(d[61]), "+f"(d[62]), "+f"(d[63]), "+f"(d[64]), "+f"(d[65]), "+f"(d[66]), "+f"(d[67]), "+f"(d[68]), "+f"(d[69]), "+f"(d[70]), "+f"(d[71]), "+f"(d[72]), "+f"(d[73]), "+f"(d[74]), "+f"(d[75]), "+f"(d[76]), "+f"(d[77]), "+f"(d[78]), "+f"(d[79]), "+f"(d[80]), "+f"(d[81]), "+f"(d[82]), "+f"(d[83]), "+f"(d[84]), "+f"(d[85]), "+f"(d[86]), "+f"(d[87]), "+f"(d[88]), "+f"(d[89]), "+f"(d[90]), "+f"(d[91]), "+f"(d[92]), "+f"(d[93]), "+f"(d[94]), "+f"(d[95]), "+f"(d[96]), "+f"(d[97]), "+f"(d[98]), "+f"(d[99]), "+f"(d[100]), "+f"(d[101]), "+f"(d[102]), "+f"(d[103]), "+f"(d[104]), "+f"(d[105]), "+f"(d[106]), "+f"(d[107]), "+f"(d[108]), "+f"(d[109]), "+f"(d[110]), "+f"(d[111]), "+f"(d[112]), "+f"(d[113]), "+f"(d[114]), "+f"(d[115]), "+f"(d[116]), "+f"(d[117]), "+f"(d[118]), "+f"(d[119])
    : "l"(descA), "l"(descB), "r"(scaleD));
}
__device__ __forceinline__ void wgmma_ss_n192_tb(float (&d)[96], uint64_t descA, uint64_t descB, int scaleD) {
  asm volatile("{\n.reg .pred p;\nsetp.ne.b32 p, %98, 0;\n"
    "wgmma.mma_async.sync.aligned.m64n192k16.f32.bf16.bf16 {%0, %1, %2, %3, %4, %5, %6, %7, %8, %9, %10, %11, %12, %13, %14, %15, %16, %17, %18, %19, %20, %21, %22, %23, %24, %25, %26, %27, %28, %29, %30, %31, %32, %33, %34, %35, %36, %37, %38, %39, %40, %41, %42, %43, %44, %45, %46, %47, %48, %49, %50, %51, %52, %53, %54, %55, %56, %57, %58, %59, %60, %61, %62, %63, %64, %65, %66, %67, %68, %69, %70, %71, %72, %73, %74, %75, %76, %77, %78, %79, %80, %81, %82, %83, %84, %85, %86, %87, %88, %89, %90, %91, %92, %93, %94, %95}, %96, %97, p, 1, 1, 0, 1;\n}\n"
    : "+f"(d[0]), "+f"(d[1]), "+f"(d[2]), "+f"(d[3]), "+f"(d[4]), "+f"(d[5]), "+f"(d[6]), "+f"(d[7]), "+f"(d[8]), "+f"(d[9]), "+f"(d[10]), "+f"(d[11]), "+f"(d[12]), "+f"(d[13]), "+f"(d[14]), "+f"(d[15]), "+f"(d[16]), "+f"(d[17]), "+f"(d[18]), "+f"(d[19]), "+f"(d[20]), "+f"(d[21]), "+f"(d[22]), "+f"(d[23]), "+f"(d[24]), "+f"(d[25]), "+f"(d[26]), "+f"(d[27]), "+f"(d[28]), "+f"(d[29]), "+f"(d[30]), "+f"(d[31]), "+f"(d[32]), "+f"(d[33]), "+f"(d[34]), "+f"(d[35]), "+f"(d[36]), "+f"(d[37]), "+f"(d[38]), "+f"(d[39]), "+f"(d[40]), "+f"(d[41]), "+f"(d[42]), "+f"(d[43]), "+f"(d[44]), "+f"(d[45]), "+f"(d[46]), "+f"(d[47]), "+f"(d[48]), "+f"(d[49]), "+f"(d[50]), "+f"(d[51]), "+f"(d[52]), "+f"(d[53]), "+f"(d[54]), "+f"(d[55]), "+f"(d[56]), "+f"(d[57]), "+f"(d[58]), "+f"(d[59]), "+f"(d[60]), "+f"(d[61]), "+f"(d[62]), "+f"(d[63]), "+f"(d[64]), "+f"(d[65]), "+f"(d[66]), "+f"(d[67]), "+f"(d[68]), "+f"(d[69]), "+f"(d[70]), "+f"(d[71]), "+f"(d[72]), "+f"(d[73]), "+f"(d[74]), "+f"(d[75]), "+f"(d[76]), "+f"(d[77]), "+f"(d[78]), "+f"(d[79]), "+f"(d[80]), "+f"(d[81]), "+f"(d[82]), "+f"(d[83]), "+f"(d[84]), "+f"(d[85]), "+f"(d[86]), "+f"(d[87]), "+f"(d[88]), "+f"(d[89]), "+f"(d[90]), "+f"(d[91]), "+f"(d[92]), "+f"(d[93]), "+f"(d[94]), "+f"(d[95])
    : "l"(descA), "l"(descB), "r"(scaleD));
}
__device__ __forceinline__ void wgmma_ss_n64_tb(float (&d)[32], uint64_t descA, uint64_t descB, int scaleD) {
  asm volatile("{\n.reg .pred p;\nsetp.ne.b32 p, %34, 0;\n"
    "wgmma.mma_async.sync.aligned.m64n64k16.f32.bf16.bf16 {%0, %1, %2, %3, %4, %5, %6, %7, %8, %9, %10, %11, %12, %13, %14, %15, %16, %17, %18, %19, %20, %21, %22, %23, %24, %25, %26, %27, %28, %29, %30, %31}, %32, %33, p, 1, 1, 0, 1;\n}\n"
    : "+f"(d[0]), "+f"(d[1]), "+f"(d[2]), "+f"(d[3]), "+f"(d[4]), "+f"(d[5]), "+f"(d[6]), "+f"(d[7]), "+f"(d[8]), "+f"(d[9]), "+f"(d[10]), "+f"(d[11]), "+f"(d[12]), "+f"(d[13]), "+f"(d[14]), "+f"(d[15]), "+f"(d[16]), "+f"(d[17]), "+f"(d[18]), "+f"(d[19]), "+f"(d[20]), "+f"(d[21]), "+f"(d[22]), "+f"(d[23]), "+f"(d[24]), "+f"(d[25]), "+f"(d[26]), "+f"(d[27]), "+f"(d[28]), "+f"(d[29]), "+f"(d[30]), "+f"(d[31])
    : "l"(descA), "l"(descB), "r"(scaleD));
}
__device__ __forceinline__ void wgmma_ss_n16_tb(float (&d)[8], uint64_t descA, uint64_t descB, int scaleD) {
  asm volatile("{\n.reg .pred p;\nsetp.ne.b32 p, %10, 0;\n"
    "wgmma.mma_async.sync.aligned.m64n16k16.f32.bf16.bf16 {%0, %1, %2, %3, %4, %5, %6, %7}, %8, %9, p, 1, 1, 0, 1;\n}\n"
    : "+f"(d[0]), "+f"(d[1]), "+f"(d[2]), "+f"(d[3]), "+f"(d[4]), "+f"(d[5]), "+f"(d[6]), "+f"(d[7])
    : "l"(descA), "l"(descB), "r"(scaleD));
}
__device__ __forceinline__ void wgmma_rs_n128(float (&d)[64], uint32_t a0, uint32_t a1, uint32_t a2, uint32_t a3, uint64_t descB, int scaleD) {
  asm volatile("{\n.reg .pred p;\nsetp.ne.b32 p, %69, 0;\n"
    "wgmma.mma_async.sync.aligned.m64n128k16.f32.bf16.bf16 {%0, %1, %2, %3, %4, %5, %6, %7, %8, %9, %10, %11, %12, %13, %14, %15, %16, %17, %18, %19, %20, %21, %22, %23, %24, %25, %26, %27, %28, %29, %30, %31, %32, %33, %34, %35, %36, %37, %38, %39, %40, %41, %42, %43, %44, %45, %46, %47, %48, %49, %50, %51, %52, %53, %54, %55, %56, %57, %58, %59, %60, %61, %62, %63}, {%64, %65, %66, %67}, %68, p, 1, 1, 0;\n}\n"
    : "+f"(d[0]), "+f"(d[1]), "+f"(d[2]), "+f"(d[3]), "+f"(d[4]), "+f"(d[5]), "+f"(d[6]), "+f"(d[7]), "+f"(d[8]), "+f"(d[9]), "+f"(d[10]), "+f"(d[11]), "+f"(d[12]), "+f"(d[13]), "+f"(d[14]), "+f"(d[15]), "+f"(d[16]), "+f"(d[17]), "+f"(d[18]), "+f"(d[19]), "+f"(d[20]), "+f"(d[21]), "+f"(d[22]), "+f"(d[23]), "+f"(d[24]), "+f"(d[25]), "+f"(d[26]), "+f"(d[27]), "+f"(d[28]), "+f"(d[29]), "+f"(d[30]), "+f"(d[31]), "+f"(d[32]), "+f"(d[33]), "+f"(d[34]), "+f"(d[35]), "+f"(d[36]), "+f"(d[37]), "+f"(d[38]), "+f"(d[39]), "+f"(d[40]), "+f"(d[41]), "+f"(d[42]), "+f"(d[43]), "+f"(d[44]), "+f"(d[45]), "+f"(d[46]), "+f"(d[47]), "+f"(d[48]), "+f"(d[49]), "+f"(d[50]), "+f"(d[51]), "+f"(d[52]), "+f"(d[53]), "+f"(d[54]), "+f"(d[55]), "+f"(d[56]), "+f"(d[57]), "+f"(d[58]), "+f"(d[59]), "+f"(d[60]), "+f"(d[61]), "+f"(d[62]), "+f"(d[63])
    : "r"(a0), "r"(a1), "r"(a2), "r"(a3), "l"(descB), "r"(scaleD));
}
__device__ __forceinline__ void wgmma_rs_n64(float (&d)[32], uint32_t a0, uint32_t a1, uint32_t a2, uint32_t a3, uint64_t descB, int scaleD) {
  asm volatile("{\n.reg .pred p;\nsetp.ne.b32 p, %37, 0;\n"
    "wgmma.mma_async.sync.aligned.m64n64k16.f32.bf16.bf16 {%0, %1, %2, %3, %4, %5, %6, %7, %8, %9, %10, %11, %12, %13, %14, %15, %16, %17, %18, %19, %20, %21, %22, %23, %24, %25, %26, %27, %28, %29, %30, %31}, {%32, %33, %34, %35}, %36, p, 1, 1, 0;\n}\n"
    : "+f"(d[0]), "+f"(d[1]), "+f"(d[2]), "+f"(d[3]), "+f"(d[4]), "+f"(d[5]), "+f"(d[6]), "+f"(d[7]), "+f"(d[8]), "+f"(d[9]), "+f"(d[10]), "+f"(d[11]), "+f"(d[12]), "+f"(d[13]), "+f"(d[14]), "+f"(d[15]), "+f"(d[16]), "+f"(d[17]), "+f"(d[18]), "+f"(d[19]), "+f"(d[20]), "+f"(d[21]), "+f"(d[22]), "+f"(d[23]), "+f"(d[24]), "+f"(d[25]), "+f"(d[26]), "+f"(d[27]), "+f"(d[28]), "+f"(d[29]), "+f"(d[30]), "+f"(d[31])
    : "r"(a0), "r"(a1), "r"(a2), "r"(a3), "l"(descB), "r"(scaleD));
}
__device__ __forceinline__ void wgmma_rs_n24_tb(float (&d)[12], uint32_t a0, uint32_t a1, uint32_t a2, uint32_t a3, uint64_t descB, int scaleD) {
  asm volatile("{\n.reg .pred p;\nsetp.ne.b32 p, %17, 0;\n"
    "wgmma.mma_async.sync.aligned.m64n24k16.f32.bf16.bf16 {%0, %1, %2, %3, %4, %5, %6, %7, %8, %9, %10, %11}, {%12, %13, %14, %15}, %16, p, 1, 1, 1;\n}\n"
    : "+f"(d[0]), "+f"(d[1]), "+f"(d[2]), "+f"(d[3]), "+f"(d[4]), "+f"(d[5]), "+f"(d[6]), "+f"(d[7]), "+f"(d[8]), "+f"(d[9]), "+f"(d[10]), "+f"(d[11])
    : "r"(a0), "r"(a1), "r"(a2), "r"(a3), "l"(descB), "r"(scaleD));
}


constexpr int LG_THREADS = 384;
constexpr int LG_A_BYTES = 128 * DM * 2;

template <int MODE>
struct LGCfg;
template <>
struct LGCfg<0> {
  static constexpr int BK = 32, NSLAB = 4, STAGES = 4;
};
template <>
struct LGCfg<1> {
  static constexpr int BK = 16, NSLAB = 6, STAGES = 5;
};
template <int MODE>
constexpr int lg_smem_bytes() {
  return LG_A_BYTES + LGCfg<MODE>::STAGES * LGCfg<MODE>::NSLAB * LGCfg<MODE>::BK * 128 + 128 + 1024;
}

template <int MODE>
__global__ void __launch_bounds__(LG_THREADS, 1)
ln_gemm_kernel(const __grid_constant__ CUtensorMap tmB0, const __grid_constant__ CUtensorMap tmB1, const bf16* __restrict__ xin) {
  using C = LGCfg<MODE>;
  constexpr int SLAB_BYTES = C::BK * 128;
  constexpr int STAGE_BYTES = C::NSLAB * SLAB_BYTES;
  constexpr int NKB = DM / C::BK;
  extern __shared__ uint8_t smem_raw[];
  const uint32_t sbase = (smem_u32(smem_raw) + 1023u) & ~1023u;
  const uint32_t sA = sbase;
  const uint32_t sB = sbase + LG_A_BYTES;
  const uint32_t sBar = sB + C::STAGES * STAGE_BYTES;
  const int tid = threadIdx.x, warp = tid >> 5, lane = tid & 31;
  const int rank = blockIdx.x & 1;
  const int pair = blockIdx.x >> 1;
  const int n_blk = pair & 7;
  const int m_blk = (pair >> 3) * 2 + rank;

  if (tid == 0) {
    for (int s = 0; s < C::STAGES; s++) {
      mbar_init(sBar + 8 * s, 1);
      mbar_init(sBar + 8 * (C::STAGES + s), 4);
    }
    fence_mbar_init();
  }
  pdl_launch();
  cluster_sync_all();

  if (warp >= 8) {
    asm volatile("setmaxnreg.dec.sync.aligned.u32 40;");
    if (warp == 8 && lane == 0) {
      prefetch_tmap(&tmB0);
      if (MODE == 1) prefetch_tmap(&tmB1);
      for (int kb = 0; kb < NKB; kb++) {
        const int s = kb % C::STAGES;
        const uint32_t ph = (kb / C::STAGES) & 1;
        mbar_wait(sBar + 8 * (C::STAGES + s), ph ^ 1);
        const uint32_t full = sBar + 8 * s;
        mbar_expect_tx(full, STAGE_BYTES);
        const uint32_t dst = sB + s * STAGE_BYTES;
        if (MODE == 0) {
#pragma unroll
          for (int j = 0; j < 2; j++) {
            const int sl = rank * 2 + j;
            tma_load_2d_mc(dst + sl * SLAB_BYTES, &tmB0, n_blk * 240 + sl * 64, kb * C::BK, full, (uint16_t)3);
          }
        } else {
#pragma unroll
          for (int j = 0; j < 3; j++) {
            const int sl = rank * 3 + j;
            tma_load_2d_mc(dst + sl * SLAB_BYTES, rank == 0 ? &tmB0 : &tmB1, n_blk * 192 + j * 64, kb * C::BK, full, (uint16_t)3);
          }
        }
      }
    }
  } else {
    asm volatile("setmaxnreg.inc.sync.aligned.u32 232;");
    const int wg = warp >> 2;
    const int wwarp = warp & 3;
    pdl_wait();
    {
      const int hw = lane >> 4, l16 = lane & 15;
#pragma unroll
      for (int half = 0; half < 2; half++) {
        uint4 v[4][5];
#pragma unroll
        for (int it = 0; it < 4; it++) {
          const int lrow = wg * 64 + wwarp * 16 + (half * 4 + it) * 2 + hw;
          const uint4* src = reinterpret_cast<const uint4*>(xin + (size_t)(m_blk * 128 + lrow) * DM);
#pragma unroll
          for (int j = 0; j < 5; j++) v[it][j] = __ldg(src + j * 16 + l16);
        }
#pragma unroll
        for (int it = 0; it < 4; it++) {
          const int lrow = wg * 64 + wwarp * 16 + (half * 4 + it) * 2 + hw;
          float f[40];
#pragma unroll
          for (int j = 0; j < 5; j++) {
            f[j * 8 + 0] = bf_lo(v[it][j].x); f[j * 8 + 1] = bf_hi(v[it][j].x);
            f[j * 8 + 2] = bf_lo(v[it][j].y); f[j * 8 + 3] = bf_hi(v[it][j].y);
            f[j * 8 + 4] = bf_lo(v[it][j].z); f[j * 8 + 5] = bf_hi(v[it][j].z);
            f[j * 8 + 6] = bf_lo(v[it][j].w); f[j * 8 + 7] = bf_hi(v[it][j].w);
          }
          float sum = 0.f;
#pragma unroll
          for (int i = 0; i < 40; i++) sum += f[i];
#pragma unroll
          for (int o = 1; o < 16; o <<= 1) sum += __shfl_xor_sync(0xffffffffu, sum, o);
          const float mean = sum * (1.0f / DM);
          float sq = 0.f;
#pragma unroll
          for (int i = 0; i < 40; i++) { const float d = f[i] - mean; sq += d * d; }
#pragma unroll
          for (int o = 1; o < 16; o <<= 1) sq += __shfl_xor_sync(0xffffffffu, sq, o);
          const float var_b = bf16_round(sq * (1.0f / DM));
          const float den = bf16_round(sqrtf(bf16_round(var_b + 1e-5f)));
          const float inv = 1.0f / den;
          const float mean_b = bf16_round(mean);
#pragma unroll
          for (int j = 0; j < 5; j++) {
            uint32_t w[4];
#pragma unroll
            for (int e = 0; e < 4; e++) {
              const float a = bf16_round(f[j * 8 + 2 * e] - mean_b) * inv;
              const float b = bf16_round(f[j * 8 + 2 * e + 1] - mean_b) * inv;
              w[e] = pack_bf16(a, b);
            }
            const int ch = j * 16 + l16;
            const uint32_t addr = sA + (ch >> 3) * 16384 + lrow * 128 + (((ch & 7) ^ (lrow & 7)) << 4);
            asm volatile("st.shared.v4.b32 [%0], {%1, %2, %3, %4};" ::"r"(addr), "r"(w[0]), "r"(w[1]), "r"(w[2]), "r"(w[3]) : "memory");
          }
        }
      }
    }
    fence_proxy_async();
    named_bar_sync(1 + wg, 128);

    const uint32_t aBase = sA + wg * 64 * 128;
    if (MODE == 0) {
      float acc[120];
#pragma unroll
      for (int i = 0; i < 120; i++) acc[i] = 0.f;
      for (int kb = 0; kb < NKB; kb++) {
        const int s = kb % C::STAGES;
        const uint32_t ph = (kb / C::STAGES) & 1;
        mbar_wait(sBar + 8 * s, ph);
        wgmma_fence();
#pragma unroll
        for (int ks = 0; ks < C::BK / 16; ks++) {
          const int k = kb * C::BK + ks * 16;
          const uint64_t da = make_desc(aBase + (k >> 6) * 16384 + (k & 63) * 2, 16, 1024, 1);
          const uint64_t db = make_desc(sB + s * STAGE_BYTES + ks * 2048, SLAB_BYTES, 1024, 1);
          wgmma_ss_n240_tb(acc, da, db, 1);
        }
        wgmma_commit();
        wgmma_wait<1>();
        if (kb > 0 && (tid & 127) == 0) {
          const int ps = (kb - 1) % C::STAGES;
          mbar_arrive_cluster(sBar + 8 * (C::STAGES + ps), 0);
          mbar_arrive_cluster(sBar + 8 * (C::STAGES + ps), 1);
        }
      }
      wgmma_wait<0>();
      const int g = lane >> 2, c4 = lane & 3;
      const int row0 = m_blk * 128 + wg * 64 + wwarp * 16 + g;
#pragma unroll
      for (int j = 0; j < 30; j++) {
        const int gc = n_blk * 240 + j * 8 + c4 * 2;
        const int which = gc / DM;
        const int within = gc - which * DM;
        const uint32_t p0 = pack_bf16(acc[4 * j], acc[4 * j + 1]);
        const uint32_t p1 = pack_bf16(acc[4 * j + 2], acc[4 * j + 3]);
        if (which == 0) {
          *reinterpret_cast<uint32_t*>(g_q + (size_t)row0 * DM + within) = p0;
          *reinterpret_cast<uint32_t*>(g_q + (size_t)(row0 + 8) * DM + within) = p1;
        } else {
          const int head = within / DH;
          const int d = within - head * DH;
          bf16* img = (which == 1 ? g_kimg : g_vimg) + (size_t)head * IMG_HEAD_ELEMS;
          const int off0 = (row0 >> 3) * 192 + (d >> 3) * 64 + (row0 & 7) * 8 + (d & 7);
          *reinterpret_cast<uint32_t*>(img + off0) = p0;
          *reinterpret_cast<uint32_t*>(img + off0 + 192) = p1;
          if (d == 18) {
            const uint2 pad = make_uint2(which == 1 ? 0u : 0x00003f80u, 0u);
            *reinterpret_cast<uint2*>(img + off0 + 2) = pad;
            *reinterpret_cast<uint2*>(img + off0 + 192 + 2) = pad;
          }
        }
      }
    } else {
      float accg[96], accu[96];
#pragma unroll
      for (int i = 0; i < 96; i++) { accg[i] = 0.f; accu[i] = 0.f; }
      for (int kb = 0; kb < NKB; kb++) {
        const int s = kb % C::STAGES;
        const uint32_t ph = (kb / C::STAGES) & 1;
        mbar_wait(sBar + 8 * s, ph);
        wgmma_fence();
        {
          const int k = kb * 16;
          const uint64_t da = make_desc(aBase + (k >> 6) * 16384 + (k & 63) * 2, 16, 1024, 1);
          const uint64_t dg = make_desc(sB + s * STAGE_BYTES, SLAB_BYTES, 1024, 1);
          const uint64_t du = make_desc(sB + s * STAGE_BYTES + 3 * SLAB_BYTES, SLAB_BYTES, 1024, 1);
          wgmma_ss_n192_tb(accg, da, dg, 1);
          wgmma_ss_n192_tb(accu, da, du, 1);
        }
        wgmma_commit();
        wgmma_wait<1>();
        if (kb > 0 && (tid & 127) == 0) {
          const int ps = (kb - 1) % C::STAGES;
          mbar_arrive_cluster(sBar + 8 * (C::STAGES + ps), 0);
          mbar_arrive_cluster(sBar + 8 * (C::STAGES + ps), 1);
        }
      }
      wgmma_wait<0>();
      const int g = lane >> 2, c4 = lane & 3;
      const int row0 = m_blk * 128 + wg * 64 + wwarp * 16 + g;
#pragma unroll
      for (int j = 0; j < 24; j++) {
        float r[4];
#pragma unroll
        for (int e = 0; e < 4; e++) {
          const float gt = bf16_round(accg[4 * j + e]);
          const float up = bf16_round(accu[4 * j + e]);
          r[e] = (gt * (gt > 0.f ? 1.f : 0.f)) * up;
        }
        const int col = n_blk * 192 + j * 8 + c4 * 2;
        *reinterpret_cast<uint32_t*>(g_hh + (size_t)row0 * FF + col) = pack_bf16(r[0], r[1]);
        *reinterpret_cast<uint32_t*>(g_hh + (size_t)(row0 + 8) * FF + col) = pack_bf16(r[2], r[3]);
      }
    }
  }
  __syncwarp();
  cluster_sync_relaxed();
}

constexpr int RG_THREADS = 288;
constexpr int RG_STAGES = 8;
constexpr int RG_STAGE_BYTES = 16384 + 8192 + 2048;
constexpr int RG_SMEM = RG_STAGES * RG_STAGE_BYTES + 256 + 1024;

template <int KTOT>
__global__ void __launch_bounds__(RG_THREADS, 1)
res_gemm_kernel(const __grid_constant__ CUtensorMap tmA, const __grid_constant__ CUtensorMap tmB64, const __grid_constant__ CUtensorMap tmB16,
                const bf16* __restrict__ resid, bf16* __restrict__ out) {
  constexpr int NKB = KTOT / 64;
  extern __shared__ uint8_t smem_raw[];
  const uint32_t sbase = (smem_u32(smem_raw) + 1023u) & ~1023u;
  const uint32_t sBar = sbase + RG_STAGES * RG_STAGE_BYTES;
  const int tid = threadIdx.x, warp = tid >> 5, lane = tid & 31;
  const int rank = blockIdx.x & 1;
  const int pair = blockIdx.x >> 1;
  const int m_blk = pair >> 2;
  const int n_blk = (pair & 3) * 2 + rank;
  const int n0 = n_blk * 80;

  if (tid == 0) {
    for (int s = 0; s < RG_STAGES; s++) {
      mbar_init(sBar + 8 * s, 1);
      mbar_init(sBar + 8 * (RG_STAGES + s), 4);
    }
    fence_mbar_init();
  }
  pdl_launch();
  cluster_sync_all();

  if (warp == 8) {
    if (lane == 0) {
      prefetch_tmap(&tmA); prefetch_tmap(&tmB64); prefetch_tmap(&tmB16);
      constexpr int PRE = NKB < RG_STAGES ? NKB : RG_STAGES;
      for (int kb = 0; kb < PRE; kb++) {
        const uint32_t full = sBar + 8 * kb;
        const uint32_t st = sbase + kb * RG_STAGE_BYTES;
        mbar_expect_tx(full, RG_STAGE_BYTES);
        tma_load_2d(st + 16384, &tmB64, n0, kb * 64, full);
        tma_load_2d(st + 16384 + 8192, &tmB16, n0 + 64, kb * 64, full);
      }
      pdl_wait();
      for (int kb = 0; kb < NKB; kb++) {
        const int s = kb % RG_STAGES;
        const uint32_t full = sBar + 8 * s;
        const uint32_t st = sbase + s * RG_STAGE_BYTES;
        if (kb >= PRE) {
          const uint32_t ph = (kb / RG_STAGES) & 1;
          mbar_wait(sBar + 8 * (RG_STAGES + s), ph ^ 1);
          mbar_expect_tx(full, RG_STAGE_BYTES);
          tma_load_2d(st + 16384, &tmB64, n0, kb * 64, full);
          tma_load_2d(st + 16384 + 8192, &tmB16, n0 + 64, kb * 64, full);
        }
        tma_load_2d_mc(st + rank * 8192, &tmA, kb * 64, m_blk * 128 + rank * 64, full, (uint16_t)3);
      }
    }
  } else {
    const int wg = warp >> 2, wwarp = warp & 3;
    const int g = lane >> 2, c4 = lane & 3;
    const int row0 = m_blk * 128 + wg * 64 + wwarp * 16 + g;
    pdl_wait();
    uint32_t res[20];
#pragma unroll
    for (int j = 0; j < 10; j++) {
      res[2 * j] = __ldg(reinterpret_cast<const uint32_t*>(resid + (size_t)row0 * DM + n0 + j * 8 + c4 * 2));
      res[2 * j + 1] = __ldg(reinterpret_cast<const uint32_t*>(resid + (size_t)(row0 + 8) * DM + n0 + j * 8 + c4 * 2));
    }
    float acc0[32], acc1[8];
#pragma unroll
    for (int i = 0; i < 32; i++) acc0[i] = 0.f;
#pragma unroll
    for (int i = 0; i < 8; i++) acc1[i] = 0.f;
    for (int kb = 0; kb < NKB; kb++) {
      const int s = kb % RG_STAGES;
      const uint32_t ph = (kb / RG_STAGES) & 1;
      const uint32_t st = sbase + s * RG_STAGE_BYTES;
      mbar_wait(sBar + 8 * s, ph);
      wgmma_fence();
#pragma unroll
      for (int ks = 0; ks < 4; ks++) {
        const uint64_t da = make_desc(st + wg * 8192 + ks * 32, 16, 1024, 1);
        const uint64_t db0 = make_desc(st + 16384 + ks * 2048, 8192, 1024, 1);
        const uint64_t db1 = make_desc(st + 16384 + 8192 + ks * 512, 2048, 256, 3);
        wgmma_ss_n64_tb(acc0, da, db0, 1);
        wgmma_ss_n16_tb(acc1, da, db1, 1);
      }
      wgmma_commit();
      wgmma_wait<1>();
      if (kb > 0 && (tid & 127) == 0) {
        const int ps = (kb - 1) % RG_STAGES;
        mbar_arrive_cluster(sBar + 8 * (RG_STAGES + ps), 0);
        mbar_arrive_cluster(sBar + 8 * (RG_STAGES + ps), 1);
      }
    }
    wgmma_wait<0>();
#pragma unroll
    for (int j = 0; j < 10; j++) {
      float a[4];
#pragma unroll
      for (int e = 0; e < 4; e++) a[e] = bf16_round(j < 8 ? acc0[4 * j + e] : acc1[4 * (j - 8) + e]);
      const uint32_t o0 = pack_bf16(bf_lo(res[2 * j]) + a[0], bf_hi(res[2 * j]) + a[1]);
      const uint32_t o1 = pack_bf16(bf_lo(res[2 * j + 1]) + a[2], bf_hi(res[2 * j + 1]) + a[3]);
      *reinterpret_cast<uint32_t*>(out + (size_t)row0 * DM + n0 + j * 8 + c4 * 2) = o0;
      *reinterpret_cast<uint32_t*>(out + (size_t)(row0 + 8) * DM + n0 + j * 8 + c4 * 2) = o1;
    }
  }
  __syncwarp();
  cluster_sync_relaxed();
}

constexpr int AT_THREADS = 512;
constexpr int AT_KV_BYTES = IMG_HEAD_ELEMS * 2;
constexpr int AT_SMEM = 2 * AT_KV_BYTES + 256 + 1024;
constexpr int AT_CHUNKS = 8;

__device__ __forceinline__ float exp2_poly(float s, float c64, float b64) {
  const float u = __saturatef(fmaf(s, c64, b64));
  const float MAGIC = 12582912.0f - 64.0f;
  const float r = fmaf(u, 64.0f, MAGIC);
  const float q = MAGIC - r;
  const float fr = fmaf(u, 64.0f, q);
  float p = fmaf(fr, 0.009570102207362652f, 0.05591785907745361f);
  p = fmaf(p, fr, 0.240247443318367f);
  p = fmaf(p, fr, 0.6931217908859253f);
  p = fmaf(p, fr, 0.9999992847442627f);
  return __uint_as_float(__float_as_uint(p) + (__float_as_uint(r) << 23));
}

__global__ void __launch_bounds__(AT_THREADS, 1) attn_kernel() {
  extern __shared__ uint8_t smem_raw[];
  const uint32_t sbase = (smem_u32(smem_raw) + 1023u) & ~1023u;
  const uint32_t sK = sbase, sV = sbase + AT_KV_BYTES;
  const uint32_t sBar = sV + AT_KV_BYTES;
  const int tid = threadIdx.x, warp = tid >> 5, lane = tid & 31;
  const int head = blockIdx.x >> 2, quarter = blockIdx.x & 3;
  if (tid == 0) {
    for (int i = 0; i < AT_CHUNKS; i++) mbar_init(sBar + 8 * i, 1);
    fence_mbar_init();
  }
  pdl_launch();
  __syncthreads();
  pdl_wait();
  if (tid == 0) {
    const uint8_t* kg = reinterpret_cast<const uint8_t*>(g_kimg + (size_t)head * IMG_HEAD_ELEMS);
    const uint8_t* vg = reinterpret_cast<const uint8_t*>(g_vimg + (size_t)head * IMG_HEAD_ELEMS);
    constexpr int CB = AT_KV_BYTES / AT_CHUNKS;
    for (int i = 0; i < AT_CHUNKS; i++) {
      mbar_expect_tx(sBar + 8 * i, 2 * CB);
      bulk_g2s(sK + i * CB, kg + i * CB, CB, sBar + 8 * i);
      bulk_g2s(sV + i * CB, vg + i * CB, CB, sBar + 8 * i);
    }
  }
  const int wg = warp >> 2, wwarp = warp & 3;
  const int g = lane >> 2, c4 = lane & 3;
  const float SC = 0.22360679774997896f * 1.4426950408889634f;
  const float SC64 = SC * (1.0f / 64.0f);

  for (int rep = 0; rep < 2; rep++) {
    const int row0 = quarter * 512 + (rep * 4 + wg) * 64 + wwarp * 16 + g;
    uint32_t qa[8];
    {
      const bf16* q0 = g_q + (size_t)row0 * DM + head * DH;
      const bf16* q1 = q0 + 8 * DM;
      qa[0] = *reinterpret_cast<const uint32_t*>(q0 + c4 * 2);
      qa[1] = *reinterpret_cast<const uint32_t*>(q1 + c4 * 2);
      qa[2] = *reinterpret_cast<const uint32_t*>(q0 + 8 + c4 * 2);
      qa[3] = *reinterpret_cast<const uint32_t*>(q1 + 8 + c4 * 2);
      qa[4] = c4 < 2 ? *reinterpret_cast<const uint32_t*>(q0 + 16 + c4 * 2) : 0u;
      qa[5] = c4 < 2 ? *reinterpret_cast<const uint32_t*>(q1 + 16 + c4 * 2) : 0u;
      qa[6] = 0u;
      qa[7] = 0u;
    }
    float o[12];
#pragma unroll
    for (int i = 0; i < 12; i++) o[i] = 0.f;
    float m0 = -INFINITY, m1 = -INFINITY;
#pragma unroll 1
    for (int t = 0; t < 16; t++) {
      if (rep == 0) mbar_wait(sBar + 8 * (t >> 1), 0);
      float s[64];
      wgmma_fence();
      {
        const uint64_t dk0 = make_desc(sK + t * 6144, 128, 384, 0);
        const uint64_t dk1 = make_desc(sK + t * 6144 + 256, 128, 384, 0);
        wgmma_rs_n128(s, qa[0], qa[1], qa[2], qa[3], dk0, 0);
        wgmma_rs_n128(s, qa[4], qa[5], qa[6], qa[7], dk1, 1);
      }
      wgmma_commit();
      wgmma_wait<0>();
      float mx0 = s[0], mx1 = s[2];
#pragma unroll
      for (int j = 0; j < 16; j++) {
        mx0 = fmaxf(mx0, fmaxf(s[4 * j], s[4 * j + 1]));
        mx1 = fmaxf(mx1, fmaxf(s[4 * j + 2], s[4 * j + 3]));
      }
      mx0 = fmaxf(mx0, __shfl_xor_sync(0xffffffffu, mx0, 1));
      mx1 = fmaxf(mx1, __shfl_xor_sync(0xffffffffu, mx1, 1));
      mx0 = fmaxf(mx0, __shfl_xor_sync(0xffffffffu, mx0, 2));
      mx1 = fmaxf(mx1, __shfl_xor_sync(0xffffffffu, mx1, 2));
      const float mn0 = fmaxf(m0, mx0), mn1 = fmaxf(m1, mx1);
      const float al0 = ex2((m0 - mn0) * SC), al1 = ex2((m1 - mn1) * SC);
      m0 = mn0; m1 = mn1;
      const float mc0 = -mn0 * SC, mc1 = -mn1 * SC;
      const float b0 = fmaf(mc0, 1.0f / 64.0f, 1.0f), b1 = fmaf(mc1, 1.0f / 64.0f, 1.0f);
      uint32_t p[32];
#pragma unroll
      for (int j = 0; j < 16; j++) {
        float e0, e1, e2, e3;
        e0 = ex2(fmaf(s[4 * j], SC, mc0));
        e1 = ex2(fmaf(s[4 * j + 1], SC, mc0));
        e2 = ex2(fmaf(s[4 * j + 2], SC, mc1));
        if ((j & 1) == 0) e3 = exp2_poly(s[4 * j + 3], SC64, b1);
        else { e3 = ex2(fmaf(s[4 * j + 3], SC, mc1)); e0 = exp2_poly(s[4 * j], SC64, b0); }
        p[2 * j] = pack_bf16(e0, e1);
        p[2 * j + 1] = pack_bf16(e2, e3);
      }
#pragma unroll
      for (int j = 0; j < 3; j++) {
        o[4 * j] *= al0; o[4 * j + 1] *= al0;
        o[4 * j + 2] *= al1; o[4 * j + 3] *= al1;
      }
      wgmma_fence();
#pragma unroll
      for (int kk = 0; kk < 8; kk++) {
        const uint64_t dv = make_desc(sV + t * 6144 + kk * 768, 384, 128, 0);
        wgmma_rs_n24_tb(o, p[4 * kk], p[4 * kk + 1], p[4 * kk + 2], p[4 * kk + 3], dv, 1);
      }
      wgmma_commit();
      wgmma_wait<0>();
    }
    const float l0 = __shfl_sync(0xffffffffu, o[8], (lane & ~3) | 2);
    const float l1 = __shfl_sync(0xffffffffu, o[10], (lane & ~3) | 2);
    const float i0 = 1.0f / l0, i1 = 1.0f / l1;
    bf16* o0 = g_o + (size_t)row0 * DM + head * DH;
    bf16* o1 = o0 + 8 * DM;
#pragma unroll
    for (int j = 0; j < 3; j++) {
      if (j < 2 || c4 < 2) {
        *reinterpret_cast<uint32_t*>(o0 + j * 8 + c4 * 2) = pack_bf16(o[4 * j] * i0, o[4 * j + 1] * i0);
        *reinterpret_cast<uint32_t*>(o1 + j * 8 + c4 * 2) = pack_bf16(o[4 * j + 2] * i1, o[4 * j + 3] * i1);
      }
    }
  }
}

typedef CUresult (*EncodeTiledFn)(CUtensorMap*, CUtensorMapDataType, cuuint32_t, void*, const cuuint64_t*, const cuuint64_t*,
                                  const cuuint32_t*, const cuuint32_t*, CUtensorMapInterleave, CUtensorMapSwizzle,
                                  CUtensorMapL2promotion, CUtensorMapFloatOOBfill);

static void make_map(EncodeTiledFn fn, CUtensorMap* tm, const void* ptr, uint64_t rows, uint64_t cols, uint32_t box_rows,
                     uint32_t box_cols, CUtensorMapSwizzle sw) {
  cuuint64_t dims[2] = {cols, rows};
  cuuint64_t strides[1] = {cols * 2};
  cuuint32_t box[2] = {box_cols, box_rows};
  cuuint32_t es[2] = {1, 1};
  fn(tm, CU_TENSOR_MAP_DATA_TYPE_BFLOAT16, 2, const_cast<void*>(ptr), dims, strides, box, es, CU_TENSOR_MAP_INTERLEAVE_NONE, sw,
     CU_TENSOR_MAP_L2_PROMOTION_L2_256B, CU_TENSOR_MAP_FLOAT_OOB_FILL_NONE);
}

template <typename... KArgs, typename... Args>
static void launch(void (*kern)(KArgs...), int grid, int block, int smem, int cluster, bool pdl, Args... args) {
  cudaLaunchConfig_t cfg = {};
  cfg.gridDim = dim3(grid);
  cfg.blockDim = dim3(block);
  cfg.dynamicSmemBytes = smem;
  cfg.stream = cudaStreamPerThread;
  cudaLaunchAttribute at[2];
  int n = 0;
  if (cluster > 1) {
    at[n].id = cudaLaunchAttributeClusterDimension;
    at[n].val.clusterDim.x = cluster; at[n].val.clusterDim.y = 1; at[n].val.clusterDim.z = 1;
    n++;
  }
  if (pdl) {
    at[n].id = cudaLaunchAttributeProgrammaticStreamSerialization;
    at[n].val.programmaticStreamSerializationAllowed = 1;
    n++;
  }
  cfg.attrs = at;
  cfg.numAttrs = n;
  cudaLaunchKernelEx(&cfg, kern, KArgs(args)...);
}

extern "C" void kernel_launch(void* const* d_in, const int* in_sizes, int n_in, void* d_out, int out_size) {
  const bf16* x = (const bf16*)d_in[0];
  const bf16* wqkv = (const bf16*)d_in[1];
  const bf16* wo = (const bf16*)d_in[2];
  const bf16* wg = (const bf16*)d_in[4];
  const bf16* wu = (const bf16*)d_in[5];
  const bf16* wd = (const bf16*)d_in[6];
  bf16* out = (bf16*)d_out;

  static EncodeTiledFn enc = nullptr;
  static void *p_o = nullptr, *p_h = nullptr, *p_hh = nullptr;
  if (!enc) {
    void* fn = nullptr;
    cudaDriverEntryPointQueryResult qr;
    cudaGetDriverEntryPoint("cuTensorMapEncodeTiled", &fn, cudaEnableDefault, &qr);
    enc = (EncodeTiledFn)fn;
    cudaGetSymbolAddress(&p_o, g_o);
    cudaGetSymbolAddress(&p_h, g_h);
    cudaGetSymbolAddress(&p_hh, g_hh);
    cudaFuncSetAttribute(ln_gemm_kernel<0>, cudaFuncAttributeMaxDynamicSharedMemorySize, lg_smem_bytes<0>());
    cudaFuncSetAttribute(ln_gemm_kernel<1>, cudaFuncAttributeMaxDynamicSharedMemorySize, lg_smem_bytes<1>());
    cudaFuncSetAttribute(res_gemm_kernel<DM>, cudaFuncAttributeMaxDynamicSharedMemorySize, RG_SMEM);
    cudaFuncSetAttribute(res_gemm_kernel<FF>, cudaFuncAttributeMaxDynamicSharedMemorySize, RG_SMEM);
    cudaFuncSetAttribute(attn_kernel, cudaFuncAttributeMaxDynamicSharedMemorySize, AT_SMEM);
  }
  CUtensorMap tm_wqkv, tm_wg, tm_wu, tm_wo64, tm_wo16, tm_wd64, tm_wd16, tm_o, tm_hh;
  make_map(enc, &tm_wqkv, wqkv, DM, 3 * DM, 32, 64, CU_TENSOR_MAP_SWIZZLE_128B);
  make_map(enc, &tm_wg, wg, DM, FF, 16, 64, CU_TENSOR_MAP_SWIZZLE_128B);
  make_map(enc, &tm_wu, wu, DM, FF, 16, 64, CU_TENSOR_MAP_SWIZZLE_128B);
  make_map(enc, &tm_wo64, wo, DM, DM, 64, 64, CU_TENSOR_MAP_SWIZZLE_128B);
  make_map(enc, &tm_wo16, wo, DM, DM, 64, 16, CU_TENSOR_MAP_SWIZZLE_32B);
  make_map(enc, &tm_wd64, wd, FF, DM, 64, 64, CU_TENSOR_MAP_SWIZZLE_128B);
  make_map(enc, &tm_wd16, wd, FF, DM, 64, 16, CU_TENSOR_MAP_SWIZZLE_32B);
  make_map(enc, &tm_o, p_o, SEQ, DM, 64, 64, CU_TENSOR_MAP_SWIZZLE_128B);
  make_map(enc, &tm_hh, p_hh, SEQ, FF, 64, 64, CU_TENSOR_MAP_SWIZZLE_128B);

  launch(ln_gemm_kernel<0>, 128, LG_THREADS, lg_smem_bytes<0>(), 2, false, tm_wqkv, tm_wqkv, x);
  launch(attn_kernel, 128, AT_THREADS, AT_SMEM, 1, true);
  launch(res_gemm_kernel<DM>, 128, RG_THREADS, RG_SMEM, 2, true, tm_o, tm_wo64, tm_wo16, x, (bf16*)p_h);
  launch(ln_gemm_kernel<1>, 128, LG_THREADS, lg_smem_bytes<1>(), 2, true, tm_wg, tm_wu, (const bf16*)p_h);
  launch(res_gemm_kernel<FF>, 128, RG_THREADS, RG_SMEM, 2, true, tm_hh, tm_wd64, tm_wd16, (const bf16*)p_h, out);
}
```

```cpp
#include <cuda_runtime.h>
#include <cuda_bf16.h>
#include <cuda.h>
#include <stdint.h>

typedef __nv_bfloat16 bf16;

constexpr int SEQ = 2048, DM = 640, NH = 32, DH = 20, FF = 1536;
constexpr int IMG_HEAD_ELEMS = (SEQ / 8) * 192;

__device__ __align__(1024) bf16 g_img[3 * NH * IMG_HEAD_ELEMS];
__device__ __align__(1024) bf16 g_o[SEQ * DM];
__device__ __align__(1024) bf16 g_h[SEQ * DM];
__device__ __align__(1024) bf16 g_hh[SEQ * FF];

__device__ __forceinline__ uint32_t smem_u32(const void* p) { return (uint32_t)__cvta_generic_to_shared(p); }
__device__ __forceinline__ void mbar_init(uint32_t bar, uint32_t cnt) {
  asm volatile("mbarrier.init.shared::cta.b64 [%0], %1;" ::"r"(bar), "r"(cnt) : "memory");
}
__device__ __forceinline__ void mbar_expect_tx(uint32_t bar, uint32_t bytes) {
  asm volatile("mbarrier.arrive.expect_tx.shared::cta.b64 _, [%0], %1;" ::"r"(bar), "r"(bytes) : "memory");
}
__device__ __forceinline__ void mbar_arrive(uint32_t bar) {
  asm volatile("mbarrier.arrive.shared::cta.b64 _, [%0];" ::"r"(bar) : "memory");
}
__device__ __forceinline__ void mbar_arrive_cluster(uint32_t bar, uint32_t cta) {
  asm volatile(
      "{\n.reg .b32 r;\nmapa.shared::cluster.u32 r, %0, %1;\n"
      "mbarrier.arrive.shared::cluster.b64 _, [r];\n}\n" ::"r"(bar), "r"(cta)
      : "memory");
}
__device__ __forceinline__ void mbar_wait(uint32_t bar, uint32_t parity) {
  asm volatile(
      "{\n.reg .pred p;\nLAB_WAIT:\n"
      "mbarrier.try_wait.parity.shared::cta.b64 p, [%0], %1;\n"
      "@p bra DONE;\nbra LAB_WAIT;\nDONE:\n}\n" ::"r"(bar), "r"(parity)
      : "memory");
}
__device__ __forceinline__ void mbar_wait_cluster(uint32_t bar, uint32_t parity) {
  asm volatile(
      "{\n.reg .pred p;\nLAB_WAIT:\n"
      "mbarrier.try_wait.parity.acquire.cluster.shared::cta.b64 p, [%0], %1;\n"
      "@p bra DONE;\nbra LAB_WAIT;\nDONE:\n}\n" ::"r"(bar), "r"(parity)
      : "memory");
}
__device__ __forceinline__ void fence_mbar_init() { asm volatile("fence.mbarrier_init.release.cluster;" ::: "memory"); }
__device__ __forceinline__ void fence_proxy_async() { asm volatile("fence.proxy.async.shared::cta;" ::: "memory"); }
__device__ __forceinline__ void cluster_sync_all() {
  asm volatile("barrier.cluster.arrive.release.aligned;\nbarrier.cluster.wait.acquire.aligned;" ::: "memory");
}
__device__ __forceinline__ void cluster_sync_relaxed() {
  asm volatile("barrier.cluster.arrive.relaxed.aligned;\nbarrier.cluster.wait.aligned;" ::: "memory");
}
__device__ __forceinline__ void named_bar_sync(int id, int n) { asm volatile("bar.sync %0, %1;" ::"r"(id), "r"(n) : "memory"); }
__device__ __forceinline__ void pdl_launch() { asm volatile("griddepcontrol.launch_dependents;" ::: "memory"); }
__device__ __forceinline__ void pdl_wait() { asm volatile("griddepcontrol.wait;" ::: "memory"); }

__device__ __forceinline__ void tma_load_2d(uint32_t dst, const CUtensorMap* tm, int c0, int c1, uint32_t bar) {
  asm volatile(
      "cp.async.bulk.tensor.2d.shared::cluster.global.mbarrier::complete_tx::bytes [%0], [%1, {%3, %4}], [%2];" ::"r"(dst),
      "l"((uint64_t)tm), "r"(bar), "r"(c0), "r"(c1)
      : "memory");
}
__device__ __forceinline__ void tma_load_2d_mc(uint32_t dst, const CUtensorMap* tm, int c0, int c1, uint32_t bar, uint16_t mask) {
  asm volatile(
      "cp.async.bulk.tensor.2d.shared::cluster.global.mbarrier::complete_tx::bytes.multicast::cluster [%0], [%1, {%3, %4}], [%2], %5;" ::"r"(dst),
      "l"((uint64_t)tm), "r"(bar), "r"(c0), "r"(c1), "h"(mask)
      : "memory");
}
__device__ __forceinline__ void bulk_g2s(uint32_t dst, const void* src, uint32_t bytes, uint32_t bar) {
  asm volatile("cp.async.bulk.shared::cluster.global.mbarrier::complete_tx::bytes [%0], [%1], %2, [%3];" ::"r"(dst), "l"(src),
               "r"(bytes), "r"(bar)
               : "memory");
}
__device__ __forceinline__ void bulk_s2g(void* dst, uint32_t src, uint32_t bytes) {
  asm volatile("cp.async.bulk.global.shared::cta.bulk_group [%0], [%1], %2;" ::"l"(dst), "r"(src), "r"(bytes) : "memory");
}
__device__ __forceinline__ void tma_store_2d(const CUtensorMap* tm, uint32_t src, int c0, int c1) {
  asm volatile("cp.async.bulk.tensor.2d.global.shared::cta.bulk_group [%0, {%2, %3}], [%1];" ::"l"((uint64_t)tm), "r"(src), "r"(c0), "r"(c1) : "memory");
}
__device__ __forceinline__ void bulk_commit() { asm volatile("cp.async.bulk.commit_group;" ::: "memory"); }
__device__ __forceinline__ void bulk_wait_all() { asm volatile("cp.async.bulk.wait_group 0;" ::: "memory"); }
__device__ __forceinline__ void st_shared_b32(uint32_t addr, uint32_t v) { asm volatile("st.shared.b32 [%0], %1;" ::"r"(addr), "r"(v) : "memory"); }
__device__ __forceinline__ void st_shared_v2(uint32_t addr, uint32_t a, uint32_t b) { asm volatile("st.shared.v2.b32 [%0], {%1, %2};" ::"r"(addr), "r"(a), "r"(b) : "memory"); }
__device__ __forceinline__ void prefetch_tmap(const CUtensorMap* tm) {
  asm volatile("prefetch.tensormap [%0];" ::"l"((uint64_t)tm) : "memory");
}
__device__ __forceinline__ void wgmma_fence() { asm volatile("wgmma.fence.sync.aligned;" ::: "memory"); }
__device__ __forceinline__ void wgmma_commit() { asm volatile("wgmma.commit_group.sync.aligned;" ::: "memory"); }
template <int N>
__device__ __forceinline__ void wgmma_wait() { asm volatile("wgmma.wait_group.sync.aligned %0;" ::"n"(N) : "memory"); }

__device__ __forceinline__ uint64_t make_desc(uint32_t addr, uint32_t lbo, uint32_t sbo, uint32_t layout) {
  return (uint64_t)((addr & 0x3FFFF) >> 4) | ((uint64_t)((lbo & 0x3FFFF) >> 4) << 16) | ((uint64_t)((sbo & 0x3FFFF) >> 4) << 32) |
         ((uint64_t)layout << 62);
}
__device__ __forceinline__ uint32_t pack_bf16(float lo, float hi) {
  uint32_t r;
  asm("cvt.rn.bf16x2.f32 %0, %1, %2;" : "=r"(r) : "f"(hi), "f"(lo));
  return r;
}
__device__ __forceinline__ float bf16_round(float x) { return __bfloat162float(__float2bfloat16_rn(x)); }
__device__ __forceinline__ float bf_lo(uint32_t u) { return __uint_as_float(u << 16); }
__device__ __forceinline__ float bf_hi(uint32_t u) { return __uint_as_float(u & 0xffff0000u); }
__device__ __forceinline__ float ex2(float x) {
  float y;
  asm("ex2.approx.ftz.f32 %0, %1;" : "=f"(y) : "f"(x));
  return y;
}

__device__ __forceinline__ void wgmma_ss_n240_tb(float (&d)[120], uint64_t descA, uint64_t descB, int scaleD) {
  asm volatile("{\n.reg .pred p;\nsetp.ne.b32 p, %122, 0;\n"
    "wgmma.mma_async.sync.aligned.m64n240k16.f32.bf16.bf16 {%0, %1, %2, %3, %4, %5, %6, %7, %8, %9, %10, %11, %12, %13, %14, %15, %16, %17, %18, %19, %20, %21, %22, %23, %24, %25, %26, %27, %28, %29, %30, %31, %32, %33, %34, %35, %36, %37, %38, %39, %40, %41, %42, %43, %44, %45, %46, %47, %48, %49, %50, %51, %52, %53, %54, %55, %56, %57, %58, %59, %60, %61, %62, %63, %64, %65, %66, %67, %68, %69, %70, %71, %72, %73, %74, %75, %76, %77, %78, %79, %80, %81, %82, %83, %84, %85, %86, %87, %88, %89, %90, %91, %92, %93, %94, %95, %96, %97, %98, %99, %100, %101, %102, %103, %104, %105, %106, %107, %108, %109, %110, %111, %112, %113, %114, %115, %116, %117, %118, %119}, %120, %121, p, 1, 1, 0, 1;\n}\n"
    : "+f"(d[0]), "+f"(d[1]), "+f"(d[2]), "+f"(d[3]), "+f"(d[4]), "+f"(d[5]), "+f"(d[6]), "+f"(d[7]), "+f"(d[8]), "+f"(d[9]), "+f"(d[10]), "+f"(d[11]), "+f"(d[12]), "+f"(d[13]), "+f"(d[14]), "+f"(d[15]), "+f"(d[16]), "+f"(d[17]), "+f"(d[18]), "+f"(d[19]), "+f"(d[20]), "+f"(d[21]), "+f"(d[22]), "+f"(d[23]), "+f"(d[24]), "+f"(d[25]), "+f"(d[26]), "+f"(d[27]), "+f"(d[28]), "+f"(d[29]), "+f"(d[30]), "+f"(d[31]), "+f"(d[32]), "+f"(d[33]), "+f"(d[34]), "+f"(d[35]), "+f"(d[36]), "+f"(d[37]), "+f"(d[38]), "+f"(d[39]), "+f"(d[40]), "+f"(d[41]), "+f"(d[42]), "+f"(d[43]), "+f"(d[44]), "+f"(d[45]), "+f"(d[46]), "+f"(d[47]), "+f"(d[48]), "+f"(d[49]), "+f"(d[50]), "+f"(d[51]), "+f"(d[52]), "+f"(d[53]), "+f"(d[54]), "+f"(d[55]), "+f"(d[56]), "+f"(d[57]), "+f"(d[58]), "+f"(d[59]), "+f"(d[60]), "+f"(d[61]), "+f"(d[62]), "+f"(d[63]), "+f"(d[64]), "+f"(d[65]), "+f"(d[66]), "+f"(d[67]), "+f"(d[68]), "+f"(d[69]), "+f"(d[70]), "+f"(d[71]), "+f"(d[72]), "+f"(d[73]), "+f"(d[74]), "+f"(d[75]), "+f"(d[76]), "+f"(d[77]), "+f"(d[78]), "+f"(d[79]), "+f"(d[80]), "+f"(d[81]), "+f"(d[82]), "+f"(d[83]), "+f"(d[84]), "+f"(d[85]), "+f"(d[86]), "+f"(d[87]), "+f"(d[88]), "+f"(d[89]), "+f"(d[90]), "+f"(d[91]), "+f"(d[92]), "+f"(d[93]), "+f"(d[94]), "+f"(d[95]), "+f"(d[96]), "+f"(d[97]), "+f"(d[98]), "+f"(d[99]), "+f"(d[100]), "+f"(d[101]), "+f"(d[102]), "+f"(d[103]), "+f"(d[104]), "+f"(d[105]), "+f"(d[106]), "+f"(d[107]), "+f"(d[108]), "+f"(d[109]), "+f"(d[110]), "+f"(d[111]), "+f"(d[112]), "+f"(d[113]), "+f"(d[114]), "+f"(d[115]), "+f"(d[116]), "+f"(d[117]), "+f"(d[118]), "+f"(d[119])
    : "l"(descA), "l"(descB), "r"(scaleD));
}
__device__ __forceinline__ void wgmma_ss_n192_tb(float (&d)[96], uint64_t descA, uint64_t descB, int scaleD) {
  asm volatile("{\n.reg .pred p;\nsetp.ne.b32 p, %98, 0;\n"
    "wgmma.mma_async.sync.aligned.m64n192k16.f32.bf16.bf16 {%0, %1, %2, %3, %4, %5, %6, %7, %8, %9, %10, %11, %12, %13, %14, %15, %16, %17, %18, %19, %20, %21, %22, %23, %24, %25, %26, %27, %28, %29, %30, %31, %32, %33, %34, %35, %36, %37, %38, %39, %40, %41, %42, %43, %44, %45, %46, %47, %48, %49, %50, %51, %52, %53, %54, %55, %56, %57, %58, %59, %60, %61, %62, %63, %64, %65, %66, %67, %68, %69, %70, %71, %72, %73, %74, %75, %76, %77, %78, %79, %80, %81, %82, %83, %84, %85, %86, %87, %88, %89, %90, %91, %92, %93, %94, %95}, %96, %97, p, 1, 1, 0, 1;\n}\n"
    : "+f"(d[0]), "+f"(d[1]), "+f"(d[2]), "+f"(d[3]), "+f"(d[4]), "+f"(d[5]), "+f"(d[6]), "+f"(d[7]), "+f"(d[8]), "+f"(d[9]), "+f"(d[10]), "+f"(d[11]), "+f"(d[12]), "+f"(d[13]), "+f"(d[14]), "+f"(d[15]), "+f"(d[16]), "+f"(d[17]), "+f"(d[18]), "+f"(d[19]), "+f"(d[20]), "+f"(d[21]), "+f"(d[22]), "+f"(d[23]), "+f"(d[24]), "+f"(d[25]), "+f"(d[26]), "+f"(d[27]), "+f"(d[28]), "+f"(d[29]), "+f"(d[30]), "+f"(d[31]), "+f"(d[32]), "+f"(d[33]), "+f"(d[34]), "+f"(d[35]), "+f"(d[36]), "+f"(d[37]), "+f"(d[38]), "+f"(d[39]), "+f"(d[40]), "+f"(d[41]), "+f"(d[42]), "+f"(d[43]), "+f"(d[44]), "+f"(d[45]), "+f"(d[46]), "+f"(d[47]), "+f"(d[48]), "+f"(d[49]), "+f"(d[50]), "+f"(d[51]), "+f"(d[52]), "+f"(d[53]), "+f"(d[54]), "+f"(d[55]), "+f"(d[56]), "+f"(d[57]), "+f"(d[58]), "+f"(d[59]), "+f"(d[60]), "+f"(d[61]), "+f"(d[62]), "+f"(d[63]), "+f"(d[64]), "+f"(d[65]), "+f"(d[66]), "+f"(d[67]), "+f"(d[68]), "+f"(d[69]), "+f"(d[70]), "+f"(d[71]), "+f"(d[72]), "+f"(d[73]), "+f"(d[74]), "+f"(d[75]), "+f"(d[76]), "+f"(d[77]), "+f"(d[78]), "+f"(d[79]), "+f"(d[80]), "+f"(d[81]), "+f"(d[82]), "+f"(d[83]), "+f"(d[84]), "+f"(d[85]), "+f"(d[86]), "+f"(d[87]), "+f"(d[88]), "+f"(d[89]), "+f"(d[90]), "+f"(d[91]), "+f"(d[92]), "+f"(d[93]), "+f"(d[94]), "+f"(d[95])
    : "l"(descA), "l"(descB), "r"(scaleD));
}
__device__ __forceinline__ void wgmma_ss_n64_tb(float (&d)[32], uint64_t descA, uint64_t descB, int scaleD) {
  asm volatile("{\n.reg .pred p;\nsetp.ne.b32 p, %34, 0;\n"
    "wgmma.mma_async.sync.aligned.m64n64k16.f32.bf16.bf16 {%0, %1, %2, %3, %4, %5, %6, %7, %8, %9, %10, %11, %12, %13, %14, %15, %16, %17, %18, %19, %20, %21, %22, %23, %24, %25, %26, %27, %28, %29, %30, %31}, %32, %33, p, 1, 1, 0, 1;\n}\n"
    : "+f"(d[0]), "+f"(d[1]), "+f"(d[2]), "+f"(d[3]), "+f"(d[4]), "+f"(d[5]), "+f"(d[6]), "+f"(d[7]), "+f"(d[8]), "+f"(d[9]), "+f"(d[10]), "+f"(d[11]), "+f"(d[12]), "+f"(d[13]), "+f"(d[14]), "+f"(d[15]), "+f"(d[16]), "+f"(d[17]), "+f"(d[18]), "+f"(d[19]), "+f"(d[20]), "+f"(d[21]), "+f"(d[22]), "+f"(d[23]), "+f"(d[24]), "+f"(d[25]), "+f"(d[26]), "+f"(d[27]), "+f"(d[28]), "+f"(d[29]), "+f"(d[30]), "+f"(d[31])
    : "l"(descA), "l"(descB), "r"(scaleD));
}
__device__ __forceinline__ void wgmma_ss_n16_tb(float (&d)[8], uint64_t descA, uint64_t descB, int scaleD) {
  asm volatile("{\n.reg .pred p;\nsetp.ne.b32 p, %10, 0;\n"
    "wgmma.mma_async.sync.aligned.m64n16k16.f32.bf16.bf16 {%0, %1, %2, %3, %4, %5, %6, %7}, %8, %9, p, 1, 1, 0, 1;\n}\n"
    : "+f"(d[0]), "+f"(d[1]), "+f"(d[2]), "+f"(d[3]), "+f"(d[4]), "+f"(d[5]), "+f"(d[6]), "+f"(d[7])
    : "l"(descA), "l"(descB), "r"(scaleD));
}
__device__ __forceinline__ void wgmma_rs_n128(float (&d)[64], uint32_t a0, uint32_t a1, uint32_t a2, uint32_t a3, uint64_t descB, int scaleD) {
  asm volatile("{\n.reg .pred p;\nsetp.ne.b32 p, %69, 0;\n"
    "wgmma.mma_async.sync.aligned.m64n128k16.f32.bf16.bf16 {%0, %1, %2, %3, %4, %5, %6, %7, %8, %9, %10, %11, %12, %13, %14, %15, %16, %17, %18, %19, %20, %21, %22, %23, %24, %25, %26, %27, %28, %29, %30, %31, %32, %33, %34, %35, %36, %37, %38, %39, %40, %41, %42, %43, %44, %45, %46, %47, %48, %49, %50, %51, %52, %53, %54, %55, %56, %57, %58, %59, %60, %61, %62, %63}, {%64, %65, %66, %67}, %68, p, 1, 1, 0;\n}\n"
    : "+f"(d[0]), "+f"(d[1]), "+f"(d[2]), "+f"(d[3]), "+f"(d[4]), "+f"(d[5]), "+f"(d[6]), "+f"(d[7]), "+f"(d[8]), "+f"(d[9]), "+f"(d[10]), "+f"(d[11]), "+f"(d[12]), "+f"(d[13]), "+f"(d[14]), "+f"(d[15]), "+f"(d[16]), "+f"(d[17]), "+f"(d[18]), "+f"(d[19]), "+f"(d[20]), "+f"(d[21]), "+f"(d[22]), "+f"(d[23]), "+f"(d[24]), "+f"(d[25]), "+f"(d[26]), "+f"(d[27]), "+f"(d[28]), "+f"(d[29]), "+f"(d[30]), "+f"(d[31]), "+f"(d[32]), "+f"(d[33]), "+f"(d[34]), "+f"(d[35]), "+f"(d[36]), "+f"(d[37]), "+f"(d[38]), "+f"(d[39]), "+f"(d[40]), "+f"(d[41]), "+f"(d[42]), "+f"(d[43]), "+f"(d[44]), "+f"(d[45]), "+f"(d[46]), "+f"(d[47]), "+f"(d[48]), "+f"(d[49]), "+f"(d[50]), "+f"(d[51]), "+f"(d[52]), "+f"(d[53]), "+f"(d[54]), "+f"(d[55]), "+f"(d[56]), "+f"(d[57]), "+f"(d[58]), "+f"(d[59]), "+f"(d[60]), "+f"(d[61]), "+f"(d[62]), "+f"(d[63])
    : "r"(a0), "r"(a1), "r"(a2), "r"(a3), "l"(descB), "r"(scaleD));
}
__device__ __forceinline__ void wgmma_rs_n64(float (&d)[32], uint32_t a0, uint32_t a1, uint32_t a2, uint32_t a3, uint64_t descB, int scaleD) {
  asm volatile("{\n.reg .pred p;\nsetp.ne.b32 p, %37, 0;\n"
    "wgmma.mma_async.sync.aligned.m64n64k16.f32.bf16.bf16 {%0, %1, %2, %3, %4, %5, %6, %7, %8, %9, %10, %11, %12, %13, %14, %15, %16, %17, %18, %19, %20, %21, %22, %23, %24, %25, %26, %27, %28, %29, %30, %31}, {%32, %33, %34, %35}, %36, p, 1, 1, 0;\n}\n"
    : "+f"(d[0]), "+f"(d[1]), "+f"(d[2]), "+f"(d[3]), "+f"(d[4]), "+f"(d[5]), "+f"(d[6]), "+f"(d[7]), "+f"(d[8]), "+f"(d[9]), "+f"(d[10]), "+f"(d[11]), "+f"(d[12]), "+f"(d[13]), "+f"(d[14]), "+f"(d[15]), "+f"(d[16]), "+f"(d[17]), "+f"(d[18]), "+f"(d[19]), "+f"(d[20]), "+f"(d[21]), "+f"(d[22]), "+f"(d[23]), "+f"(d[24]), "+f"(d[25]), "+f"(d[26]), "+f"(d[27]), "+f"(d[28]), "+f"(d[29]), "+f"(d[30]), "+f"(d[31])
    : "r"(a0), "r"(a1), "r"(a2), "r"(a3), "l"(descB), "r"(scaleD));
}
__device__ __forceinline__ void wgmma_rs_n24_tb(float (&d)[12], uint32_t a0, uint32_t a1, uint32_t a2, uint32_t a3, uint64_t descB, int scaleD) {
  asm volatile("{\n.reg .pred p;\nsetp.ne.b32 p, %17, 0;\n"
    "wgmma.mma_async.sync.aligned.m64n24k16.f32.bf16.bf16 {%0, %1, %2, %3, %4, %5, %6, %7, %8, %9, %10, %11}, {%12, %13, %14, %15}, %16, p, 1, 1, 1;\n}\n"
    : "+f"(d[0]), "+f"(d[1]), "+f"(d[2]), "+f"(d[3]), "+f"(d[4]), "+f"(d[5]), "+f"(d[6]), "+f"(d[7]), "+f"(d[8]), "+f"(d[9]), "+f"(d[10]), "+f"(d[11])
    : "r"(a0), "r"(a1), "r"(a2), "r"(a3), "l"(descB), "r"(scaleD));
}


constexpr int LG_THREADS = 384;
constexpr int LG_A_BYTES = 128 * DM * 2;

template <int MODE>
struct LGCfg;
template <>
struct LGCfg<0> {
  static constexpr int BK = 32, NSLAB = 4, STAGES = 4;
};
template <>
struct LGCfg<1> {
  static constexpr int BK = 16, NSLAB = 6, STAGES = 5;
};
template <int MODE>
constexpr int lg_smem_bytes() {
  return LG_A_BYTES + LGCfg<MODE>::STAGES * LGCfg<MODE>::NSLAB * LGCfg<MODE>::BK * 128 + 128 + 1024;
}

template <int MODE>
__global__ void __launch_bounds__(LG_THREADS, 1)
ln_gemm_kernel(const __grid_constant__ CUtensorMap tmB0, const __grid_constant__ CUtensorMap tmB1, const __grid_constant__ CUtensorMap tmOut,
               const bf16* __restrict__ xin) {
  using C = LGCfg<MODE>;
  constexpr int SLAB_BYTES = C::BK * 128;
  constexpr int STAGE_BYTES = C::NSLAB * SLAB_BYTES;
  constexpr int NKB = DM / C::BK;
  extern __shared__ uint8_t smem_raw[];
  const uint32_t sbase = (smem_u32(smem_raw) + 1023u) & ~1023u;
  const uint32_t sA = sbase;
  const uint32_t sB = sbase + LG_A_BYTES;
  const uint32_t sBar = sB + C::STAGES * STAGE_BYTES;
  const int tid = threadIdx.x, warp = tid >> 5, lane = tid & 31;
  const int rank = blockIdx.x & 1;
  const int pair = blockIdx.x >> 1;
  const int n_blk = pair & 7;
  const int m_blk = (pair >> 3) * 2 + rank;

  if (tid == 0) {
    for (int s = 0; s < C::STAGES; s++) {
      mbar_init(sBar + 8 * s, 1);
      mbar_init(sBar + 8 * (C::STAGES + s), 4);
    }
    fence_mbar_init();
  }
  pdl_launch();
  cluster_sync_all();

  if (warp >= 8) {
    asm volatile("setmaxnreg.dec.sync.aligned.u32 40;");
    if (warp == 8 && lane == 0) {
      prefetch_tmap(&tmB0);
      if (MODE == 1) prefetch_tmap(&tmB1);
      for (int kb = 0; kb < NKB; kb++) {
        const int s = kb % C::STAGES;
        const uint32_t ph = (kb / C::STAGES) & 1;
        mbar_wait(sBar + 8 * (C::STAGES + s), ph ^ 1);
        const uint32_t full = sBar + 8 * s;
        mbar_expect_tx(full, STAGE_BYTES);
        const uint32_t dst = sB + s * STAGE_BYTES;
        if (MODE == 0) {
#pragma unroll
          for (int j = 0; j < 2; j++) {
            const int sl = rank * 2 + j;
            tma_load_2d_mc(dst + sl * SLAB_BYTES, &tmB0, n_blk * 240 + sl * 64, kb * C::BK, full, (uint16_t)3);
          }
        } else {
#pragma unroll
          for (int j = 0; j < 3; j++) {
            const int sl = rank * 3 + j;
            tma_load_2d_mc(dst + sl * SLAB_BYTES, rank == 0 ? &tmB0 : &tmB1, n_blk * 192 + j * 64, kb * C::BK, full, (uint16_t)3);
          }
        }
      }
    }
  } else {
    asm volatile("setmaxnreg.inc.sync.aligned.u32 232;");
    const int wg = __shfl_sync(0xffffffffu, warp >> 2, 0);
    const int wwarp = warp & 3;
    pdl_wait();
    {
      const int hw = lane >> 4, l16 = lane & 15;
#pragma unroll
      for (int half = 0; half < 2; half++) {
        uint4 v[4][5];
#pragma unroll
        for (int it = 0; it < 4; it++) {
          const int lrow = wg * 64 + wwarp * 16 + (half * 4 + it) * 2 + hw;
          const uint4* src = reinterpret_cast<const uint4*>(xin + (size_t)(m_blk * 128 + lrow) * DM);
#pragma unroll
          for (int j = 0; j < 5; j++) v[it][j] = __ldg(src + j * 16 + l16);
        }
#pragma unroll
        for (int it = 0; it < 4; it++) {
          const int lrow = wg * 64 + wwarp * 16 + (half * 4 + it) * 2 + hw;
          float f[40];
#pragma unroll
          for (int j = 0; j < 5; j++) {
            f[j * 8 + 0] = bf_lo(v[it][j].x); f[j * 8 + 1] = bf_hi(v[it][j].x);
            f[j * 8 + 2] = bf_lo(v[it][j].y); f[j * 8 + 3] = bf_hi(v[it][j].y);
            f[j * 8 + 4] = bf_lo(v[it][j].z); f[j * 8 + 5] = bf_hi(v[it][j].z);
            f[j * 8 + 6] = bf_lo(v[it][j].w); f[j * 8 + 7] = bf_hi(v[it][j].w);
          }
          float sum = 0.f;
#pragma unroll
          for (int i = 0; i < 40; i++) sum += f[i];
#pragma unroll
          for (int o = 1; o < 16; o <<= 1) sum += __shfl_xor_sync(0xffffffffu, sum, o);
          const float mean = sum * (1.0f / DM);
          float sq = 0.f;
#pragma unroll
          for (int i = 0; i < 40; i++) { const float d = f[i] - mean; sq += d * d; }
#pragma unroll
          for (int o = 1; o < 16; o <<= 1) sq += __shfl_xor_sync(0xffffffffu, sq, o);
          const float var_b = bf16_round(sq * (1.0f / DM));
          const float den = bf16_round(sqrtf(bf16_round(var_b + 1e-5f)));
          const float inv = 1.0f / den;
          const float nmi = -bf16_round(mean) * inv;
#pragma unroll
          for (int j = 0; j < 5; j++) {
            uint32_t w[4];
#pragma unroll
            for (int e = 0; e < 4; e++) {
              const float a = fmaf(f[j * 8 + 2 * e], inv, nmi);
              const float b = fmaf(f[j * 8 + 2 * e + 1], inv, nmi);
              w[e] = pack_bf16(a, b);
            }
            const int ch = j * 16 + l16;
            const uint32_t addr = sA + (ch >> 3) * 16384 + lrow * 128 + (((ch & 7) ^ (lrow & 7)) << 4);
            asm volatile("st.shared.v4.b32 [%0], {%1, %2, %3, %4};" ::"r"(addr), "r"(w[0]), "r"(w[1]), "r"(w[2]), "r"(w[3]) : "memory");
          }
        }
      }
    }
    fence_proxy_async();
    named_bar_sync(1 + wg, 128);

    const uint32_t aBase = sA + wg * 64 * 128;
    if (MODE == 0) {
      float acc[120];
#pragma unroll
      for (int i = 0; i < 120; i++) acc[i] = 0.f;
      for (int kb = 0; kb < NKB; kb++) {
        const int s = kb % C::STAGES;
        const uint32_t ph = (kb / C::STAGES) & 1;
        mbar_wait(sBar + 8 * s, ph);
        wgmma_fence();
#pragma unroll
        for (int ks = 0; ks < C::BK / 16; ks++) {
          const int k = kb * C::BK + ks * 16;
          const uint64_t da = make_desc(aBase + (k >> 6) * 16384 + (k & 63) * 2, 16, 1024, 1);
          const uint64_t db = make_desc(sB + s * STAGE_BYTES + ks * 2048, SLAB_BYTES, 1024, 1);
          wgmma_ss_n240_tb(acc, da, db, 1);
        }
        wgmma_commit();
        wgmma_wait<1>();
        if (kb > 0 && (tid & 127) == 0) {
          const int ps = (kb - 1) % C::STAGES;
          mbar_arrive_cluster(sBar + 8 * (C::STAGES + ps), 0);
          mbar_arrive_cluster(sBar + 8 * (C::STAGES + ps), 1);
        }
      }
      wgmma_wait<0>();
      named_bar_sync(3, 256);
      const int g = lane >> 2, c4 = lane & 3;
      const uint32_t stg = sA + wg * (12 * 3072) + (wwarp * 2) * 384 + g * 16;
      const int hbase = n_blk * 12;
#pragma unroll
      for (int j = 0; j < 30; j++) {
        const int cb = (j * 8) % 20;
        const int hb = (j * 8) / 20;
        int d = cb + c4 * 2;
        int hl = hb;
        if (cb == 16 && c4 >= 2) { d -= 20; hl += 1; }
        const uint32_t a0 = stg + hl * 3072 + (d >> 3) * 128 + (d & 7) * 2;
        st_shared_b32(a0, pack_bf16(acc[4 * j], acc[4 * j + 1]));
        st_shared_b32(a0 + 384, pack_bf16(acc[4 * j + 2], acc[4 * j + 3]));
        if (d == 18) {
          const uint32_t pad = (hbase + hl >= 64) ? 0x00003f80u : 0u;
          st_shared_v2(a0 + 4, pad, 0u);
          st_shared_v2(a0 + 388, pad, 0u);
        }
      }
      fence_proxy_async();
      named_bar_sync(1 + wg, 128);
      if ((tid & 127) < 12) {
        const int hl = tid & 127;
        bf16* dst = g_img + (size_t)(hbase + hl) * IMG_HEAD_ELEMS + (size_t)(m_blk * 16 + wg * 8) * 192;
        bulk_s2g(dst, sA + wg * (12 * 3072) + hl * 3072, 3072);
        bulk_commit();
        bulk_wait_all();
      }
    } else {
      float accg[96], accu[96];
#pragma unroll
      for (int i = 0; i < 96; i++) { accg[i] = 0.f; accu[i] = 0.f; }
      for (int kb = 0; kb < NKB; kb++) {
        const int s = kb % C::STAGES;
        const uint32_t ph = (kb / C::STAGES) & 1;
        mbar_wait(sBar + 8 * s, ph);
        wgmma_fence();
        {
          const int k = kb * 16;
          const uint64_t da = make_desc(aBase + (k >> 6) * 16384 + (k & 63) * 2, 16, 1024, 1);
          const uint64_t dg = make_desc(sB + s * STAGE_BYTES, SLAB_BYTES, 1024, 1);
          const uint64_t du = make_desc(sB + s * STAGE_BYTES + 3 * SLAB_BYTES, SLAB_BYTES, 1024, 1);
          wgmma_ss_n192_tb(accg, da, dg, 1);
          wgmma_ss_n192_tb(accu, da, du, 1);
        }
        wgmma_commit();
        wgmma_wait<1>();
        if (kb > 0 && (tid & 127) == 0) {
          const int ps = (kb - 1) % C::STAGES;
          mbar_arrive_cluster(sBar + 8 * (C::STAGES + ps), 0);
          mbar_arrive_cluster(sBar + 8 * (C::STAGES + ps), 1);
        }
      }
      wgmma_wait<0>();
      named_bar_sync(3, 256);
      const int g = lane >> 2, c4 = lane & 3;
      const uint32_t stg = sA + wg * 24576 + (wwarp * 16 + g) * 128 + c4 * 4;
#pragma unroll
      for (int j = 0; j < 24; j++) {
        uint32_t pk[2];
#pragma unroll
        for (int h = 0; h < 2; h++) {
          const uint32_t gp = pack_bf16(accg[4 * j + 2 * h], accg[4 * j + 2 * h + 1]);
          const uint32_t up = pack_bf16(accu[4 * j + 2 * h], accu[4 * j + 2 * h + 1]);
          const float g0 = bf_lo(gp), g1 = bf_hi(gp);
          const float r0 = (g0 * (g0 > 0.f ? 1.f : 0.f)) * bf_lo(up);
          const float r1 = (g1 * (g1 > 0.f ? 1.f : 0.f)) * bf_hi(up);
          pk[h] = pack_bf16(r0, r1);
        }
        const uint32_t a0 = stg + (j >> 3) * 8192 + (((j & 7) ^ g) << 4);
        st_shared_b32(a0, pk[0]);
        st_shared_b32(a0 + 1024, pk[1]);
      }
      fence_proxy_async();
      named_bar_sync(1 + wg, 128);
      if ((tid & 127) == 0) {
#pragma unroll
        for (int sl = 0; sl < 3; sl++) tma_store_2d(&tmOut, sA + wg * 24576 + sl * 8192, n_blk * 192 + sl * 64, m_blk * 128 + wg * 64);
        bulk_commit();
        bulk_wait_all();
      }
    }
  }
  __syncwarp();
  cluster_sync_relaxed();
}

constexpr int RG_THREADS = 288;
constexpr int RG_STAGES = 8;
constexpr int RG_STAGE_BYTES = 16384 + 8192 + 2048;
constexpr int RG_SMEM = RG_STAGES * RG_STAGE_BYTES + 256 + 1024;

template <int KTOT>
__global__ void __launch_bounds__(RG_THREADS, 1)
res_gemm_kernel(const __grid_constant__ CUtensorMap tmA, const __grid_constant__ CUtensorMap tmB64, const __grid_constant__ CUtensorMap tmB16,
                const bf16* __restrict__ resid, bf16* __restrict__ out) {
  constexpr int NKB = KTOT / 64;
  extern __shared__ uint8_t smem_raw[];
  const uint32_t sbase = (smem_u32(smem_raw) + 1023u) & ~1023u;
  const uint32_t sBar = sbase + RG_STAGES * RG_STAGE_BYTES;
  const int tid = threadIdx.x, warp = tid >> 5, lane = tid & 31;
  const int rank = blockIdx.x & 1;
  const int pair = blockIdx.x >> 1;
  const int m_blk = pair >> 2;
  const int n_blk = (pair & 3) * 2 + rank;
  const int n0 = n_blk * 80;

  if (tid == 0) {
    for (int s = 0; s < RG_STAGES; s++) {
      mbar_init(sBar + 8 * s, 1);
      mbar_init(sBar + 8 * (RG_STAGES + s), 4);
    }
    fence_mbar_init();
  }
  pdl_launch();
  cluster_sync_all();

  if (warp == 8) {
    if (lane == 0) {
      prefetch_tmap(&tmA); prefetch_tmap(&tmB64); prefetch_tmap(&tmB16);
      constexpr int PRE = NKB < RG_STAGES ? NKB : RG_STAGES;
      for (int kb = 0; kb < PRE; kb++) {
        const uint32_t full = sBar + 8 * kb;
        const uint32_t st = sbase + kb * RG_STAGE_BYTES;
        mbar_expect_tx(full, RG_STAGE_BYTES);
        tma_load_2d(st + 16384, &tmB64, n0, kb * 64, full);
        tma_load_2d(st + 16384 + 8192, &tmB16, n0 + 64, kb * 64, full);
      }
      pdl_wait();
      for (int kb = 0; kb < NKB; kb++) {
        const int s = kb % RG_STAGES;
        const uint32_t full = sBar + 8 * s;
        const uint32_t st = sbase + s * RG_STAGE_BYTES;
        if (kb >= PRE) {
          const uint32_t ph = (kb / RG_STAGES) & 1;
          mbar_wait(sBar + 8 * (RG_STAGES + s), ph ^ 1);
          mbar_expect_tx(full, RG_STAGE_BYTES);
          tma_load_2d(st + 16384, &tmB64, n0, kb * 64, full);
          tma_load_2d(st + 16384 + 8192, &tmB16, n0 + 64, kb * 64, full);
        }
        tma_load_2d_mc(st + rank * 8192, &tmA, kb * 64, m_blk * 128 + rank * 64, full, (uint16_t)3);
      }
    }
  } else {
    const int wg = __shfl_sync(0xffffffffu, warp >> 2, 0), wwarp = warp & 3;
    const int g = lane >> 2, c4 = lane & 3;
    const int row0 = m_blk * 128 + wg * 64 + wwarp * 16 + g;
    pdl_wait();
    uint32_t res[20];
#pragma unroll
    for (int j = 0; j < 10; j++) {
      res[2 * j] = __ldg(reinterpret_cast<const uint32_t*>(resid + (size_t)row0 * DM + n0 + j * 8 + c4 * 2));
      res[2 * j + 1] = __ldg(reinterpret_cast<const uint32_t*>(resid + (size_t)(row0 + 8) * DM + n0 + j * 8 + c4 * 2));
    }
    float acc0[32], acc1[8];
#pragma unroll
    for (int i = 0; i < 32; i++) acc0[i] = 0.f;
#pragma unroll
    for (int i = 0; i < 8; i++) acc1[i] = 0.f;
    const uint64_t da_base = make_desc(sbase + wg * 8192, 16, 1024, 1);
    const uint64_t db0_base = make_desc(sbase + 16384, 8192, 1024, 1);
    const uint64_t db1_base = make_desc(sbase + 16384 + 8192, 2048, 256, 3);
    for (int kb = 0; kb < NKB; kb++) {
      const int s = kb % RG_STAGES;
      const uint32_t ph = (kb / RG_STAGES) & 1;
      const uint64_t so = (uint64_t)(uint32_t)(s * (RG_STAGE_BYTES >> 4));
      mbar_wait(sBar + 8 * s, ph);
      wgmma_fence();
#pragma unroll
      for (int ks = 0; ks < 4; ks++) {
        wgmma_ss_n64_tb(acc0, da_base + so + ks * 2, db0_base + so + ks * 128, 1);
        wgmma_ss_n16_tb(acc1, da_base + so + ks * 2, db1_base + so + ks * 32, 1);
      }
      wgmma_commit();
      wgmma_wait<1>();
      if (kb > 0 && (tid & 127) == 0) {
        const int ps = (kb - 1) % RG_STAGES;
        mbar_arrive_cluster(sBar + 8 * (RG_STAGES + ps), 0);
        mbar_arrive_cluster(sBar + 8 * (RG_STAGES + ps), 1);
      }
    }
    wgmma_wait<0>();
#pragma unroll
    for (int j = 0; j < 10; j++) {
      float a[4];
#pragma unroll
      for (int e = 0; e < 4; e++) a[e] = bf16_round(j < 8 ? acc0[4 * j + e] : acc1[4 * (j - 8) + e]);
      const uint32_t o0 = pack_bf16(bf_lo(res[2 * j]) + a[0], bf_hi(res[2 * j]) + a[1]);
      const uint32_t o1 = pack_bf16(bf_lo(res[2 * j + 1]) + a[2], bf_hi(res[2 * j + 1]) + a[3]);
      *reinterpret_cast<uint32_t*>(out + (size_t)row0 * DM + n0 + j * 8 + c4 * 2) = o0;
      *reinterpret_cast<uint32_t*>(out + (size_t)(row0 + 8) * DM + n0 + j * 8 + c4 * 2) = o1;
    }
  }
  __syncwarp();
  cluster_sync_relaxed();
}

constexpr int AT_THREADS = 512;
constexpr int AT_KV_BYTES = IMG_HEAD_ELEMS * 2;
constexpr int AT_SMEM = 2 * AT_KV_BYTES + 256 + 1024;
constexpr int AT_CHUNKS = 8;

__device__ __forceinline__ float exp2_poly(float s, float c64, float b64) {
  const float u = __saturatef(fmaf(s, c64, b64));
  const float MAGIC = 12582912.0f - 64.0f;
  const float r = fmaf(u, 64.0f, MAGIC);
  const float q = MAGIC - r;
  const float fr = fmaf(u, 64.0f, q);
  float p = fmaf(fr, 0.009570102207362652f, 0.05591785907745361f);
  p = fmaf(p, fr, 0.240247443318367f);
  p = fmaf(p, fr, 0.6931217908859253f);
  p = fmaf(p, fr, 0.9999992847442627f);
  return __uint_as_float(__float_as_uint(p) + (__float_as_uint(r) << 23));
}

__global__ void __launch_bounds__(AT_THREADS, 1) attn_kernel() {
  extern __shared__ uint8_t smem_raw[];
  const uint32_t sbase = (smem_u32(smem_raw) + 1023u) & ~1023u;
  const uint32_t sK = sbase, sV = sbase + AT_KV_BYTES;
  const uint32_t sBar = sV + AT_KV_BYTES;
  const int tid = threadIdx.x, warp = tid >> 5, lane = tid & 31;
  const int head = blockIdx.x >> 2, quarter = blockIdx.x & 3;
  if (tid == 0) {
    for (int i = 0; i < AT_CHUNKS; i++) mbar_init(sBar + 8 * i, 1);
    fence_mbar_init();
  }
  pdl_launch();
  __syncthreads();
  pdl_wait();
  if (tid == 0) {
    const uint8_t* kg = reinterpret_cast<const uint8_t*>(g_img + (size_t)(32 + head) * IMG_HEAD_ELEMS);
    const uint8_t* vg = reinterpret_cast<const uint8_t*>(g_img + (size_t)(64 + head) * IMG_HEAD_ELEMS);
    constexpr int CB = AT_KV_BYTES / AT_CHUNKS;
    for (int i = 0; i < AT_CHUNKS; i++) {
      mbar_expect_tx(sBar + 8 * i, 2 * CB);
      bulk_g2s(sK + i * CB, kg + i * CB, CB, sBar + 8 * i);
      bulk_g2s(sV + i * CB, vg + i * CB, CB, sBar + 8 * i);
    }
  }
  const int wg = warp >> 2, wwarp = warp & 3;
  const int g = lane >> 2, c4 = lane & 3;
  const float SC = 0.22360679774997896f * 1.4426950408889634f;
  const float SC64 = SC * (1.0f / 64.0f);

  for (int rep = 0; rep < 2; rep++) {
    const int row0 = quarter * 512 + (rep * 4 + wg) * 64 + wwarp * 16 + g;
    uint32_t qa[8];
    {
      const bf16* q0 = g_img + (size_t)head * IMG_HEAD_ELEMS + (size_t)(row0 >> 3) * 192 + g * 8 + c4 * 2;
      const bf16* q1 = q0 + 192;
      qa[0] = *reinterpret_cast<const uint32_t*>(q0);
      qa[1] = *reinterpret_cast<const uint32_t*>(q1);
      qa[2] = *reinterpret_cast<const uint32_t*>(q0 + 64);
      qa[3] = *reinterpret_cast<const uint32_t*>(q1 + 64);
      qa[4] = *reinterpret_cast<const uint32_t*>(q0 + 128);
      qa[5] = *reinterpret_cast<const uint32_t*>(q1 + 128);
      qa[6] = 0u;
      qa[7] = 0u;
    }
    float o[12];
#pragma unroll
    for (int i = 0; i < 12; i++) o[i] = 0.f;
    float m0 = -INFINITY, m1 = -INFINITY;
#pragma unroll 1
    for (int t = 0; t < 16; t++) {
      if (rep == 0) mbar_wait(sBar + 8 * (t >> 1), 0);
      float s[64];
      wgmma_fence();
      {
        const uint64_t dk0 = make_desc(sK + t * 6144, 128, 384, 0);
        const uint64_t dk1 = make_desc(sK + t * 6144 + 256, 128, 384, 0);
        wgmma_rs_n128(s, qa[0], qa[1], qa[2], qa[3], dk0, 0);
        wgmma_rs_n128(s, qa[4], qa[5], qa[6], qa[7], dk1, 1);
      }
      wgmma_commit();
      wgmma_wait<0>();
      float mx0 = s[0], mx1 = s[2];
#pragma unroll
      for (int j = 0; j < 16; j++) {
        mx0 = fmaxf(mx0, fmaxf(s[4 * j], s[4 * j + 1]));
        mx1 = fmaxf(mx1, fmaxf(s[4 * j + 2], s[4 * j + 3]));
      }
      mx0 = fmaxf(mx0, __shfl_xor_sync(0xffffffffu, mx0, 1));
      mx1 = fmaxf(mx1, __shfl_xor_sync(0xffffffffu, mx1, 1));
      mx0 = fmaxf(mx0, __shfl_xor_sync(0xffffffffu, mx0, 2));
      mx1 = fmaxf(mx1, __shfl_xor_sync(0xffffffffu, mx1, 2));
      const float mn0 = fmaxf(m0, mx0), mn1 = fmaxf(m1, mx1);
      const float al0 = ex2((m0 - mn0) * SC), al1 = ex2((m1 - mn1) * SC);
      m0 = mn0; m1 = mn1;
      const float mc0 = -mn0 * SC, mc1 = -mn1 * SC;
      const float b0 = fmaf(mc0, 1.0f / 64.0f, 1.0f), b1 = fmaf(mc1, 1.0f / 64.0f, 1.0f);
      uint32_t p[32];
#pragma unroll
      for (int j = 0; j < 16; j++) {
        float e0, e1, e2, e3;
        e0 = ex2(fmaf(s[4 * j], SC, mc0));
        e1 = ex2(fmaf(s[4 * j + 1], SC, mc0));
        e2 = ex2(fmaf(s[4 * j + 2], SC, mc1));
        if ((j & 1) == 0) e3 = exp2_poly(s[4 * j + 3], SC64, b1);
        else { e3 = ex2(fmaf(s[4 * j + 3], SC, mc1)); e0 = exp2_poly(s[4 * j], SC64, b0); }
        p[2 * j] = pack_bf16(e0, e1);
        p[2 * j + 1] = pack_bf16(e2, e3);
      }
#pragma unroll
      for (int j = 0; j < 3; j++) {
        o[4 * j] *= al0; o[4 * j + 1] *= al0;
        o[4 * j + 2] *= al1; o[4 * j + 3] *= al1;
      }
      wgmma_fence();
#pragma unroll
      for (int kk = 0; kk < 8; kk++) {
        const uint64_t dv = make_desc(sV + t * 6144 + kk * 768, 384, 128, 0);
        wgmma_rs_n24_tb(o, p[4 * kk], p[4 * kk + 1], p[4 * kk + 2], p[4 * kk + 3], dv, 1);
      }
      wgmma_commit();
      wgmma_wait<0>();
    }
    const float l0 = __shfl_sync(0xffffffffu, o[8], (lane & ~3) | 2);
    const float l1 = __shfl_sync(0xffffffffu, o[10], (lane & ~3) | 2);
    const float i0 = 1.0f / l0, i1 = 1.0f / l1;
    bf16* o0 = g_o + (size_t)row0 * DM + head * DH;
    bf16* o1 = o0 + 8 * DM;
#pragma unroll
    for (int j = 0; j < 3; j++) {
      if (j < 2 || c4 < 2) {
        *reinterpret_cast<uint32_t*>(o0 + j * 8 + c4 * 2) = pack_bf16(o[4 * j] * i0, o[4 * j + 1] * i0);
        *reinterpret_cast<uint32_t*>(o1 + j * 8 + c4 * 2) = pack_bf16(o[4 * j + 2] * i1, o[4 * j + 3] * i1);
      }
    }
  }
}

typedef CUresult (*EncodeTiledFn)(CUtensorMap*, CUtensorMapDataType, cuuint32_t, void*, const cuuint64_t*, const cuuint64_t*,
                                  const cuuint32_t*, const cuuint32_t*, CUtensorMapInterleave, CUtensorMapSwizzle,
                                  CUtensorMapL2promotion, CUtensorMapFloatOOBfill);

static void make_map(EncodeTiledFn fn, CUtensorMap* tm, const void* ptr, uint64_t rows, uint64_t cols, uint32_t box_rows,
                     uint32_t box_cols, CUtensorMapSwizzle sw) {
  cuuint64_t dims[2] = {cols, rows};
  cuuint64_t strides[1] = {cols * 2};
  cuuint32_t box[2] = {box_cols, box_rows};
  cuuint32_t es[2] = {1, 1};
  fn(tm, CU_TENSOR_MAP_DATA_TYPE_BFLOAT16, 2, const_cast<void*>(ptr), dims, strides, box, es, CU_TENSOR_MAP_INTERLEAVE_NONE, sw,
     CU_TENSOR_MAP_L2_PROMOTION_L2_256B, CU_TENSOR_MAP_FLOAT_OOB_FILL_NONE);
}

template <typename... KArgs, typename... Args>
static void launch(void (*kern)(KArgs...), int grid, int block, int smem, int cluster, bool pdl, Args... args) {
  cudaLaunchConfig_t cfg = {};
  cfg.gridDim = dim3(grid);
  cfg.blockDim = dim3(block);
  cfg.dynamicSmemBytes = smem;
  cfg.stream = cudaStreamPerThread;
  cudaLaunchAttribute at[2];
  int n = 0;
  if (cluster > 1) {
    at[n].id = cudaLaunchAttributeClusterDimension;
    at[n].val.clusterDim.x = cluster; at[n].val.clusterDim.y = 1; at[n].val.clusterDim.z = 1;
    n++;
  }
  if (pdl) {
    at[n].id = cudaLaunchAttributeProgrammaticStreamSerialization;
    at[n].val.programmaticStreamSerializationAllowed = 1;
    n++;
  }
  cfg.attrs = at;
  cfg.numAttrs = n;
  cudaLaunchKernelEx(&cfg, kern, KArgs(args)...);
}

extern "C" void kernel_launch(void* const* d_in, const int* in_sizes, int n_in, void* d_out, int out_size) {
  const bf16* x = (const bf16*)d_in[0];
  const bf16* wqkv = (const bf16*)d_in[1];
  const bf16* wo = (const bf16*)d_in[2];
  const bf16* wg = (const bf16*)d_in[4];
  const bf16* wu = (const bf16*)d_in[5];
  const bf16* wd = (const bf16*)d_in[6];
  bf16* out = (bf16*)d_out;

  static EncodeTiledFn enc = nullptr;
  static void *p_o = nullptr, *p_h = nullptr, *p_hh = nullptr;
  if (!enc) {
    void* fn = nullptr;
    cudaDriverEntryPointQueryResult qr;
    cudaGetDriverEntryPoint("cuTensorMapEncodeTiled", &fn, cudaEnableDefault, &qr);
    enc = (EncodeTiledFn)fn;
    cudaGetSymbolAddress(&p_o, g_o);
    cudaGetSymbolAddress(&p_h, g_h);
    cudaGetSymbolAddress(&p_hh, g_hh);
    cudaFuncSetAttribute(ln_gemm_kernel<0>, cudaFuncAttributeMaxDynamicSharedMemorySize, lg_smem_bytes<0>());
    cudaFuncSetAttribute(ln_gemm_kernel<1>, cudaFuncAttributeMaxDynamicSharedMemorySize, lg_smem_bytes<1>());
    cudaFuncSetAttribute(res_gemm_kernel<DM>, cudaFuncAttributeMaxDynamicSharedMemorySize, RG_SMEM);
    cudaFuncSetAttribute(res_gemm_kernel<FF>, cudaFuncAttributeMaxDynamicSharedMemorySize, RG_SMEM);
    cudaFuncSetAttribute(attn_kernel, cudaFuncAttributeMaxDynamicSharedMemorySize, AT_SMEM);
  }
  CUtensorMap tm_wqkv, tm_wg, tm_wu, tm_wo64, tm_wo16, tm_wd64, tm_wd16, tm_o, tm_hh;
  make_map(enc, &tm_wqkv, wqkv, DM, 3 * DM, 32, 64, CU_TENSOR_MAP_SWIZZLE_128B);
  make_map(enc, &tm_wg, wg, DM, FF, 16, 64, CU_TENSOR_MAP_SWIZZLE_128B);
  make_map(enc, &tm_wu, wu, DM, FF, 16, 64, CU_TENSOR_MAP_SWIZZLE_128B);
  make_map(enc, &tm_wo64, wo, DM, DM, 64, 64, CU_TENSOR_MAP_SWIZZLE_128B);
  make_map(enc, &tm_wo16, wo, DM, DM, 64, 16, CU_TENSOR_MAP_SWIZZLE_32B);
  make_map(enc, &tm_wd64, wd, FF, DM, 64, 64, CU_TENSOR_MAP_SWIZZLE_128B);
  make_map(enc, &tm_wd16, wd, FF, DM, 64, 16, CU_TENSOR_MAP_SWIZZLE_32B);
  make_map(enc, &tm_o, p_o, SEQ, DM, 64, 64, CU_TENSOR_MAP_SWIZZLE_128B);
  make_map(enc, &tm_hh, p_hh, SEQ, FF, 64, 64, CU_TENSOR_MAP_SWIZZLE_128B);

  launch(ln_gemm_kernel<0>, 128, LG_THREADS, lg_smem_bytes<0>(), 2, false, tm_wqkv, tm_wqkv, tm_wqkv, x);
  launch(attn_kernel, 128, AT_THREADS, AT_SMEM, 1, true);
  launch(res_gemm_kernel<DM>, 128, RG_THREADS, RG_SMEM, 2, true, tm_o, tm_wo64, tm_wo16, x, (bf16*)p_h);
  launch(ln_gemm_kernel<1>, 128, LG_THREADS, lg_smem_bytes<1>(), 2, true, tm_wg, tm_wu, tm_hh, (const bf16*)p_h);
  launch(res_gemm_kernel<FF>, 128, RG_THREADS, RG_SMEM, 2, true, tm_hh, tm_wd64, tm_wd16, (const bf16*)p_h, out);
}
```

```cpp
#include <cuda_runtime.h>
#include <cuda_bf16.h>
#include <cuda.h>
#include <stdint.h>

typedef __nv_bfloat16 bf16;

constexpr int SEQ = 2048, DM = 640, NH = 32, DH = 20, FF = 1536;
constexpr int IMG_HEAD_ELEMS = (SEQ / 8) * 192;

__device__ __align__(1024) bf16 g_img[3 * NH * IMG_HEAD_ELEMS];
__device__ __align__(1024) bf16 g_o[SEQ * DM];
__device__ __align__(1024) bf16 g_h[SEQ * DM];
__device__ __align__(1024) bf16 g_hh[SEQ * FF];

__device__ __forceinline__ uint32_t smem_u32(const void* p) { return (uint32_t)__cvta_generic_to_shared(p); }
__device__ __forceinline__ void mbar_init(uint32_t bar, uint32_t cnt) {
  asm volatile("mbarrier.init.shared::cta.b64 [%0], %1;" ::"r"(bar), "r"(cnt) : "memory");
}
__device__ __forceinline__ void mbar_expect_tx(uint32_t bar, uint32_t bytes) {
  asm volatile("mbarrier.arrive.expect_tx.shared::cta.b64 _, [%0], %1;" ::"r"(bar), "r"(bytes) : "memory");
}
__device__ __forceinline__ void mbar_arrive(uint32_t bar) {
  asm volatile("mbarrier.arrive.shared::cta.b64 _, [%0];" ::"r"(bar) : "memory");
}
__device__ __forceinline__ void mbar_arrive_cluster(uint32_t bar, uint32_t cta) {
  asm volatile(
      "{\n.reg .b32 r;\nmapa.shared::cluster.u32 r, %0, %1;\n"
      "mbarrier.arrive.shared::cluster.b64 _, [r];\n}\n" ::"r"(bar), "r"(cta)
      : "memory");
}
__device__ __forceinline__ void mbar_wait(uint32_t bar, uint32_t parity) {
  asm volatile(
      "{\n.reg .pred p;\nLAB_WAIT:\n"
      "mbarrier.try_wait.parity.shared::cta.b64 p, [%0], %1;\n"
      "@p bra DONE;\nbra LAB_WAIT;\nDONE:\n}\n" ::"r"(bar), "r"(parity)
      : "memory");
}
__device__ __forceinline__ void mbar_wait_cluster(uint32_t bar, uint32_t parity) {
  asm volatile(
      "{\n.reg .pred p;\nLAB_WAIT:\n"
      "mbarrier.try_wait.parity.acquire.cluster.shared::cta.b64 p, [%0], %1;\n"
      "@p bra DONE;\nbra LAB_WAIT;\nDONE:\n}\n" ::"r"(bar), "r"(parity)
      : "memory");
}
__device__ __forceinline__ void fence_mbar_init() { asm volatile("fence.mbarrier_init.release.cluster;" ::: "memory"); }
__device__ __forceinline__ void fence_proxy_async() { asm volatile("fence.proxy.async.shared::cta;" ::: "memory"); }
__device__ __forceinline__ void cluster_sync_all() {
  asm volatile("barrier.cluster.arrive.release.aligned;\nbarrier.cluster.wait.acquire.aligned;" ::: "memory");
}
__device__ __forceinline__ void cluster_sync_relaxed() {
  asm volatile("barrier.cluster.arrive.relaxed.aligned;\nbarrier.cluster.wait.aligned;" ::: "memory");
}
__device__ __forceinline__ void named_bar_sync(int id, int n) { asm volatile("bar.sync %0, %1;" ::"r"(id), "r"(n) : "memory"); }
__device__ __forceinline__ void pdl_launch() { asm volatile("griddepcontrol.launch_dependents;" ::: "memory"); }
__device__ __forceinline__ void pdl_wait() { asm volatile("griddepcontrol.wait;" ::: "memory"); }

__device__ __forceinline__ void tma_load_2d(uint32_t dst, const CUtensorMap* tm, int c0, int c1, uint32_t bar) {
  asm volatile(
      "cp.async.bulk.tensor.2d.shared::cluster.global.mbarrier::complete_tx::bytes [%0], [%1, {%3, %4}], [%2];" ::"r"(dst),
      "l"((uint64_t)tm), "r"(bar), "r"(c0), "r"(c1)
      : "memory");
}
__device__ __forceinline__ void tma_load_2d_mc(uint32_t dst, const CUtensorMap* tm, int c0, int c1, uint32_t bar, uint16_t mask) {
  asm volatile(
      "cp.async.bulk.tensor.2d.shared::cluster.global.mbarrier::complete_tx::bytes.multicast::cluster [%0], [%1, {%3, %4}], [%2], %5;" ::"r"(dst),
      "l"((uint64_t)tm), "r"(bar), "r"(c0), "r"(c1), "h"(mask)
      : "memory");
}
__device__ __forceinline__ void bulk_g2s(uint32_t dst, const void* src, uint32_t bytes, uint32_t bar) {
  asm volatile("cp.async.bulk.shared::cluster.global.mbarrier::complete_tx::bytes [%0], [%1], %2, [%3];" ::"r"(dst), "l"(src),
               "r"(bytes), "r"(bar)
               : "memory");
}
__device__ __forceinline__ void bulk_s2g(void* dst, uint32_t src, uint32_t bytes) {
  asm volatile("cp.async.bulk.global.shared::cta.bulk_group [%0], [%1], %2;" ::"l"(dst), "r"(src), "r"(bytes) : "memory");
}
__device__ __forceinline__ void tma_store_2d(const CUtensorMap* tm, uint32_t src, int c0, int c1) {
  asm volatile("cp.async.bulk.tensor.2d.global.shared::cta.bulk_group [%0, {%2, %3}], [%1];" ::"l"((uint64_t)tm), "r"(src), "r"(c0), "r"(c1) : "memory");
}
__device__ __forceinline__ void bulk_commit() { asm volatile("cp.async.bulk.commit_group;" ::: "memory"); }
__device__ __forceinline__ void bulk_wait_all() { asm volatile("cp.async.bulk.wait_group 0;" ::: "memory"); }
__device__ __forceinline__ void st_shared_b32(uint32_t addr, uint32_t v) { asm volatile("st.shared.b32 [%0], %1;" ::"r"(addr), "r"(v) : "memory"); }
__device__ __forceinline__ void st_shared_v2(uint32_t addr, uint32_t a, uint32_t b) { asm volatile("st.shared.v2.b32 [%0], {%1, %2};" ::"r"(addr), "r"(a), "r"(b) : "memory"); }
__device__ __forceinline__ void prefetch_tmap(const CUtensorMap* tm) {
  asm volatile("prefetch.tensormap [%0];" ::"l"((uint64_t)tm) : "memory");
}
__device__ __forceinline__ void wgmma_fence() { asm volatile("wgmma.fence.sync.aligned;" ::: "memory"); }
__device__ __forceinline__ void wgmma_commit() { asm volatile("wgmma.commit_group.sync.aligned;" ::: "memory"); }
template <int N>
__device__ __forceinline__ void wgmma_wait() { asm volatile("wgmma.wait_group.sync.aligned %0;" ::"n"(N) : "memory"); }

__device__ __forceinline__ uint64_t make_desc(uint32_t addr, uint32_t lbo, uint32_t sbo, uint32_t layout) {
  return (uint64_t)((addr & 0x3FFFF) >> 4) | ((uint64_t)((lbo & 0x3FFFF) >> 4) << 16) | ((uint64_t)((sbo & 0x3FFFF) >> 4) << 32) |
         ((uint64_t)layout << 62);
}
__device__ __forceinline__ uint32_t pack_bf16(float lo, float hi) {
  uint32_t r;
  asm("cvt.rn.bf16x2.f32 %0, %1, %2;" : "=r"(r) : "f"(hi), "f"(lo));
  return r;
}
__device__ __forceinline__ float bf16_round(float x) { return __bfloat162float(__float2bfloat16_rn(x)); }
__device__ __forceinline__ float bf_lo(uint32_t u) { return __uint_as_float(u << 16); }
__device__ __forceinline__ float bf_hi(uint32_t u) { return __uint_as_float(u & 0xffff0000u); }
__device__ __forceinline__ float ex2(float x) {
  float y;
  asm("ex2.approx.ftz.f32 %0, %1;" : "=f"(y) : "f"(x));
  return y;
}

__device__ __forceinline__ void wgmma_ss_n240_tb(float (&d)[120], uint64_t descA, uint64_t descB, int scaleD) {
  asm volatile("{\n.reg .pred p;\nsetp.ne.b32 p, %122, 0;\n"
    "wgmma.mma_async.sync.aligned.m64n240k16.f32.bf16.bf16 {%0, %1, %2, %3, %4, %5, %6, %7, %8, %9, %10, %11, %12, %13, %14, %15, %16, %17, %18, %19, %20, %21, %22, %23, %24, %25, %26, %27, %28, %29, %30, %31, %32, %33, %34, %35, %36, %37, %38, %39, %40, %41, %42, %43, %44, %45, %46, %47, %48, %49, %50, %51, %52, %53, %54, %55, %56, %57, %58, %59, %60, %61, %62, %63, %64, %65, %66, %67, %68, %69, %70, %71, %72, %73, %74, %75, %76, %77, %78, %79, %80, %81, %82, %83, %84, %85, %86, %87, %88, %89, %90, %91, %92, %93, %94, %95, %96, %97, %98, %99, %100, %101, %102, %103, %104, %105, %106, %107, %108, %109, %110, %111, %112, %113, %114, %115, %116, %117, %118, %119}, %120, %121, p, 1, 1, 0, 1;\n}\n"
    : "+f"(d[0]), "+f"(d[1]), "+f"(d[2]), "+f"(d[3]), "+f"(d[4]), "+f"(d[5]), "+f"(d[6]), "+f"(d[7]), "+f"(d[8]), "+f"(d[9]), "+f"(d[10]), "+f"(d[11]), "+f"(d[12]), "+f"(d[13]), "+f"(d[14]), "+f"(d[15]), "+f"(d[16]), "+f"(d[17]), "+f"(d[18]), "+f"(d[19]), "+f"(d[20]), "+f"(d[21]), "+f"(d[22]), "+f"(d[23]), "+f"(d[24]), "+f"(d[25]), "+f"(d[26]), "+f"(d[27]), "+f"(d[28]), "+f"(d[29]), "+f"(d[30]), "+f"(d[31]), "+f"(d[32]), "+f"(d[33]), "+f"(d[34]), "+f"(d[35]), "+f"(d[36]), "+f"(d[37]), "+f"(d[38]), "+f"(d[39]), "+f"(d[40]), "+f"(d[41]), "+f"(d[42]), "+f"(d[43]), "+f"(d[44]), "+f"(d[45]), "+f"(d[46]), "+f"(d[47]), "+f"(d[48]), "+f"(d[49]), "+f"(d[50]), "+f"(d[51]), "+f"(d[52]), "+f"(d[53]), "+f"(d[54]), "+f"(d[55]), "+f"(d[56]), "+f"(d[57]), "+f"(d[58]), "+f"(d[59]), "+f"(d[60]), "+f"(d[61]), "+f"(d[62]), "+f"(d[63]), "+f"(d[64]), "+f"(d[65]), "+f"(d[66]), "+f"(d[67]), "+f"(d[68]), "+f"(d[69]), "+f"(d[70]), "+f"(d[71]), "+f"(d[72]), "+f"(d[73]), "+f"(d[74]), "+f"(d[75]), "+f"(d[76]), "+f"(d[77]), "+f"(d[78]), "+f"(d[79]), "+f"(d[80]), "+f"(d[81]), "+f"(d[82]), "+f"(d[83]), "+f"(d[84]), "+f"(d[85]), "+f"(d[86]), "+f"(d[87]), "+f"(d[88]), "+f"(d[89]), "+f"(d[90]), "+f"(d[91]), "+f"(d[92]), "+f"(d[93]), "+f"(d[94]), "+f"(d[95]), "+f"(d[96]), "+f"(d[97]), "+f"(d[98]), "+f"(d[99]), "+f"(d[100]), "+f"(d[101]), "+f"(d[102]), "+f"(d[103]), "+f"(d[104]), "+f"(d[105]), "+f"(d[106]), "+f"(d[107]), "+f"(d[108]), "+f"(d[109]), "+f"(d[110]), "+f"(d[111]), "+f"(d[112]), "+f"(d[113]), "+f"(d[114]), "+f"(d[115]), "+f"(d[116]), "+f"(d[117]), "+f"(d[118]), "+f"(d[119])
    : "l"(descA), "l"(descB), "r"(scaleD));
}
__device__ __forceinline__ void wgmma_ss_n192_tb(float (&d)[96], uint64_t descA, uint64_t descB, int scaleD) {
  asm volatile("{\n.reg .pred p;\nsetp.ne.b32 p, %98, 0;\n"
    "wgmma.mma_async.sync.aligned.m64n192k16.f32.bf16.bf16 {%0, %1, %2, %3, %4, %5, %6, %7, %8, %9, %10, %11, %12, %13, %14, %15, %16, %17, %18, %19, %20, %21, %22, %23, %24, %25, %26, %27, %28, %29, %30, %31, %32, %33, %34, %35, %36, %37, %38, %39, %40, %41, %42, %43, %44, %45, %46, %47, %48, %49, %50, %51, %52, %53, %54, %55, %56, %57, %58, %59, %60, %61, %62, %63, %64, %65, %66, %67, %68, %69, %70, %71, %72, %73, %74, %75, %76, %77, %78, %79, %80, %81, %82, %83, %84, %85, %86, %87, %88, %89, %90, %91, %92, %93, %94, %95}, %96, %97, p, 1, 1, 0, 1;\n}\n"
    : "+f"(d[0]), "+f"(d[1]), "+f"(d[2]), "+f"(d[3]), "+f"(d[4]), "+f"(d[5]), "+f"(d[6]), "+f"(d[7]), "+f"(d[8]), "+f"(d[9]), "+f"(d[10]), "+f"(d[11]), "+f"(d[12]), "+f"(d[13]), "+f"(d[14]), "+f"(d[15]), "+f"(d[16]), "+f"(d[17]), "+f"(d[18]), "+f"(d[19]), "+f"(d[20]), "+f"(d[21]), "+f"(d[22]), "+f"(d[23]), "+f"(d[24]), "+f"(d[25]), "+f"(d[26]), "+f"(d[27]), "+f"(d[28]), "+f"(d[29]), "+f"(d[30]), "+f"(d[31]), "+f"(d[32]), "+f"(d[33]), "+f"(d[34]), "+f"(d[35]), "+f"(d[36]), "+f"(d[37]), "+f"(d[38]), "+f"(d[39]), "+f"(d[40]), "+f"(d[41]), "+f"(d[42]), "+f"(d[43]), "+f"(d[44]), "+f"(d[45]), "+f"(d[46]), "+f"(d[47]), "+f"(d[48]), "+f"(d[49]), "+f"(d[50]), "+f"(d[51]), "+f"(d[52]), "+f"(d[53]), "+f"(d[54]), "+f"(d[55]), "+f"(d[56]), "+f"(d[57]), "+f"(d[58]), "+f"(d[59]), "+f"(d[60]), "+f"(d[61]), "+f"(d[62]), "+f"(d[63]), "+f"(d[64]), "+f"(d[65]), "+f"(d[66]), "+f"(d[67]), "+f"(d[68]), "+f"(d[69]), "+f"(d[70]), "+f"(d[71]), "+f"(d[72]), "+f"(d[73]), "+f"(d[74]), "+f"(d[75]), "+f"(d[76]), "+f"(d[77]), "+f"(d[78]), "+f"(d[79]), "+f"(d[80]), "+f"(d[81]), "+f"(d[82]), "+f"(d[83]), "+f"(d[84]), "+f"(d[85]), "+f"(d[86]), "+f"(d[87]), "+f"(d[88]), "+f"(d[89]), "+f"(d[90]), "+f"(d[91]), "+f"(d[92]), "+f"(d[93]), "+f"(d[94]), "+f"(d[95])
    : "l"(descA), "l"(descB), "r"(scaleD));
}
__device__ __forceinline__ void wgmma_ss_n64_tb(float (&d)[32], uint64_t descA, uint64_t descB, int scaleD) {
  asm volatile("{\n.reg .pred p;\nsetp.ne.b32 p, %34, 0;\n"
    "wgmma.mma_async.sync.aligned.m64n64k16.f32.bf16.bf16 {%0, %1, %2, %3, %4, %5, %6, %7, %8, %9, %10, %11, %12, %13, %14, %15, %16, %17, %18, %19, %20, %21, %22, %23, %24, %25, %26, %27, %28, %29, %30, %31}, %32, %33, p, 1, 1, 0, 1;\n}\n"
    : "+f"(d[0]), "+f"(d[1]), "+f"(d[2]), "+f"(d[3]), "+f"(d[4]), "+f"(d[5]), "+f"(d[6]), "+f"(d[7]), "+f"(d[8]), "+f"(d[9]), "+f"(d[10]), "+f"(d[11]), "+f"(d[12]), "+f"(d[13]), "+f"(d[14]), "+f"(d[15]), "+f"(d[16]), "+f"(d[17]), "+f"(d[18]), "+f"(d[19]), "+f"(d[20]), "+f"(d[21]), "+f"(d[22]), "+f"(d[23]), "+f"(d[24]), "+f"(d[25]), "+f"(d[26]), "+f"(d[27]), "+f"(d[28]), "+f"(d[29]), "+f"(d[30]), "+f"(d[31])
    : "l"(descA), "l"(descB), "r"(scaleD));
}
__device__ __forceinline__ void wgmma_ss_n16_tb(float (&d)[8], uint64_t descA, uint64_t descB, int scaleD) {
  asm volatile("{\n.reg .pred p;\nsetp.ne.b32 p, %10, 0;\n"
    "wgmma.mma_async.sync.aligned.m64n16k16.f32.bf16.bf16 {%0, %1, %2, %3, %4, %5, %6, %7}, %8, %9, p, 1, 1, 0, 1;\n}\n"
    : "+f"(d[0]), "+f"(d[1]), "+f"(d[2]), "+f"(d[3]), "+f"(d[4]), "+f"(d[5]), "+f"(d[6]), "+f"(d[7])
    : "l"(descA), "l"(descB), "r"(scaleD));
}
__device__ __forceinline__ void wgmma_rs_n128(float (&d)[64], uint32_t a0, uint32_t a1, uint32_t a2, uint32_t a3, uint64_t descB, int scaleD) {
  asm volatile("{\n.reg .pred p;\nsetp.ne.b32 p, %69, 0;\n"
    "wgmma.mma_async.sync.aligned.m64n128k16.f32.bf16.bf16 {%0, %1, %2, %3, %4, %5, %6, %7, %8, %9, %10, %11, %12, %13, %14, %15, %16, %17, %18, %19, %20, %21, %22, %23, %24, %25, %26, %27, %28, %29, %30, %31, %32, %33, %34, %35, %36, %37, %38, %39, %40, %41, %42, %43, %44, %45, %46, %47, %48, %49, %50, %51, %52, %53, %54, %55, %56, %57, %58, %59, %60, %61, %62, %63}, {%64, %65, %66, %67}, %68, p, 1, 1, 0;\n}\n"
    : "+f"(d[0]), "+f"(d[1]), "+f"(d[2]), "+f"(d[3]), "+f"(d[4]), "+f"(d[5]), "+f"(d[6]), "+f"(d[7]), "+f"(d[8]), "+f"(d[9]), "+f"(d[10]), "+f"(d[11]), "+f"(d[12]), "+f"(d[13]), "+f"(d[14]), "+f"(d[15]), "+f"(d[16]), "+f"(d[17]), "+f"(d[18]), "+f"(d[19]), "+f"(d[20]), "+f"(d[21]), "+f"(d[22]), "+f"(d[23]), "+f"(d[24]), "+f"(d[25]), "+f"(d[26]), "+f"(d[27]), "+f"(d[28]), "+f"(d[29]), "+f"(d[30]), "+f"(d[31]), "+f"(d[32]), "+f"(d[33]), "+f"(d[34]), "+f"(d[35]), "+f"(d[36]), "+f"(d[37]), "+f"(d[38]), "+f"(d[39]), "+f"(d[40]), "+f"(d[41]), "+f"(d[42]), "+f"(d[43]), "+f"(d[44]), "+f"(d[45]), "+f"(d[46]), "+f"(d[47]), "+f"(d[48]), "+f"(d[49]), "+f"(d[50]), "+f"(d[51]), "+f"(d[52]), "+f"(d[53]), "+f"(d[54]), "+f"(d[55]), "+f"(d[56]), "+f"(d[57]), "+f"(d[58]), "+f"(d[59]), "+f"(d[60]), "+f"(d[61]), "+f"(d[62]), "+f"(d[63])
    : "r"(a0), "r"(a1), "r"(a2), "r"(a3), "l"(descB), "r"(scaleD));
}
__device__ __forceinline__ void wgmma_rs_n64(float (&d)[32], uint32_t a0, uint32_t a1, uint32_t a2, uint32_t a3, uint64_t descB, int scaleD) {
  asm volatile("{\n.reg .pred p;\nsetp.ne.b32 p, %37, 0;\n"
    "wgmma.mma_async.sync.aligned.m64n64k16.f32.bf16.bf16 {%0, %1, %2, %3, %4, %5, %6, %7, %8, %9, %10, %11, %12, %13, %14, %15, %16, %17, %18, %19, %20, %21, %22, %23, %24, %25, %26, %27, %28, %29, %30, %31}, {%32, %33, %34, %35}, %36, p, 1, 1, 0;\n}\n"
    : "+f"(d[0]), "+f"(d[1]), "+f"(d[2]), "+f"(d[3]), "+f"(d[4]), "+f"(d[5]), "+f"(d[6]), "+f"(d[7]), "+f"(d[8]), "+f"(d[9]), "+f"(d[10]), "+f"(d[11]), "+f"(d[12]), "+f"(d[13]), "+f"(d[14]), "+f"(d[15]), "+f"(d[16]), "+f"(d[17]), "+f"(d[18]), "+f"(d[19]), "+f"(d[20]), "+f"(d[21]), "+f"(d[22]), "+f"(d[23]), "+f"(d[24]), "+f"(d[25]), "+f"(d[26]), "+f"(d[27]), "+f"(d[28]), "+f"(d[29]), "+f"(d[30]), "+f"(d[31])
    : "r"(a0), "r"(a1), "r"(a2), "r"(a3), "l"(descB), "r"(scaleD));
}
__device__ __forceinline__ void wgmma_rs_n24_tb(float (&d)[12], uint32_t a0, uint32_t a1, uint32_t a2, uint32_t a3, uint64_t descB, int scaleD) {
  asm volatile("{\n.reg .pred p;\nsetp.ne.b32 p, %17, 0;\n"
    "wgmma.mma_async.sync.aligned.m64n24k16.f32.bf16.bf16 {%0, %1, %2, %3, %4, %5, %6, %7, %8, %9, %10, %11}, {%12, %13, %14, %15}, %16, p, 1, 1, 1;\n}\n"
    : "+f"(d[0]), "+f"(d[1]), "+f"(d[2]), "+f"(d[3]), "+f"(d[4]), "+f"(d[5]), "+f"(d[6]), "+f"(d[7]), "+f"(d[8]), "+f"(d[9]), "+f"(d[10]), "+f"(d[11])
    : "r"(a0), "r"(a1), "r"(a2), "r"(a3), "l"(descB), "r"(scaleD));
}


constexpr int LG_THREADS = 384;
constexpr int LG_A_BYTES = 128 * DM * 2;

template <int MODE>
struct LGCfg;
template <>
struct LGCfg<0> {
  static constexpr int BK = 32, NSLAB = 4, STAGES = 4;
};
template <>
struct LGCfg<1> {
  static constexpr int BK = 16, NSLAB = 6, STAGES = 4;
};
template <int MODE>
constexpr int lg_smem_bytes() {
  return LG_A_BYTES + LGCfg<MODE>::STAGES * LGCfg<MODE>::NSLAB * LGCfg<MODE>::BK * 128 + 128 + 1024;
}

template <int WG>
__device__ __forceinline__ void qkv_mainloop(float (&acc)[120], uint32_t sA, uint32_t sB, uint32_t sBar, bool leader) {
  using C = LGCfg<0>;
  constexpr int SLAB_BYTES = C::BK * 128, STAGE_BYTES = C::NSLAB * SLAB_BYTES, NKB = DM / C::BK, NST = C::STAGES;
  static_assert(NST * C::BK == 128, "round = 2 slabs of A");
  uint64_t da_base = make_desc(sA + WG * 8192, 16, 1024, 1);
  const uint64_t db_base = make_desc(sB, SLAB_BYTES, 1024, 1);
#pragma unroll 1
  for (int r = 0; r < NKB / NST; r++) {
#pragma unroll
    for (int s = 0; s < NST; s++) {
      mbar_wait(sBar + 8 * s, r & 1);
      wgmma_fence();
#pragma unroll
      for (int ks = 0; ks < 2; ks++) {
        const int k = s * 32 + ks * 16;
        wgmma_ss_n240_tb(acc, da_base + (uint64_t)(((k >> 6) * 16384 + (k & 63) * 2) >> 4), db_base + (uint64_t)((s * STAGE_BYTES + ks * 2048) >> 4), 1);
      }
      wgmma_commit();
      wgmma_wait<1>();
      if (leader && (s > 0 || r > 0)) {
        const int ps = (s + NST - 1) % NST;
        mbar_arrive_cluster(sBar + 8 * (NST + ps), 0);
        mbar_arrive_cluster(sBar + 8 * (NST + ps), 1);
      }
    }
    da_base += (2 * 16384) >> 4;
  }
}
template <int WG>
__device__ __forceinline__ void glu_mainloop(float (&accg)[96], float (&accu)[96], uint32_t sA, uint32_t sB, uint32_t sBar, bool leader) {
  using C = LGCfg<1>;
  constexpr int SLAB_BYTES = C::BK * 128, STAGE_BYTES = C::NSLAB * SLAB_BYTES, NKB = DM / C::BK, NST = C::STAGES;
  static_assert(NST * C::BK == 64, "round = 1 slab of A");
  uint64_t da_base = make_desc(sA + WG * 8192, 16, 1024, 1);
  const uint64_t db_base = make_desc(sB, SLAB_BYTES, 1024, 1);
#pragma unroll 1
  for (int r = 0; r < NKB / NST; r++) {
#pragma unroll
    for (int s = 0; s < NST; s++) {
      mbar_wait(sBar + 8 * s, r & 1);
      wgmma_fence();
      const uint64_t da = da_base + (uint64_t)((s * 32) >> 4);
      wgmma_ss_n192_tb(accg, da, db_base + (uint64_t)((s * STAGE_BYTES) >> 4), 1);
      wgmma_ss_n192_tb(accu, da, db_base + (uint64_t)((s * STAGE_BYTES + 3 * SLAB_BYTES) >> 4), 1);
      wgmma_commit();
      wgmma_wait<1>();
      if (leader && (s > 0 || r > 0)) {
        const int ps = (s + NST - 1) % NST;
        mbar_arrive_cluster(sBar + 8 * (NST + ps), 0);
        mbar_arrive_cluster(sBar + 8 * (NST + ps), 1);
      }
    }
    da_base += 16384 >> 4;
  }
}

template <int MODE>
__global__ void __launch_bounds__(LG_THREADS, 1)
ln_gemm_kernel(const __grid_constant__ CUtensorMap tmB0, const __grid_constant__ CUtensorMap tmB1, const __grid_constant__ CUtensorMap tmOut,
               const bf16* __restrict__ xin) {
  using C = LGCfg<MODE>;
  constexpr int SLAB_BYTES = C::BK * 128;
  constexpr int STAGE_BYTES = C::NSLAB * SLAB_BYTES;
  constexpr int NKB = DM / C::BK;
  extern __shared__ uint8_t smem_raw[];
  const uint32_t sbase = (smem_u32(smem_raw) + 1023u) & ~1023u;
  const uint32_t sA = sbase;
  const uint32_t sB = sbase + LG_A_BYTES;
  const uint32_t sBar = sB + C::STAGES * STAGE_BYTES;
  const int tid = threadIdx.x, warp = tid >> 5, lane = tid & 31;
  const int rank = blockIdx.x & 1;
  const int pair = blockIdx.x >> 1;
  const int n_blk = pair & 7;
  const int m_blk = (pair >> 3) * 2 + rank;

  if (tid == 256) {
    prefetch_tmap(&tmB0);
    if (MODE == 1) { prefetch_tmap(&tmB1); prefetch_tmap(&tmOut); }
  }
  if (tid == 0) {
    for (int s = 0; s < C::STAGES; s++) {
      mbar_init(sBar + 8 * s, 1);
      mbar_init(sBar + 8 * (C::STAGES + s), 4);
    }
    fence_mbar_init();
  }
  pdl_launch();
  cluster_sync_all();

  auto issue_stage = [&](int kb) {
    const int s = kb % C::STAGES;
    const uint32_t full = sBar + 8 * s;
    mbar_expect_tx(full, STAGE_BYTES);
    const uint32_t dst = sB + s * STAGE_BYTES;
    if (MODE == 0) {
#pragma unroll
      for (int j = 0; j < 2; j++) {
        const int sl = rank * 2 + j;
        tma_load_2d_mc(dst + sl * SLAB_BYTES, &tmB0, n_blk * 240 + sl * 64, kb * C::BK, full, (uint16_t)3);
      }
    } else {
#pragma unroll
      for (int j = 0; j < 3; j++) {
        const int sl = rank * 3 + j;
        tma_load_2d_mc(dst + sl * SLAB_BYTES, rank == 0 ? &tmB0 : &tmB1, n_blk * 192 + j * 64, kb * C::BK, full, (uint16_t)3);
      }
    }
  };
  if (tid == 256) {
    for (int kb = 0; kb < C::STAGES; kb++) issue_stage(kb);
  }
  __syncwarp();
  pdl_wait();
  {
    const int hw = lane >> 4, l16 = lane & 15;
#pragma unroll
    for (int half = 0; half < 2; half++) {
      uint4 v[3][5];
#pragma unroll
      for (int it = 0; it < 3; it++) {
        const int pr = warp + (half * 3 + it) * 12;
        const int lrow = (pr < 64 ? pr : 0) * 2 + hw;
        const uint4* src = reinterpret_cast<const uint4*>(xin + (size_t)(m_blk * 128 + lrow) * DM);
#pragma unroll
        for (int j = 0; j < 5; j++) v[it][j] = __ldg(src + j * 16 + l16);
      }
      float mean[3], inv[3];
#pragma unroll
      for (int it = 0; it < 3; it++) {
        float s0 = 0.f, s1 = 0.f, s2 = 0.f, s3 = 0.f;
#pragma unroll
        for (int j = 0; j < 5; j++) {
          s0 += bf_lo(v[it][j].x) + bf_hi(v[it][j].x);
          s1 += bf_lo(v[it][j].y) + bf_hi(v[it][j].y);
          s2 += bf_lo(v[it][j].z) + bf_hi(v[it][j].z);
          s3 += bf_lo(v[it][j].w) + bf_hi(v[it][j].w);
        }
        mean[it] = (s0 + s1) + (s2 + s3);
      }
#pragma unroll
      for (int o = 1; o < 16; o <<= 1) {
#pragma unroll
        for (int it = 0; it < 3; it++) mean[it] += __shfl_xor_sync(0xffffffffu, mean[it], o);
      }
#pragma unroll
      for (int it = 0; it < 3; it++) {
        mean[it] *= (1.0f / DM);
        float s0 = 0.f, s1 = 0.f, s2 = 0.f, s3 = 0.f;
#pragma unroll
        for (int j = 0; j < 5; j++) {
          float d;
          d = bf_lo(v[it][j].x) - mean[it]; s0 = fmaf(d, d, s0);
          d = bf_hi(v[it][j].x) - mean[it]; s1 = fmaf(d, d, s1);
          d = bf_lo(v[it][j].y) - mean[it]; s2 = fmaf(d, d, s2);
          d = bf_hi(v[it][j].y) - mean[it]; s3 = fmaf(d, d, s3);
          d = bf_lo(v[it][j].z) - mean[it]; s0 = fmaf(d, d, s0);
          d = bf_hi(v[it][j].z) - mean[it]; s1 = fmaf(d, d, s1);
          d = bf_lo(v[it][j].w) - mean[it]; s2 = fmaf(d, d, s2);
          d = bf_hi(v[it][j].w) - mean[it]; s3 = fmaf(d, d, s3);
        }
        inv[it] = (s0 + s1) + (s2 + s3);
      }
#pragma unroll
      for (int o = 1; o < 16; o <<= 1) {
#pragma unroll
        for (int it = 0; it < 3; it++) inv[it] += __shfl_xor_sync(0xffffffffu, inv[it], o);
      }
#pragma unroll
      for (int it = 0; it < 3; it++) {
        const int pr = warp + (half * 3 + it) * 12;
        const int lrow = pr * 2 + hw;
        const float var_b = bf16_round(inv[it] * (1.0f / DM));
        const float den = bf16_round(sqrtf(bf16_round(var_b + 1e-5f)));
        const float iv = __frcp_rn(den);
        const float nmi = -bf16_round(mean[it]) * iv;
        if (pr < 64) {
#pragma unroll
          for (int j = 0; j < 5; j++) {
            const uint32_t w0 = pack_bf16(fmaf(bf_lo(v[it][j].x), iv, nmi), fmaf(bf_hi(v[it][j].x), iv, nmi));
            const uint32_t w1 = pack_bf16(fmaf(bf_lo(v[it][j].y), iv, nmi), fmaf(bf_hi(v[it][j].y), iv, nmi));
            const uint32_t w2 = pack_bf16(fmaf(bf_lo(v[it][j].z), iv, nmi), fmaf(bf_hi(v[it][j].z), iv, nmi));
            const uint32_t w3 = pack_bf16(fmaf(bf_lo(v[it][j].w), iv, nmi), fmaf(bf_hi(v[it][j].w), iv, nmi));
            const int ch = j * 16 + l16;
            const uint32_t addr = sA + (ch >> 3) * 16384 + lrow * 128 + (((ch & 7) ^ (lrow & 7)) << 4);
            asm volatile("st.shared.v4.b32 [%0], {%1, %2, %3, %4};" ::"r"(addr), "r"(w0), "r"(w1), "r"(w2), "r"(w3) : "memory");
          }
        }
      }
    }
  }
  fence_proxy_async();
  __syncthreads();

  if (warp >= 8) {
    asm volatile("setmaxnreg.dec.sync.aligned.u32 40;");
    if (tid == 256) {
      for (int kb = C::STAGES; kb < NKB; kb++) {
        const int s = kb % C::STAGES;
        const uint32_t ph = (kb / C::STAGES) & 1;
        mbar_wait(sBar + 8 * (C::STAGES + s), ph ^ 1);
        issue_stage(kb);
      }
    }
  } else {
    asm volatile("setmaxnreg.inc.sync.aligned.u32 232;");
    const int wg = __shfl_sync(0xffffffffu, warp >> 2, 0);
    const int wwarp = warp & 3;
    if (MODE == 0) {
      float acc[120];
#pragma unroll
      for (int i = 0; i < 120; i++) acc[i] = 0.f;
      if (wg == 0) qkv_mainloop<0>(acc, sA, sB, sBar, (tid & 127) == 0);
      else qkv_mainloop<1>(acc, sA, sB, sBar, (tid & 127) == 0);
      wgmma_wait<0>();
      named_bar_sync(3, 256);
      const int g = lane >> 2, c4 = lane & 3;
      const uint32_t stg = sA + wg * (12 * 3072) + (wwarp * 2) * 384 + g * 16;
      const int hbase = n_blk * 12;
#pragma unroll
      for (int j = 0; j < 30; j++) {
        const int cb = (j * 8) % 20;
        const int hb = (j * 8) / 20;
        int d = cb + c4 * 2;
        int hl = hb;
        if (cb == 16 && c4 >= 2) { d -= 20; hl += 1; }
        const uint32_t a0 = stg + hl * 3072 + (d >> 3) * 128 + (d & 7) * 2;
        st_shared_b32(a0, pack_bf16(acc[4 * j], acc[4 * j + 1]));
        st_shared_b32(a0 + 384, pack_bf16(acc[4 * j + 2], acc[4 * j + 3]));
        if (d == 18) {
          const uint32_t pad = (hbase + hl >= 64) ? 0x00003f80u : 0u;
          st_shared_v2(a0 + 4, pad, 0u);
          st_shared_v2(a0 + 388, pad, 0u);
        }
      }
      fence_proxy_async();
      named_bar_sync(1 + wg, 128);
      if ((tid & 127) < 12) {
        const int hl = tid & 127;
        bf16* dst = g_img + (size_t)(hbase + hl) * IMG_HEAD_ELEMS + (size_t)(m_blk * 16 + wg * 8) * 192;
        bulk_s2g(dst, sA + wg * (12 * 3072) + hl * 3072, 3072);
        bulk_commit();
        bulk_wait_all();
      }
    } else {
      float accg[96], accu[96];
#pragma unroll
      for (int i = 0; i < 96; i++) { accg[i] = 0.f; accu[i] = 0.f; }
      if (wg == 0) glu_mainloop<0>(accg, accu, sA, sB, sBar, (tid & 127) == 0);
      else glu_mainloop<1>(accg, accu, sA, sB, sBar, (tid & 127) == 0);
      wgmma_wait<0>();
      named_bar_sync(3, 256);
      const int g = lane >> 2, c4 = lane & 3;
      const uint32_t stg = sA + wg * 24576 + (wwarp * 16 + g) * 128 + c4 * 4;
#pragma unroll
      for (int j = 0; j < 24; j++) {
        uint32_t pk[2];
#pragma unroll
        for (int h = 0; h < 2; h++) {
          const uint32_t gp = pack_bf16(accg[4 * j + 2 * h], accg[4 * j + 2 * h + 1]);
          const uint32_t up = pack_bf16(accu[4 * j + 2 * h], accu[4 * j + 2 * h + 1]);
          const float g0 = bf_lo(gp), g1 = bf_hi(gp);
          const float r0 = (g0 * (g0 > 0.f ? 1.f : 0.f)) * bf_lo(up);
          const float r1 = (g1 * (g1 > 0.f ? 1.f : 0.f)) * bf_hi(up);
          pk[h] = pack_bf16(r0, r1);
        }
        const uint32_t a0 = stg + (j >> 3) * 8192 + (((j & 7) ^ g) << 4);
        st_shared_b32(a0, pk[0]);
        st_shared_b32(a0 + 1024, pk[1]);
      }
      fence_proxy_async();
      named_bar_sync(1 + wg, 128);
      if ((tid & 127) == 0) {
#pragma unroll
        for (int sl = 0; sl < 3; sl++) tma_store_2d(&tmOut, sA + wg * 24576 + sl * 8192, n_blk * 192 + sl * 64, m_blk * 128 + wg * 64);
        bulk_commit();
        bulk_wait_all();
      }
    }
  }
  __syncwarp();
  cluster_sync_relaxed();
}

constexpr int RG_THREADS = 288;
constexpr int RG_STAGES = 8;
constexpr int RG_STAGE_BYTES = 16384 + 8192 + 2048;
constexpr int RG_SMEM = RG_STAGES * RG_STAGE_BYTES + 256 + 1024;

template <int NKB, int NST, int WG>
__device__ __forceinline__ void res_mainloop(float (&acc0)[32], float (&acc1)[8], uint32_t sbase, uint32_t sBar, bool leader) {
  const uint64_t da_base = make_desc(sbase + WG * 8192, 16, 1024, 1);
  const uint64_t db0_base = make_desc(sbase + 16384, 8192, 1024, 1);
  const uint64_t db1_base = make_desc(sbase + 16384 + 8192, 2048, 256, 3);
#pragma unroll 1
  for (int r = 0; r < NKB / NST; r++) {
#pragma unroll
    for (int s = 0; s < NST; s++) {
      const uint64_t so = (uint64_t)(s * (RG_STAGE_BYTES >> 4));
      mbar_wait(sBar + 8 * s, r & 1);
      wgmma_fence();
#pragma unroll
      for (int ks = 0; ks < 4; ks++) {
        wgmma_ss_n64_tb(acc0, da_base + so + ks * 2, db0_base + so + ks * 128, 1);
        wgmma_ss_n16_tb(acc1, da_base + so + ks * 2, db1_base + so + ks * 32, 1);
      }
      wgmma_commit();
      wgmma_wait<1>();
      if (leader && (s > 0 || r > 0)) {
        const int ps = (s + NST - 1) % NST;
        mbar_arrive_cluster(sBar + 8 * (NST + ps), 0);
        mbar_arrive_cluster(sBar + 8 * (NST + ps), 1);
      }
    }
  }
}

template <int KTOT>
__global__ void __launch_bounds__(RG_THREADS, 1)
res_gemm_kernel(const __grid_constant__ CUtensorMap tmA, const __grid_constant__ CUtensorMap tmB64, const __grid_constant__ CUtensorMap tmB16,
                const bf16* __restrict__ resid, bf16* __restrict__ out) {
  constexpr int NKB = KTOT / 64;
  constexpr int NST = (KTOT == DM) ? 5 : 8;
  extern __shared__ uint8_t smem_raw[];
  const uint32_t sbase = (smem_u32(smem_raw) + 1023u) & ~1023u;
  const uint32_t sBar = sbase + NST * RG_STAGE_BYTES;
  const int tid = threadIdx.x, warp = tid >> 5, lane = tid & 31;
  const int rank = blockIdx.x & 1;
  const int pair = blockIdx.x >> 1;
  const int m_blk = pair >> 2;
  const int n_blk = (pair & 3) * 2 + rank;
  const int n0 = n_blk * 80;

  if (tid == 0) {
    for (int s = 0; s < NST; s++) {
      mbar_init(sBar + 8 * s, 1);
      mbar_init(sBar + 8 * (NST + s), 4);
    }
    fence_mbar_init();
  }
  pdl_launch();
  cluster_sync_all();

  if (warp == 8) {
    if (lane == 0) {
      prefetch_tmap(&tmA); prefetch_tmap(&tmB64); prefetch_tmap(&tmB16);
      constexpr int PRE = NKB < NST ? NKB : NST;
      for (int kb = 0; kb < PRE; kb++) {
        const uint32_t full = sBar + 8 * kb;
        const uint32_t st = sbase + kb * RG_STAGE_BYTES;
        mbar_expect_tx(full, RG_STAGE_BYTES);
        tma_load_2d(st + 16384, &tmB64, n0, kb * 64, full);
        tma_load_2d(st + 16384 + 8192, &tmB16, n0 + 64, kb * 64, full);
      }
      pdl_wait();
      for (int kb = 0; kb < NKB; kb++) {
        const int s = kb % NST;
        const uint32_t full = sBar + 8 * s;
        const uint32_t st = sbase + s * RG_STAGE_BYTES;
        if (kb >= PRE) {
          const uint32_t ph = (kb / NST) & 1;
          mbar_wait(sBar + 8 * (NST + s), ph ^ 1);
          mbar_expect_tx(full, RG_STAGE_BYTES);
          tma_load_2d(st + 16384, &tmB64, n0, kb * 64, full);
          tma_load_2d(st + 16384 + 8192, &tmB16, n0 + 64, kb * 64, full);
        }
        tma_load_2d_mc(st + rank * 8192, &tmA, kb * 64, m_blk * 128 + rank * 64, full, (uint16_t)3);
      }
    }
  } else {
    const int wg = __shfl_sync(0xffffffffu, warp >> 2, 0), wwarp = warp & 3;
    const int g = lane >> 2, c4 = lane & 3;
    const int row0 = m_blk * 128 + wg * 64 + wwarp * 16 + g;
    pdl_wait();
    uint32_t res[20];
#pragma unroll
    for (int j = 0; j < 10; j++) {
      res[2 * j] = __ldg(reinterpret_cast<const uint32_t*>(resid + (size_t)row0 * DM + n0 + j * 8 + c4 * 2));
      res[2 * j + 1] = __ldg(reinterpret_cast<const uint32_t*>(resid + (size_t)(row0 + 8) * DM + n0 + j * 8 + c4 * 2));
    }
    float acc0[32], acc1[8];
#pragma unroll
    for (int i = 0; i < 32; i++) acc0[i] = 0.f;
#pragma unroll
    for (int i = 0; i < 8; i++) acc1[i] = 0.f;
    if (wg == 0) res_mainloop<NKB, NST, 0>(acc0, acc1, sbase, sBar, (tid & 127) == 0);
    else res_mainloop<NKB, NST, 1>(acc0, acc1, sbase, sBar, (tid & 127) == 0);
    wgmma_wait<0>();
#pragma unroll
    for (int j = 0; j < 10; j++) {
      float a[4];
#pragma unroll
      for (int e = 0; e < 4; e++) a[e] = bf16_round(j < 8 ? acc0[4 * j + e] : acc1[4 * (j - 8) + e]);
      const uint32_t o0 = pack_bf16(bf_lo(res[2 * j]) + a[0], bf_hi(res[2 * j]) + a[1]);
      const uint32_t o1 = pack_bf16(bf_lo(res[2 * j + 1]) + a[2], bf_hi(res[2 * j + 1]) + a[3]);
      *reinterpret_cast<uint32_t*>(out + (size_t)row0 * DM + n0 + j * 8 + c4 * 2) = o0;
      *reinterpret_cast<uint32_t*>(out + (size_t)(row0 + 8) * DM + n0 + j * 8 + c4 * 2) = o1;
    }
  }
  __syncwarp();
  cluster_sync_relaxed();
}

constexpr int AT_THREADS = 512;
constexpr int AT_KV_BYTES = IMG_HEAD_ELEMS * 2;
constexpr int AT_SMEM = 2 * AT_KV_BYTES + 256 + 1024;
constexpr int AT_CHUNKS = 8;

__device__ __forceinline__ float exp2_poly(float s, float c64, float b64) {
  const float u = __saturatef(fmaf(s, c64, b64));
  const float MAGIC = 12582912.0f - 64.0f;
  const float r = fmaf(u, 64.0f, MAGIC);
  const float q = MAGIC - r;
  const float fr = fmaf(u, 64.0f, q);
  float p = fmaf(fr, 0.009570102207362652f, 0.05591785907745361f);
  p = fmaf(p, fr, 0.240247443318367f);
  p = fmaf(p, fr, 0.6931217908859253f);
  p = fmaf(p, fr, 0.9999992847442627f);
  return __uint_as_float(__float_as_uint(p) + (__float_as_uint(r) << 23));
}

__global__ void __launch_bounds__(AT_THREADS, 1) attn_kernel() {
  extern __shared__ uint8_t smem_raw[];
  const uint32_t sbase = (smem_u32(smem_raw) + 1023u) & ~1023u;
  const uint32_t sK = sbase, sV = sbase + AT_KV_BYTES;
  const uint32_t sBar = sV + AT_KV_BYTES;
  const int tid = threadIdx.x, warp = tid >> 5, lane = tid & 31;
  const int head = blockIdx.x >> 2, quarter = blockIdx.x & 3;
  if (tid == 0) {
    for (int i = 0; i < AT_CHUNKS; i++) mbar_init(sBar + 8 * i, 1);
    fence_mbar_init();
  }
  pdl_launch();
  __syncthreads();
  pdl_wait();
  if (tid == 0) {
    const uint8_t* kg = reinterpret_cast<const uint8_t*>(g_img + (size_t)(32 + head) * IMG_HEAD_ELEMS);
    const uint8_t* vg = reinterpret_cast<const uint8_t*>(g_img + (size_t)(64 + head) * IMG_HEAD_ELEMS);
    constexpr int CB = AT_KV_BYTES / AT_CHUNKS;
    for (int i = 0; i < AT_CHUNKS; i++) {
      mbar_expect_tx(sBar + 8 * i, 2 * CB);
      bulk_g2s(sK + i * CB, kg + i * CB, CB, sBar + 8 * i);
      bulk_g2s(sV + i * CB, vg + i * CB, CB, sBar + 8 * i);
    }
  }
  const int wg = warp >> 2, wwarp = warp & 3;
  const int g = lane >> 2, c4 = lane & 3;
  const float SC = 0.22360679774997896f * 1.4426950408889634f;
  const float SC64 = SC * (1.0f / 64.0f);

  for (int rep = 0; rep < 2; rep++) {
    const int row0 = quarter * 512 + (rep * 4 + wg) * 64 + wwarp * 16 + g;
    uint32_t qa[8];
    {
      const bf16* q0 = g_img + (size_t)head * IMG_HEAD_ELEMS + (size_t)(row0 >> 3) * 192 + g * 8 + c4 * 2;
      const bf16* q1 = q0 + 192;
      qa[0] = *reinterpret_cast<const uint32_t*>(q0);
      qa[1] = *reinterpret_cast<const uint32_t*>(q1);
      qa[2] = *reinterpret_cast<const uint32_t*>(q0 + 64);
      qa[3] = *reinterpret_cast<const uint32_t*>(q1 + 64);
      qa[4] = *reinterpret_cast<const uint32_t*>(q0 + 128);
      qa[5] = *reinterpret_cast<const uint32_t*>(q1 + 128);
      qa[6] = 0u;
      qa[7] = 0u;
    }
    float o[12];
#pragma unroll
    for (int i = 0; i < 12; i++) o[i] = 0.f;
    float m0 = -INFINITY, m1 = -INFINITY;
#pragma unroll 1
    for (int t = 0; t < 16; t++) {
      if (rep == 0) mbar_wait(sBar + 8 * (t >> 1), 0);
      float s[64];
      wgmma_fence();
      {
        const uint64_t dk0 = make_desc(sK + t * 6144, 128, 384, 0);
        const uint64_t dk1 = make_desc(sK + t * 6144 + 256, 128, 384, 0);
        wgmma_rs_n128(s, qa[0], qa[1], qa[2], qa[3], dk0, 0);
        wgmma_rs_n128(s, qa[4], qa[5], qa[6], qa[7], dk1, 1);
      }
      wgmma_commit();
      wgmma_wait<0>();
      float mx0 = s[0], mx1 = s[2];
#pragma unroll
      for (int j = 0; j < 16; j++) {
        mx0 = fmaxf(mx0, fmaxf(s[4 * j], s[4 * j + 1]));
        mx1 = fmaxf(mx1, fmaxf(s[4 * j + 2], s[4 * j + 3]));
      }
      mx0 = fmaxf(mx0, __shfl_xor_sync(0xffffffffu, mx0, 1));
      mx1 = fmaxf(mx1, __shfl_xor_sync(0xffffffffu, mx1, 1));
      mx0 = fmaxf(mx0, __shfl_xor_sync(0xffffffffu, mx0, 2));
      mx1 = fmaxf(mx1, __shfl_xor_sync(0xffffffffu, mx1, 2));
      const float mn0 = fmaxf(m0, mx0), mn1 = fmaxf(m1, mx1);
      const float al0 = ex2((m0 - mn0) * SC), al1 = ex2((m1 - mn1) * SC);
      m0 = mn0; m1 = mn1;
      const float mc0 = -mn0 * SC, mc1 = -mn1 * SC;
      const float b0 = fmaf(mc0, 1.0f / 64.0f, 1.0f), b1 = fmaf(mc1, 1.0f / 64.0f, 1.0f);
      uint32_t p[32];
#pragma unroll
      for (int j = 0; j < 16; j++) {
        float e0, e1, e2, e3;
        e0 = ex2(fmaf(s[4 * j], SC, mc0));
        e1 = ex2(fmaf(s[4 * j + 1], SC, mc0));
        e2 = ex2(fmaf(s[4 * j + 2], SC, mc1));
        if ((j & 1) == 0) e3 = exp2_poly(s[4 * j + 3], SC64, b1);
        else { e3 = ex2(fmaf(s[4 * j + 3], SC, mc1)); e0 = exp2_poly(s[4 * j], SC64, b0); }
        p[2 * j] = pack_bf16(e0, e1);
        p[2 * j + 1] = pack_bf16(e2, e3);
      }
#pragma unroll
      for (int j = 0; j < 3; j++) {
        o[4 * j] *= al0; o[4 * j + 1] *= al0;
        o[4 * j + 2] *= al1; o[4 * j + 3] *= al1;
      }
      wgmma_fence();
#pragma unroll
      for (int kk = 0; kk < 8; kk++) {
        const uint64_t dv = make_desc(sV + t * 6144 + kk * 768, 384, 128, 0);
        wgmma_rs_n24_tb(o, p[4 * kk], p[4 * kk + 1], p[4 * kk + 2], p[4 * kk + 3], dv, 1);
      }
      wgmma_commit();
      wgmma_wait<0>();
    }
    const float l0 = __shfl_sync(0xffffffffu, o[8], (lane & ~3) | 2);
    const float l1 = __shfl_sync(0xffffffffu, o[10], (lane & ~3) | 2);
    const float i0 = 1.0f / l0, i1 = 1.0f / l1;
    bf16* o0 = g_o + (size_t)row0 * DM + head * DH;
    bf16* o1 = o0 + 8 * DM;
#pragma unroll
    for (int j = 0; j < 3; j++) {
      if (j < 2 || c4 < 2) {
        *reinterpret_cast<uint32_t*>(o0 + j * 8 + c4 * 2) = pack_bf16(o[4 * j] * i0, o[4 * j + 1] * i0);
        *reinterpret_cast<uint32_t*>(o1 + j * 8 + c4 * 2) = pack_bf16(o[4 * j + 2] * i1, o[4 * j + 3] * i1);
      }
    }
  }
}

typedef CUresult (*EncodeTiledFn)(CUtensorMap*, CUtensorMapDataType, cuuint32_t, void*, const cuuint64_t*, const cuuint64_t*,
                                  const cuuint32_t*, const cuuint32_t*, CUtensorMapInterleave, CUtensorMapSwizzle,
                                  CUtensorMapL2promotion, CUtensorMapFloatOOBfill);

static void make_map(EncodeTiledFn fn, CUtensorMap* tm, const void* ptr, uint64_t rows, uint64_t cols, uint32_t box_rows,
                     uint32_t box_cols, CUtensorMapSwizzle sw) {
  cuuint64_t dims[2] = {cols, rows};
  cuuint64_t strides[1] = {cols * 2};
  cuuint32_t box[2] = {box_cols, box_rows};
  cuuint32_t es[2] = {1, 1};
  fn(tm, CU_TENSOR_MAP_DATA_TYPE_BFLOAT16, 2, const_cast<void*>(ptr), dims, strides, box, es, CU_TENSOR_MAP_INTERLEAVE_NONE, sw,
     CU_TENSOR_MAP_L2_PROMOTION_L2_256B, CU_TENSOR_MAP_FLOAT_OOB_FILL_NONE);
}

template <typename... KArgs, typename... Args>
static void launch(void (*kern)(KArgs...), int grid, int block, int smem, int cluster, bool pdl, Args... args) {
  cudaLaunchConfig_t cfg = {};
  cfg.gridDim = dim3(grid);
  cfg.blockDim = dim3(block);
  cfg.dynamicSmemBytes = smem;
  cfg.stream = cudaStreamPerThread;
  cudaLaunchAttribute at[2];
  int n = 0;
  if (cluster > 1) {
    at[n].id = cudaLaunchAttributeClusterDimension;
    at[n].val.clusterDim.x = cluster; at[n].val.clusterDim.y = 1; at[n].val.clusterDim.z = 1;
    n++;
  }
  if (pdl) {
    at[n].id = cudaLaunchAttributeProgrammaticStreamSerialization;
    at[n].val.programmaticStreamSerializationAllowed = 1;
    n++;
  }
  cfg.attrs = at;
  cfg.numAttrs = n;
  cudaLaunchKernelEx(&cfg, kern, KArgs(args)...);
}

extern "C" void kernel_launch(void* const* d_in, const int* in_sizes, int n_in, void* d_out, int out_size) {
  const bf16* x = (const bf16*)d_in[0];
  const bf16* wqkv = (const bf16*)d_in[1];
  const bf16* wo = (const bf16*)d_in[2];
  const bf16* wg = (const bf16*)d_in[4];
  const bf16* wu = (const bf16*)d_in[5];
  const bf16* wd = (const bf16*)d_in[6];
  bf16* out = (bf16*)d_out;

  static EncodeTiledFn enc = nullptr;
  static void *p_o = nullptr, *p_h = nullptr, *p_hh = nullptr;
  if (!enc) {
    void* fn = nullptr;
    cudaDriverEntryPointQueryResult qr;
    cudaGetDriverEntryPoint("cuTensorMapEncodeTiled", &fn, cudaEnableDefault, &qr);
    enc = (EncodeTiledFn)fn;
    cudaGetSymbolAddress(&p_o, g_o);
    cudaGetSymbolAddress(&p_h, g_h);
    cudaGetSymbolAddress(&p_hh, g_hh);
    cudaFuncSetAttribute(ln_gemm_kernel<0>, cudaFuncAttributeMaxDynamicSharedMemorySize, lg_smem_bytes<0>());
    cudaFuncSetAttribute(ln_gemm_kernel<1>, cudaFuncAttributeMaxDynamicSharedMemorySize, lg_smem_bytes<1>());
    cudaFuncSetAttribute(res_gemm_kernel<DM>, cudaFuncAttributeMaxDynamicSharedMemorySize, RG_SMEM);
    cudaFuncSetAttribute(res_gemm_kernel<FF>, cudaFuncAttributeMaxDynamicSharedMemorySize, RG_SMEM);
    cudaFuncSetAttribute(attn_kernel, cudaFuncAttributeMaxDynamicSharedMemorySize, AT_SMEM);
  }
  CUtensorMap tm_wqkv, tm_wg, tm_wu, tm_wo64, tm_wo16, tm_wd64, tm_wd16, tm_o, tm_hh;
  make_map(enc, &tm_wqkv, wqkv, DM, 3 * DM, 32, 64, CU_TENSOR_MAP_SWIZZLE_128B);
  make_map(enc, &tm_wg, wg, DM, FF, 16, 64, CU_TENSOR_MAP_SWIZZLE_128B);
  make_map(enc, &tm_wu, wu, DM, FF, 16, 64, CU_TENSOR_MAP_SWIZZLE_128B);
  make_map(enc, &tm_wo64, wo, DM, DM, 64, 64, CU_TENSOR_MAP_SWIZZLE_128B);
  make_map(enc, &tm_wo16, wo, DM, DM, 64, 16, CU_TENSOR_MAP_SWIZZLE_32B);
  make_map(enc, &tm_wd64, wd, FF, DM, 64, 64, CU_TENSOR_MAP_SWIZZLE_128B);
  make_map(enc, &tm_wd16, wd, FF, DM, 64, 16, CU_TENSOR_MAP_SWIZZLE_32B);
  make_map(enc, &tm_o, p_o, SEQ, DM, 64, 64, CU_TENSOR_MAP_SWIZZLE_128B);
  make_map(enc, &tm_hh, p_hh, SEQ, FF, 64, 64, CU_TENSOR_MAP_SWIZZLE_128B);

  launch(ln_gemm_kernel<0>, 128, LG_THREADS, lg_smem_bytes<0>(), 2, false, tm_wqkv, tm_wqkv, tm_wqkv, x);
  launch(attn_kernel, 128, AT_THREADS, AT_SMEM, 1, true);
  launch(res_gemm_kernel<DM>, 128, RG_THREADS, RG_SMEM, 2, true, tm_o, tm_wo64, tm_wo16, x, (bf16*)p_h);
  launch(ln_gemm_kernel<1>, 128, LG_THREADS, lg_smem_bytes<1>(), 2, true, tm_wg, tm_wu, tm_hh, (const bf16*)p_h);
  launch(res_gemm_kernel<FF>, 128, RG_THREADS, RG_SMEM, 2, true, tm_hh, tm_wd64, tm_wd16, (const bf16*)p_h, out);
}
```

```cpp
#include <cuda_runtime.h>
#include <cuda_bf16.h>
#include <cuda.h>
#include <stdint.h>

typedef __nv_bfloat16 bf16;

constexpr int SEQ = 2048, DM = 640, NH = 32, DH = 20, FF = 1536;
constexpr int IMG_HEAD_ELEMS = (SEQ / 8) * 192;

__device__ __align__(1024) bf16 g_img[3 * NH * IMG_HEAD_ELEMS];
__device__ __align__(1024) bf16 g_o[SEQ * DM];
__device__ __align__(1024) bf16 g_h[SEQ * DM];
__device__ __align__(1024) bf16 g_xn[SEQ * DM];
__device__ __align__(1024) bf16 g_hh[SEQ * FF];

#define TS(k, i)
__device__ __forceinline__ uint32_t smem_u32(const void* p) { return (uint32_t)__cvta_generic_to_shared(p); }
__device__ __forceinline__ void mbar_init(uint32_t bar, uint32_t cnt) {
  asm volatile("mbarrier.init.shared::cta.b64 [%0], %1;" ::"r"(bar), "r"(cnt) : "memory");
}
__device__ __forceinline__ void mbar_expect_tx(uint32_t bar, uint32_t bytes) {
  asm volatile("mbarrier.arrive.expect_tx.shared::cta.b64 _, [%0], %1;" ::"r"(bar), "r"(bytes) : "memory");
}
__device__ __forceinline__ void mbar_arrive(uint32_t bar) {
  asm volatile("mbarrier.arrive.shared::cta.b64 _, [%0];" ::"r"(bar) : "memory");
}
__device__ __forceinline__ void mbar_arrive_cluster(uint32_t bar, uint32_t cta) {
  asm volatile(
      "{\n.reg .b32 r;\nmapa.shared::cluster.u32 r, %0, %1;\n"
      "mbarrier.arrive.shared::cluster.b64 _, [r];\n}\n" ::"r"(bar), "r"(cta)
      : "memory");
}
__device__ __forceinline__ void mbar_wait(uint32_t bar, uint32_t parity) {
  asm volatile(
      "{\n.reg .pred p;\nLAB_WAIT:\n"
      "mbarrier.try_wait.parity.shared::cta.b64 p, [%0], %1;\n"
      "@p bra DONE;\nbra LAB_WAIT;\nDONE:\n}\n" ::"r"(bar), "r"(parity)
      : "memory");
}
__device__ __forceinline__ void mbar_wait_cluster(uint32_t bar, uint32_t parity) {
  asm volatile(
      "{\n.reg .pred p;\nLAB_WAIT:\n"
      "mbarrier.try_wait.parity.acquire.cluster.shared::cta.b64 p, [%0], %1;\n"
      "@p bra DONE;\nbra LAB_WAIT;\nDONE:\n}\n" ::"r"(bar), "r"(parity)
      : "memory");
}
__device__ __forceinline__ void fence_mbar_init() { asm volatile("fence.mbarrier_init.release.cluster;" ::: "memory"); }
__device__ __forceinline__ void fence_proxy_async() { asm volatile("fence.proxy.async.shared::cta;" ::: "memory"); }
__device__ __forceinline__ void cluster_sync_all() {
  asm volatile("barrier.cluster.arrive.release.aligned;\nbarrier.cluster.wait.acquire.aligned;" ::: "memory");
}
__device__ __forceinline__ void cluster_sync_relaxed() {
  asm volatile("barrier.cluster.arrive.relaxed.aligned;\nbarrier.cluster.wait.aligned;" ::: "memory");
}
__device__ __forceinline__ void named_bar_sync(int id, int n) { asm volatile("bar.sync %0, %1;" ::"r"(id), "r"(n) : "memory"); }
__device__ __forceinline__ void pdl_launch() { asm volatile("griddepcontrol.launch_dependents;" ::: "memory"); }
__device__ __forceinline__ void pdl_wait() { asm volatile("griddepcontrol.wait;" ::: "memory"); }

__device__ __forceinline__ void tma_load_2d(uint32_t dst, const CUtensorMap* tm, int c0, int c1, uint32_t bar) {
  asm volatile(
      "cp.async.bulk.tensor.2d.shared::cluster.global.mbarrier::complete_tx::bytes [%0], [%1, {%3, %4}], [%2];" ::"r"(dst),
      "l"((uint64_t)tm), "r"(bar), "r"(c0), "r"(c1)
      : "memory");
}
__device__ __forceinline__ void tma_load_2d_mc(uint32_t dst, const CUtensorMap* tm, int c0, int c1, uint32_t bar, uint16_t mask) {
  asm volatile(
      "cp.async.bulk.tensor.2d.shared::cluster.global.mbarrier::complete_tx::bytes.multicast::cluster [%0], [%1, {%3, %4}], [%2], %5;" ::"r"(dst),
      "l"((uint64_t)tm), "r"(bar), "r"(c0), "r"(c1), "h"(mask)
      : "memory");
}
__device__ __forceinline__ void bulk_g2s(uint32_t dst, const void* src, uint32_t bytes, uint32_t bar) {
  asm volatile("cp.async.bulk.shared::cluster.global.mbarrier::complete_tx::bytes [%0], [%1], %2, [%3];" ::"r"(dst), "l"(src),
               "r"(bytes), "r"(bar)
               : "memory");
}
__device__ __forceinline__ void bulk_s2g(void* dst, uint32_t src, uint32_t bytes) {
  asm volatile("cp.async.bulk.global.shared::cta.bulk_group [%0], [%1], %2;" ::"l"(dst), "r"(src), "r"(bytes) : "memory");
}
__device__ __forceinline__ void tma_store_2d(const CUtensorMap* tm, uint32_t src, int c0, int c1) {
  asm volatile("cp.async.bulk.tensor.2d.global.shared::cta.bulk_group [%0, {%2, %3}], [%1];" ::"l"((uint64_t)tm), "r"(src), "r"(c0), "r"(c1) : "memory");
}
__device__ __forceinline__ void bulk_commit() { asm volatile("cp.async.bulk.commit_group;" ::: "memory"); }
__device__ __forceinline__ void bulk_wait_read() { asm volatile("cp.async.bulk.wait_group.read 0;" ::: "memory"); }
__device__ __forceinline__ void prefetch_l2(const void* p, uint32_t bytes) {
  asm volatile("cp.async.bulk.prefetch.L2.global [%0], %1;" ::"l"(p), "r"(bytes) : "memory");
}
__device__ __forceinline__ void bulk_wait_all() { asm volatile("cp.async.bulk.wait_group 0;" ::: "memory"); }
__device__ __forceinline__ void st_shared_b32(uint32_t addr, uint32_t v) { asm volatile("st.shared.b32 [%0], %1;" ::"r"(addr), "r"(v) : "memory"); }
__device__ __forceinline__ void st_shared_v2(uint32_t addr, uint32_t a, uint32_t b) { asm volatile("st.shared.v2.b32 [%0], {%1, %2};" ::"r"(addr), "r"(a), "r"(b) : "memory"); }
__device__ __forceinline__ void prefetch_tmap(const CUtensorMap* tm) {
  asm volatile("prefetch.tensormap [%0];" ::"l"((uint64_t)tm) : "memory");
}
__device__ __forceinline__ void wgmma_fence() { asm volatile("wgmma.fence.sync.aligned;" ::: "memory"); }
__device__ __forceinline__ void wgmma_commit() { asm volatile("wgmma.commit_group.sync.aligned;" ::: "memory"); }
template <int N>
__device__ __forceinline__ void wgmma_wait() { asm volatile("wgmma.wait_group.sync.aligned %0;" ::"n"(N) : "memory"); }

__device__ __forceinline__ uint64_t make_desc(uint32_t addr, uint32_t lbo, uint32_t sbo, uint32_t layout) {
  return (uint64_t)((addr & 0x3FFFF) >> 4) | ((uint64_t)((lbo & 0x3FFFF) >> 4) << 16) | ((uint64_t)((sbo & 0x3FFFF) >> 4) << 32) |
         ((uint64_t)layout << 62);
}
__device__ __forceinline__ uint32_t pack_bf16(float lo, float hi) {
  uint32_t r;
  asm("cvt.rn.bf16x2.f32 %0, %1, %2;" : "=r"(r) : "f"(hi), "f"(lo));
  return r;
}
__device__ __forceinline__ float bf16_round(float x) { return __bfloat162float(__float2bfloat16_rn(x)); }
__device__ __forceinline__ float bf_lo(uint32_t u) { return __uint_as_float(u << 16); }
__device__ __forceinline__ float bf_hi(uint32_t u) { return __uint_as_float(u & 0xffff0000u); }
__device__ __forceinline__ float ex2(float x) {
  float y;
  asm("ex2.approx.ftz.f32 %0, %1;" : "=f"(y) : "f"(x));
  return y;
}

__device__ __forceinline__ void wgmma_ss_n240_tb(float (&d)[120], uint64_t descA, uint64_t descB, int scaleD) {
  asm volatile("{\n.reg .pred p;\nsetp.ne.b32 p, %122, 0;\n"
    "wgmma.mma_async.sync.aligned.m64n240k16.f32.bf16.bf16 {%0, %1, %2, %3, %4, %5, %6, %7, %8, %9, %10, %11, %12, %13, %14, %15, %16, %17, %18, %19, %20, %21, %22, %23, %24, %25, %26, %27, %28, %29, %30, %31, %32, %33, %34, %35, %36, %37, %38, %39, %40, %41, %42, %43, %44, %45, %46, %47, %48, %49, %50, %51, %52, %53, %54, %55, %56, %57, %58, %59, %60, %61, %62, %63, %64, %65, %66, %67, %68, %69, %70, %71, %72, %73, %74, %75, %76, %77, %78, %79, %80, %81, %82, %83, %84, %85, %86, %87, %88, %89, %90, %91, %92, %93, %94, %95, %96, %97, %98, %99, %100, %101, %102, %103, %104, %105, %106, %107, %108, %109, %110, %111, %112, %113, %114, %115, %116, %117, %118, %119}, %120, %121, p, 1, 1, 0, 1;\n}\n"
    : "+f"(d[0]), "+f"(d[1]), "+f"(d[2]), "+f"(d[3]), "+f"(d[4]), "+f"(d[5]), "+f"(d[6]), "+f"(d[7]), "+f"(d[8]), "+f"(d[9]), "+f"(d[10]), "+f"(d[11]), "+f"(d[12]), "+f"(d[13]), "+f"(d[14]), "+f"(d[15]), "+f"(d[16]), "+f"(d[17]), "+f"(d[18]), "+f"(d[19]), "+f"(d[20]), "+f"(d[21]), "+f"(d[22]), "+f"(d[23]), "+f"(d[24]), "+f"(d[25]), "+f"(d[26]), "+f"(d[27]), "+f"(d[28]), "+f"(d[29]), "+f"(d[30]), "+f"(d[31]), "+f"(d[32]), "+f"(d[33]), "+f"(d[34]), "+f"(d[35]), "+f"(d[36]), "+f"(d[37]), "+f"(d[38]), "+f"(d[39]), "+f"(d[40]), "+f"(d[41]), "+f"(d[42]), "+f"(d[43]), "+f"(d[44]), "+f"(d[45]), "+f"(d[46]), "+f"(d[47]), "+f"(d[48]), "+f"(d[49]), "+f"(d[50]), "+f"(d[51]), "+f"(d[52]), "+f"(d[53]), "+f"(d[54]), "+f"(d[55]), "+f"(d[56]), "+f"(d[57]), "+f"(d[58]), "+f"(d[59]), "+f"(d[60]), "+f"(d[61]), "+f"(d[62]), "+f"(d[63]), "+f"(d[64]), "+f"(d[65]), "+f"(d[66]), "+f"(d[67]), "+f"(d[68]), "+f"(d[69]), "+f"(d[70]), "+f"(d[71]), "+f"(d[72]), "+f"(d[73]), "+f"(d[74]), "+f"(d[75]), "+f"(d[76]), "+f"(d[77]), "+f"(d[78]), "+f"(d[79]), "+f"(d[80]), "+f"(d[81]), "+f"(d[82]), "+f"(d[83]), "+f"(d[84]), "+f"(d[85]), "+f"(d[86]), "+f"(d[87]), "+f"(d[88]), "+f"(d[89]), "+f"(d[90]), "+f"(d[91]), "+f"(d[92]), "+f"(d[93]), "+f"(d[94]), "+f"(d[95]), "+f"(d[96]), "+f"(d[97]), "+f"(d[98]), "+f"(d[99]), "+f"(d[100]), "+f"(d[101]), "+f"(d[102]), "+f"(d[103]), "+f"(d[104]), "+f"(d[105]), "+f"(d[106]), "+f"(d[107]), "+f"(d[108]), "+f"(d[109]), "+f"(d[110]), "+f"(d[111]), "+f"(d[112]), "+f"(d[113]), "+f"(d[114]), "+f"(d[115]), "+f"(d[116]), "+f"(d[117]), "+f"(d[118]), "+f"(d[119])
    : "l"(descA), "l"(descB), "r"(scaleD));
}
__device__ __forceinline__ void wgmma_ss_n192_tb(float (&d)[96], uint64_t descA, uint64_t descB, int scaleD) {
  asm volatile("{\n.reg .pred p;\nsetp.ne.b32 p, %98, 0;\n"
    "wgmma.mma_async.sync.aligned.m64n192k16.f32.bf16.bf16 {%0, %1, %2, %3, %4, %5, %6, %7, %8, %9, %10, %11, %12, %13, %14, %15, %16, %17, %18, %19, %20, %21, %22, %23, %24, %25, %26, %27, %28, %29, %30, %31, %32, %33, %34, %35, %36, %37, %38, %39, %40, %41, %42, %43, %44, %45, %46, %47, %48, %49, %50, %51, %52, %53, %54, %55, %56, %57, %58, %59, %60, %61, %62, %63, %64, %65, %66, %67, %68, %69, %70, %71, %72, %73, %74, %75, %76, %77, %78, %79, %80, %81, %82, %83, %84, %85, %86, %87, %88, %89, %90, %91, %92, %93, %94, %95}, %96, %97, p, 1, 1, 0, 1;\n}\n"
    : "+f"(d[0]), "+f"(d[1]), "+f"(d[2]), "+f"(d[3]), "+f"(d[4]), "+f"(d[5]), "+f"(d[6]), "+f"(d[7]), "+f"(d[8]), "+f"(d[9]), "+f"(d[10]), "+f"(d[11]), "+f"(d[12]), "+f"(d[13]), "+f"(d[14]), "+f"(d[15]), "+f"(d[16]), "+f"(d[17]), "+f"(d[18]), "+f"(d[19]), "+f"(d[20]), "+f"(d[21]), "+f"(d[22]), "+f"(d[23]), "+f"(d[24]), "+f"(d[25]), "+f"(d[26]), "+f"(d[27]), "+f"(d[28]), "+f"(d[29]), "+f"(d[30]), "+f"(d[31]), "+f"(d[32]), "+f"(d[33]), "+f"(d[34]), "+f"(d[35]), "+f"(d[36]), "+f"(d[37]), "+f"(d[38]), "+f"(d[39]), "+f"(d[40]), "+f"(d[41]), "+f"(d[42]), "+f"(d[43]), "+f"(d[44]), "+f"(d[45]), "+f"(d[46]), "+f"(d[47]), "+f"(d[48]), "+f"(d[49]), "+f"(d[50]), "+f"(d[51]), "+f"(d[52]), "+f"(d[53]), "+f"(d[54]), "+f"(d[55]), "+f"(d[56]), "+f"(d[57]), "+f"(d[58]), "+f"(d[59]), "+f"(d[60]), "+f"(d[61]), "+f"(d[62]), "+f"(d[63]), "+f"(d[64]), "+f"(d[65]), "+f"(d[66]), "+f"(d[67]), "+f"(d[68]), "+f"(d[69]), "+f"(d[70]), "+f"(d[71]), "+f"(d[72]), "+f"(d[73]), "+f"(d[74]), "+f"(d[75]), "+f"(d[76]), "+f"(d[77]), "+f"(d[78]), "+f"(d[79]), "+f"(d[80]), "+f"(d[81]), "+f"(d[82]), "+f"(d[83]), "+f"(d[84]), "+f"(d[85]), "+f"(d[86]), "+f"(d[87]), "+f"(d[88]), "+f"(d[89]), "+f"(d[90]), "+f"(d[91]), "+f"(d[92]), "+f"(d[93]), "+f"(d[94]), "+f"(d[95])
    : "l"(descA), "l"(descB), "r"(scaleD));
}
__device__ __forceinline__ void wgmma_ss_n64_tb(float (&d)[32], uint64_t descA, uint64_t descB, int scaleD) {
  asm volatile("{\n.reg .pred p;\nsetp.ne.b32 p, %34, 0;\n"
    "wgmma.mma_async.sync.aligned.m64n64k16.f32.bf16.bf16 {%0, %1, %2, %3, %4, %5, %6, %7, %8, %9, %10, %11, %12, %13, %14, %15, %16, %17, %18, %19, %20, %21, %22, %23, %24, %25, %26, %27, %28, %29, %30, %31}, %32, %33, p, 1, 1, 0, 1;\n}\n"
    : "+f"(d[0]), "+f"(d[1]), "+f"(d[2]), "+f"(d[3]), "+f"(d[4]), "+f"(d[5]), "+f"(d[6]), "+f"(d[7]), "+f"(d[8]), "+f"(d[9]), "+f"(d[10]), "+f"(d[11]), "+f"(d[12]), "+f"(d[13]), "+f"(d[14]), "+f"(d[15]), "+f"(d[16]), "+f"(d[17]), "+f"(d[18]), "+f"(d[19]), "+f"(d[20]), "+f"(d[21]), "+f"(d[22]), "+f"(d[23]), "+f"(d[24]), "+f"(d[25]), "+f"(d[26]), "+f"(d[27]), "+f"(d[28]), "+f"(d[29]), "+f"(d[30]), "+f"(d[31])
    : "l"(descA), "l"(descB), "r"(scaleD));
}
__device__ __forceinline__ void wgmma_ss_n16_tb(float (&d)[8], uint64_t descA, uint64_t descB, int scaleD) {
  asm volatile("{\n.reg .pred p;\nsetp.ne.b32 p, %10, 0;\n"
    "wgmma.mma_async.sync.aligned.m64n16k16.f32.bf16.bf16 {%0, %1, %2, %3, %4, %5, %6, %7}, %8, %9, p, 1, 1, 0, 1;\n}\n"
    : "+f"(d[0]), "+f"(d[1]), "+f"(d[2]), "+f"(d[3]), "+f"(d[4]), "+f"(d[5]), "+f"(d[6]), "+f"(d[7])
    : "l"(descA), "l"(descB), "r"(scaleD));
}
__device__ __forceinline__ void wgmma_rs_n128(float (&d)[64], uint32_t a0, uint32_t a1, uint32_t a2, uint32_t a3, uint64_t descB, int scaleD) {
  asm volatile("{\n.reg .pred p;\nsetp.ne.b32 p, %69, 0;\n"
    "wgmma.mma_async.sync.aligned.m64n128k16.f32.bf16.bf16 {%0, %1, %2, %3, %4, %5, %6, %7, %8, %9, %10, %11, %12, %13, %14, %15, %16, %17, %18, %19, %20, %21, %22, %23, %24, %25, %26, %27, %28, %29, %30, %31, %32, %33, %34, %35, %36, %37, %38, %39, %40, %41, %42, %43, %44, %45, %46, %47, %48, %49, %50, %51, %52, %53, %54, %55, %56, %57, %58, %59, %60, %61, %62, %63}, {%64, %65, %66, %67}, %68, p, 1, 1, 0;\n}\n"
    : "+f"(d[0]), "+f"(d[1]), "+f"(d[2]), "+f"(d[3]), "+f"(d[4]), "+f"(d[5]), "+f"(d[6]), "+f"(d[7]), "+f"(d[8]), "+f"(d[9]), "+f"(d[10]), "+f"(d[11]), "+f"(d[12]), "+f"(d[13]), "+f"(d[14]), "+f"(d[15]), "+f"(d[16]), "+f"(d[17]), "+f"(d[18]), "+f"(d[19]), "+f"(d[20]), "+f"(d[21]), "+f"(d[22]), "+f"(d[23]), "+f"(d[24]), "+f"(d[25]), "+f"(d[26]), "+f"(d[27]), "+f"(d[28]), "+f"(d[29]), "+f"(d[30]), "+f"(d[31]), "+f"(d[32]), "+f"(d[33]), "+f"(d[34]), "+f"(d[35]), "+f"(d[36]), "+f"(d[37]), "+f"(d[38]), "+f"(d[39]), "+f"(d[40]), "+f"(d[41]), "+f"(d[42]), "+f"(d[43]), "+f"(d[44]), "+f"(d[45]), "+f"(d[46]), "+f"(d[47]), "+f"(d[48]), "+f"(d[49]), "+f"(d[50]), "+f"(d[51]), "+f"(d[52]), "+f"(d[53]), "+f"(d[54]), "+f"(d[55]), "+f"(d[56]), "+f"(d[57]), "+f"(d[58]), "+f"(d[59]), "+f"(d[60]), "+f"(d[61]), "+f"(d[62]), "+f"(d[63])
    : "r"(a0), "r"(a1), "r"(a2), "r"(a3), "l"(descB), "r"(scaleD));
}
__device__ __forceinline__ void wgmma_rs_n64(float (&d)[32], uint32_t a0, uint32_t a1, uint32_t a2, uint32_t a3, uint64_t descB, int scaleD) {
  asm volatile("{\n.reg .pred p;\nsetp.ne.b32 p, %37, 0;\n"
    "wgmma.mma_async.sync.aligned.m64n64k16.f32.bf16.bf16 {%0, %1, %2, %3, %4, %5, %6, %7, %8, %9, %10, %11, %12, %13, %14, %15, %16, %17, %18, %19, %20, %21, %22, %23, %24, %25, %26, %27, %28, %29, %30, %31}, {%32, %33, %34, %35}, %36, p, 1, 1, 0;\n}\n"
    : "+f"(d[0]), "+f"(d[1]), "+f"(d[2]), "+f"(d[3]), "+f"(d[4]), "+f"(d[5]), "+f"(d[6]), "+f"(d[7]), "+f"(d[8]), "+f"(d[9]), "+f"(d[10]), "+f"(d[11]), "+f"(d[12]), "+f"(d[13]), "+f"(d[14]), "+f"(d[15]), "+f"(d[16]), "+f"(d[17]), "+f"(d[18]), "+f"(d[19]), "+f"(d[20]), "+f"(d[21]), "+f"(d[22]), "+f"(d[23]), "+f"(d[24]), "+f"(d[25]), "+f"(d[26]), "+f"(d[27]), "+f"(d[28]), "+f"(d[29]), "+f"(d[30]), "+f"(d[31])
    : "r"(a0), "r"(a1), "r"(a2), "r"(a3), "l"(descB), "r"(scaleD));
}
__device__ __forceinline__ void wgmma_rs_n24_tb(float (&d)[12], uint32_t a0, uint32_t a1, uint32_t a2, uint32_t a3, uint64_t descB, int scaleD) {
  asm volatile("{\n.reg .pred p;\nsetp.ne.b32 p, %17, 0;\n"
    "wgmma.mma_async.sync.aligned.m64n24k16.f32.bf16.bf16 {%0, %1, %2, %3, %4, %5, %6, %7, %8, %9, %10, %11}, {%12, %13, %14, %15}, %16, p, 1, 1, 1;\n}\n"
    : "+f"(d[0]), "+f"(d[1]), "+f"(d[2]), "+f"(d[3]), "+f"(d[4]), "+f"(d[5]), "+f"(d[6]), "+f"(d[7]), "+f"(d[8]), "+f"(d[9]), "+f"(d[10]), "+f"(d[11])
    : "r"(a0), "r"(a1), "r"(a2), "r"(a3), "l"(descB), "r"(scaleD));
}

__global__ void __launch_bounds__(256) ln_kernel(const bf16* __restrict__ xin, bf16* __restrict__ xout, int tsk) {
  const int warp = threadIdx.x >> 5, lane = threadIdx.x & 31;
  const int hw = lane >> 4, l16 = lane & 15;
  const int row = (blockIdx.x * 8 + warp) * 2 + hw;
  pdl_launch();
  pdl_wait();
  const uint4* src = reinterpret_cast<const uint4*>(xin + (size_t)row * DM);
  uint4 v[5];
#pragma unroll
  for (int j = 0; j < 5; j++) v[j] = __ldg(src + j * 16 + l16);
  float s0 = 0.f, s1 = 0.f, s2 = 0.f, s3 = 0.f;
#pragma unroll
  for (int j = 0; j < 5; j++) {
    s0 += bf_lo(v[j].x) + bf_hi(v[j].x);
    s1 += bf_lo(v[j].y) + bf_hi(v[j].y);
    s2 += bf_lo(v[j].z) + bf_hi(v[j].z);
    s3 += bf_lo(v[j].w) + bf_hi(v[j].w);
  }
  float mean = (s0 + s1) + (s2 + s3);
#pragma unroll
  for (int o = 1; o < 16; o <<= 1) mean += __shfl_xor_sync(0xffffffffu, mean, o);
  mean *= (1.0f / DM);
  s0 = s1 = s2 = s3 = 0.f;
#pragma unroll
  for (int j = 0; j < 5; j++) {
    float d;
    d = bf_lo(v[j].x) - mean; s0 = fmaf(d, d, s0);
    d = bf_hi(v[j].x) - mean; s1 = fmaf(d, d, s1);
    d = bf_lo(v[j].y) - mean; s2 = fmaf(d, d, s2);
    d = bf_hi(v[j].y) - mean; s3 = fmaf(d, d, s3);
    d = bf_lo(v[j].z) - mean; s0 = fmaf(d, d, s0);
    d = bf_hi(v[j].z) - mean; s1 = fmaf(d, d, s1);
    d = bf_lo(v[j].w) - mean; s2 = fmaf(d, d, s2);
    d = bf_hi(v[j].w) - mean; s3 = fmaf(d, d, s3);
  }
  float sq = (s0 + s1) + (s2 + s3);
#pragma unroll
  for (int o = 1; o < 16; o <<= 1) sq += __shfl_xor_sync(0xffffffffu, sq, o);
  const float var_b = bf16_round(sq * (1.0f / DM));
  const float den = bf16_round(sqrtf(bf16_round(var_b + 1e-5f)));
  const float iv = __frcp_rn(den);
  const float mb = bf16_round(mean);
  uint4* dst = reinterpret_cast<uint4*>(xout + (size_t)row * DM);
#pragma unroll
  for (int j = 0; j < 5; j++) {
    uint4 w;
    uint32_t t;
    t = pack_bf16(bf_lo(v[j].x) - mb, bf_hi(v[j].x) - mb); w.x = pack_bf16(bf_lo(t) * iv, bf_hi(t) * iv);
    t = pack_bf16(bf_lo(v[j].y) - mb, bf_hi(v[j].y) - mb); w.y = pack_bf16(bf_lo(t) * iv, bf_hi(t) * iv);
    t = pack_bf16(bf_lo(v[j].z) - mb, bf_hi(v[j].z) - mb); w.z = pack_bf16(bf_lo(t) * iv, bf_hi(t) * iv);
    t = pack_bf16(bf_lo(v[j].w) - mb, bf_hi(v[j].w) - mb); w.w = pack_bf16(bf_lo(t) * iv, bf_hi(t) * iv);
    dst[j * 16 + l16] = w;
  }
}

constexpr int LG_THREADS = 384;
constexpr int LG_STAGES = 5;
template <int MODE>
struct LGCfg {
  static constexpr int NSLAB = MODE == 0 ? 4 : 6;
  static constexpr int STAGE_BYTES = 8192 + NSLAB * 4096;
  static constexpr int SMEM = LG_STAGES * STAGE_BYTES + 128 + 1024;
};

template <int WG>
__device__ __forceinline__ void qkv_mainloop(float (&acc)[120], uint32_t sbase, uint32_t sBar, bool leader) {
  constexpr int STAGE_BYTES = LGCfg<0>::STAGE_BYTES, NST = LG_STAGES;
  const uint64_t da_base = make_desc(sbase + WG * 4096, 16, 512, 2);
  const uint64_t db_base = make_desc(sbase + 8192, 4096, 1024, 1);
#pragma unroll 1
  for (int r = 0; r < 20 / NST; r++) {
#pragma unroll
    for (int s = 0; s < NST; s++) {
      mbar_wait(sBar + 8 * s, r & 1);
      wgmma_fence();
#pragma unroll
      for (int ks = 0; ks < 2; ks++)
        wgmma_ss_n240_tb(acc, da_base + (uint64_t)((s * STAGE_BYTES + ks * 32) >> 4), db_base + (uint64_t)((s * STAGE_BYTES + ks * 2048) >> 4), 1);
      wgmma_commit();
      wgmma_wait<1>();
      if (leader && (s > 0 || r > 0)) {
        const int ps = (s + NST - 1) % NST;
        mbar_arrive_cluster(sBar + 8 * (NST + ps), 0);
        mbar_arrive_cluster(sBar + 8 * (NST + ps), 1);
      }
    }
  }
}
template <int WG>
__device__ __forceinline__ void glu_mainloop(float (&accg)[96], float (&accu)[96], uint32_t sbase, uint32_t sBar, bool leader) {
  constexpr int STAGE_BYTES = LGCfg<1>::STAGE_BYTES, NST = LG_STAGES;
  const uint64_t da_base = make_desc(sbase + WG * 4096, 16, 512, 2);
  const uint64_t db_base = make_desc(sbase + 8192, 4096, 1024, 1);
#pragma unroll 1
  for (int r = 0; r < 20 / NST; r++) {
#pragma unroll
    for (int s = 0; s < NST; s++) {
      mbar_wait(sBar + 8 * s, r & 1);
      wgmma_fence();
#pragma unroll
      for (int ks = 0; ks < 2; ks++) {
        const uint64_t da = da_base + (uint64_t)((s * STAGE_BYTES + ks * 32) >> 4);
        wgmma_ss_n192_tb(accg, da, db_base + (uint64_t)((s * STAGE_BYTES + ks * 2048) >> 4), 1);
        wgmma_ss_n192_tb(accu, da, db_base + (uint64_t)((s * STAGE_BYTES + 3 * 4096 + ks * 2048) >> 4), 1);
      }
      wgmma_commit();
      wgmma_wait<1>();
      if (leader && (s > 0 || r > 0)) {
        const int ps = (s + NST - 1) % NST;
        mbar_arrive_cluster(sBar + 8 * (NST + ps), 0);
        mbar_arrive_cluster(sBar + 8 * (NST + ps), 1);
      }
    }
  }
}

template <int MODE>
__global__ void __launch_bounds__(LG_THREADS, 1)
big_gemm_kernel(const __grid_constant__ CUtensorMap tmA, const __grid_constant__ CUtensorMap tmB0, const __grid_constant__ CUtensorMap tmB1,
                const __grid_constant__ CUtensorMap tmOut) {
  using C = LGCfg<MODE>;
  constexpr int STAGE_BYTES = C::STAGE_BYTES, NST = LG_STAGES, NKB = 20;
  extern __shared__ uint8_t smem_raw[];
  const uint32_t sbase = (smem_u32(smem_raw) + 1023u) & ~1023u;
  const uint32_t sBar = sbase + NST * STAGE_BYTES;
  const int tid = threadIdx.x, warp = tid >> 5, lane = tid & 31;
  const int rank = blockIdx.x & 1;
  const int pair = blockIdx.x >> 1;
  const int n_blk = pair & 7;
  const int m_blk = (pair >> 3) * 2 + rank;
  TS(MODE * 3, 0);
  if (tid == 256) {
    prefetch_tmap(&tmA);
    prefetch_tmap(&tmB0);
    if (MODE == 1) { prefetch_tmap(&tmB1); prefetch_tmap(&tmOut); }
  }
  if (tid == 0) {
    for (int s = 0; s < NST; s++) {
      mbar_init(sBar + 8 * s, 1);
      mbar_init(sBar + 8 * (NST + s), 4);
    }
    fence_mbar_init();
  }
  pdl_launch();
  cluster_sync_all();

  if (warp >= 8) {
    asm volatile("setmaxnreg.dec.sync.aligned.u32 40;");
    if (tid == 256) {
      auto issue_b = [&](int kb) {
        const int s = kb % NST;
        const uint32_t full = sBar + 8 * s;
        mbar_expect_tx(full, STAGE_BYTES);
        const uint32_t dst = sbase + s * STAGE_BYTES + 8192;
        if (MODE == 0) {
#pragma unroll
          for (int j = 0; j < 2; j++) {
            const int sl = rank * 2 + j;
            tma_load_2d_mc(dst + sl * 4096, &tmB0, n_blk * 240 + sl * 64, kb * 32, full, (uint16_t)3);
          }
        } else {
#pragma unroll
          for (int j = 0; j < 3; j++)
            tma_load_2d_mc(dst + (rank * 3 + j) * 4096, rank == 0 ? &tmB0 : &tmB1, n_blk * 192 + j * 64, kb * 32, full, (uint16_t)3);
        }
      };
      for (int kb = 0; kb < NST; kb++) issue_b(kb);
      pdl_wait();
      for (int kb = 0; kb < NKB; kb++) {
        const int s = kb % NST;
        if (kb >= NST) {
          mbar_wait(sBar + 8 * (NST + s), ((kb / NST) & 1) ^ 1);
          issue_b(kb);
        }
        tma_load_2d(sbase + s * STAGE_BYTES, &tmA, kb * 32, m_blk * 128, sBar + 8 * s);
      }
    }
  } else {
    asm volatile("setmaxnreg.inc.sync.aligned.u32 232;");
    const int wg = __shfl_sync(0xffffffffu, warp >> 2, 0);
    const int wwarp = warp & 3;
    TS(MODE * 3, 1);
    mbar_wait(sBar, 0);
    TS(MODE * 3, 3);
    if (MODE == 0) {
      float acc[120];
#pragma unroll
      for (int i = 0; i < 120; i++) acc[i] = 0.f;
      if (wg == 0) qkv_mainloop<0>(acc, sbase, sBar, (tid & 127) == 0);
      else qkv_mainloop<1>(acc, sbase, sBar, (tid & 127) == 0);
      wgmma_wait<0>();
      TS(0, 4);
      named_bar_sync(3, 256);
      const int g = lane >> 2, c4 = lane & 3;
      const uint32_t stg = sbase + wg * (12 * 3072) + (wwarp * 2) * 384 + g * 16;
      const int hbase = n_blk * 12;
#pragma unroll
      for (int j = 0; j < 30; j++) {
        const int cb = (j * 8) % 20;
        const int hb = (j * 8) / 20;
        int d = cb + c4 * 2;
        int hl = hb;
        if (cb == 16 && c4 >= 2) { d -= 20; hl += 1; }
        const uint32_t a0 = stg + hl * 3072 + (d >> 3) * 128 + (d & 7) * 2;
        st_shared_b32(a0, pack_bf16(acc[4 * j], acc[4 * j + 1]));
        st_shared_b32(a0 + 384, pack_bf16(acc[4 * j + 2], acc[4 * j + 3]));
        if (d == 18) {
          const uint32_t pad = (hbase + hl >= 64) ? 0x00003f80u : 0u;
          st_shared_v2(a0 + 4, pad, 0u);
          st_shared_v2(a0 + 388, pad, 0u);
        }
      }
      fence_proxy_async();
      named_bar_sync(1 + wg, 128);
      if ((tid & 127) < 12) {
        const int hl = tid & 127;
        bf16* dst = g_img + (size_t)(hbase + hl) * IMG_HEAD_ELEMS + (size_t)(m_blk * 16 + wg * 8) * 192;
        bulk_s2g(dst, sbase + wg * (12 * 3072) + hl * 3072, 3072);
        bulk_commit();
        bulk_wait_read();
      }
    } else {
      float accg[96], accu[96];
#pragma unroll
      for (int i = 0; i < 96; i++) { accg[i] = 0.f; accu[i] = 0.f; }
      if (wg == 0) glu_mainloop<0>(accg, accu, sbase, sBar, (tid & 127) == 0);
      else glu_mainloop<1>(accg, accu, sbase, sBar, (tid & 127) == 0);
      wgmma_wait<0>();
      TS(3, 4);
      named_bar_sync(3, 256);
      const int g = lane >> 2, c4 = lane & 3;
      const uint32_t stg = sbase + wg * 24576 + (wwarp * 16 + g) * 128 + c4 * 4;
#pragma unroll
      for (int j = 0; j < 24; j++) {
        uint32_t pk[2];
#pragma unroll
        for (int h = 0; h < 2; h++) {
          const uint32_t gp = pack_bf16(accg[4 * j + 2 * h], accg[4 * j + 2 * h + 1]);
          const uint32_t up = pack_bf16(accu[4 * j + 2 * h], accu[4 * j + 2 * h + 1]);
          const float g0 = bf_lo(gp), g1 = bf_hi(gp);
          const float r0 = (g0 * (g0 > 0.f ? 1.f : 0.f)) * bf_lo(up);
          const float r1 = (g1 * (g1 > 0.f ? 1.f : 0.f)) * bf_hi(up);
          pk[h] = pack_bf16(r0, r1);
        }
        const uint32_t a0 = stg + (j >> 3) * 8192 + (((j & 7) ^ g) << 4);
        st_shared_b32(a0, pk[0]);
        st_shared_b32(a0 + 1024, pk[1]);
      }
      fence_proxy_async();
      named_bar_sync(1 + wg, 128);
      if ((tid & 127) == 0) {
#pragma unroll
        for (int sl = 0; sl < 3; sl++) tma_store_2d(&tmOut, sbase + wg * 24576 + sl * 8192, n_blk * 192 + sl * 64, m_blk * 128 + wg * 64);
        bulk_commit();
        bulk_wait_read();
      }
    }
  }
  __syncwarp();
  TS(MODE * 3, 5);
  cluster_sync_relaxed();
  TS(MODE * 3, 6);
}

constexpr int RG_THREADS = 288;
constexpr int RG_STAGES = 8;
constexpr int RG_STAGE_BYTES = 16384 + 8192 + 2048;
constexpr int RG_SMEM = RG_STAGES * RG_STAGE_BYTES + 256 + 1024;

template <int NKB, int NST, int WG>
__device__ __forceinline__ void res_mainloop(float (&acc0)[32], float (&acc1)[8], uint32_t sbase, uint32_t sBar, bool leader) {
  const uint64_t da_base = make_desc(sbase + WG * 8192, 16, 1024, 1);
  const uint64_t db0_base = make_desc(sbase + 16384, 8192, 1024, 1);
  const uint64_t db1_base = make_desc(sbase + 16384 + 8192, 2048, 256, 3);
#pragma unroll 1
  for (int r = 0; r < NKB / NST; r++) {
#pragma unroll
    for (int s = 0; s < NST; s++) {
      const uint64_t so = (uint64_t)(s * (RG_STAGE_BYTES >> 4));
      mbar_wait(sBar + 8 * s, r & 1);
      wgmma_fence();
#pragma unroll
      for (int ks = 0; ks < 4; ks++) {
        wgmma_ss_n64_tb(acc0, da_base + so + ks * 2, db0_base + so + ks * 128, 1);
        wgmma_ss_n16_tb(acc1, da_base + so + ks * 2, db1_base + so + ks * 32, 1);
      }
      wgmma_commit();
      wgmma_wait<1>();
      if (leader && (s > 0 || r > 0)) {
        const int ps = (s + NST - 1) % NST;
        mbar_arrive_cluster(sBar + 8 * (NST + ps), 0);
        mbar_arrive_cluster(sBar + 8 * (NST + ps), 1);
      }
    }
  }
}

template <int KTOT>
__global__ void __launch_bounds__(RG_THREADS, 1)
res_gemm_kernel(const __grid_constant__ CUtensorMap tmA, const __grid_constant__ CUtensorMap tmB64, const __grid_constant__ CUtensorMap tmB16,
                const bf16* __restrict__ resid, bf16* __restrict__ out) {
  constexpr int NKB = KTOT / 64;
  constexpr int NST = (KTOT == DM) ? 5 : 8;
  extern __shared__ uint8_t smem_raw[];
  const uint32_t sbase = (smem_u32(smem_raw) + 1023u) & ~1023u;
  const uint32_t sBar = sbase + NST * RG_STAGE_BYTES;
  const int tid = threadIdx.x, warp = tid >> 5, lane = tid & 31;
  const int rank = blockIdx.x & 1;
  const int pair = blockIdx.x >> 1;
  const int m_blk = pair >> 2;
  const int n_blk = (pair & 3) * 2 + rank;
  const int n0 = n_blk * 80;
  constexpr int TSK = KTOT == DM ? 2 : 4;
  TS(TSK, 0);

  if (tid == 0) {
    for (int s = 0; s < NST; s++) {
      mbar_init(sBar + 8 * s, 1);
      mbar_init(sBar + 8 * (NST + s), 4);
    }
    fence_mbar_init();
  }
  pdl_launch();
  cluster_sync_all();

  if (warp == 8) {
    if (lane == 0) {
      prefetch_tmap(&tmA); prefetch_tmap(&tmB64); prefetch_tmap(&tmB16);
      constexpr int PRE = NKB < NST ? NKB : NST;
      for (int kb = 0; kb < PRE; kb++) {
        const uint32_t full = sBar + 8 * kb;
        const uint32_t st = sbase + kb * RG_STAGE_BYTES;
        mbar_expect_tx(full, RG_STAGE_BYTES);
        tma_load_2d(st + 16384, &tmB64, n0, kb * 64, full);
        tma_load_2d(st + 16384 + 8192, &tmB16, n0 + 64, kb * 64, full);
      }
      pdl_wait();
      for (int kb = 0; kb < NKB; kb++) {
        const int s = kb % NST;
        const uint32_t full = sBar + 8 * s;
        const uint32_t st = sbase + s * RG_STAGE_BYTES;
        if (kb >= PRE) {
          const uint32_t ph = (kb / NST) & 1;
          mbar_wait(sBar + 8 * (NST + s), ph ^ 1);
          mbar_expect_tx(full, RG_STAGE_BYTES);
          tma_load_2d(st + 16384, &tmB64, n0, kb * 64, full);
          tma_load_2d(st + 16384 + 8192, &tmB16, n0 + 64, kb * 64, full);
        }
        tma_load_2d_mc(st + rank * 8192, &tmA, kb * 64, m_blk * 128 + rank * 64, full, (uint16_t)3);
      }
    }
  } else {
    const int wg = __shfl_sync(0xffffffffu, warp >> 2, 0), wwarp = warp & 3;
    const int g = lane >> 2, c4 = lane & 3;
    const int row0 = m_blk * 128 + wg * 64 + wwarp * 16 + g;
    TS(TSK, 1);
    pdl_wait();
    TS(TSK, 2);
    uint32_t res[20];
#pragma unroll
    for (int j = 0; j < 10; j++) {
      res[2 * j] = __ldg(reinterpret_cast<const uint32_t*>(resid + (size_t)row0 * DM + n0 + j * 8 + c4 * 2));
      res[2 * j + 1] = __ldg(reinterpret_cast<const uint32_t*>(resid + (size_t)(row0 + 8) * DM + n0 + j * 8 + c4 * 2));
    }
    float acc0[32], acc1[8];
#pragma unroll
    for (int i = 0; i < 32; i++) acc0[i] = 0.f;
#pragma unroll
    for (int i = 0; i < 8; i++) acc1[i] = 0.f;
    mbar_wait(sBar, 0);
    TS(TSK, 3);
    if (wg == 0) res_mainloop<NKB, NST, 0>(acc0, acc1, sbase, sBar, (tid & 127) == 0);
    else res_mainloop<NKB, NST, 1>(acc0, acc1, sbase, sBar, (tid & 127) == 0);
    wgmma_wait<0>();
    TS(TSK, 4);
#pragma unroll
    for (int j = 0; j < 10; j++) {
      float a[4];
#pragma unroll
      for (int e = 0; e < 4; e++) a[e] = bf16_round(j < 8 ? acc0[4 * j + e] : acc1[4 * (j - 8) + e]);
      const uint32_t o0 = pack_bf16(bf_lo(res[2 * j]) + a[0], bf_hi(res[2 * j]) + a[1]);
      const uint32_t o1 = pack_bf16(bf_lo(res[2 * j + 1]) + a[2], bf_hi(res[2 * j + 1]) + a[3]);
      *reinterpret_cast<uint32_t*>(out + (size_t)row0 * DM + n0 + j * 8 + c4 * 2) = o0;
      *reinterpret_cast<uint32_t*>(out + (size_t)(row0 + 8) * DM + n0 + j * 8 + c4 * 2) = o1;
    }
  }
  __syncwarp();
  TS(TSK, 5);
  cluster_sync_relaxed();
  TS(TSK, 6);
}

constexpr int AT_THREADS = 512;
constexpr int AT_KV_BYTES = IMG_HEAD_ELEMS * 2;
constexpr int AT_SMEM = 2 * AT_KV_BYTES + 256 + 1024;
constexpr int AT_CHUNKS = 8;

__device__ __forceinline__ float exp2_poly(float s, float c64, float b64) {
  const float u = __saturatef(fmaf(s, c64, b64));
  const float MAGIC = 12582912.0f - 64.0f;
  const float r = fmaf(u, 64.0f, MAGIC);
  const float q = MAGIC - r;
  const float fr = fmaf(u, 64.0f, q);
  float p = fmaf(fr, 0.009570102207362652f, 0.05591785907745361f);
  p = fmaf(p, fr, 0.240247443318367f);
  p = fmaf(p, fr, 0.6931217908859253f);
  p = fmaf(p, fr, 0.9999992847442627f);
  return __uint_as_float(__float_as_uint(p) + (__float_as_uint(r) << 23));
}

__global__ void __launch_bounds__(AT_THREADS, 1) attn_kernel(const bf16* __restrict__ wo, const bf16* __restrict__ wgt, const bf16* __restrict__ wup, const bf16* __restrict__ wdn) {
  extern __shared__ uint8_t smem_raw[];
  const uint32_t sbase = (smem_u32(smem_raw) + 1023u) & ~1023u;
  const uint32_t sK = sbase, sV = sbase + AT_KV_BYTES;
  const uint32_t sBar = sV + AT_KV_BYTES;
  const int tid = threadIdx.x, warp = tid >> 5, lane = tid & 31;
  const int head = blockIdx.x >> 2, quarter = blockIdx.x & 3;
  TS(1, 0);
  if (tid == 0) {
    for (int i = 0; i < AT_CHUNKS; i++) mbar_init(sBar + 8 * i, 1);
    fence_mbar_init();
  }
  pdl_launch();
  __syncthreads();
  TS(1, 1);
  pdl_wait();
  TS(1, 2);
  if (tid == 0) {
    const uint8_t* kg = reinterpret_cast<const uint8_t*>(g_img + (size_t)(32 + head) * IMG_HEAD_ELEMS);
    const uint8_t* vg = reinterpret_cast<const uint8_t*>(g_img + (size_t)(64 + head) * IMG_HEAD_ELEMS);
    constexpr int CB = AT_KV_BYTES / AT_CHUNKS;
    for (int i = 0; i < AT_CHUNKS; i++) {
      mbar_expect_tx(sBar + 8 * i, 2 * CB);
      bulk_g2s(sK + i * CB, kg + i * CB, CB, sBar + 8 * i);
      bulk_g2s(sV + i * CB, vg + i * CB, CB, sBar + 8 * i);
    }
  }
  if (tid == 32) {
    prefetch_l2(reinterpret_cast<const uint8_t*>(wo) + blockIdx.x * 6400, 6400);
    prefetch_l2(reinterpret_cast<const uint8_t*>(wgt) + blockIdx.x * 15360, 15360);
    prefetch_l2(reinterpret_cast<const uint8_t*>(wup) + blockIdx.x * 15360, 15360);
    prefetch_l2(reinterpret_cast<const uint8_t*>(wdn) + blockIdx.x * 15360, 15360);
  }
  const int wg = warp >> 2, wwarp = warp & 3;
  const int g = lane >> 2, c4 = lane & 3;
  const float SC = 0.22360679774997896f * 1.4426950408889634f;
  const float SC64 = SC * (1.0f / 64.0f);

  for (int rep = 0; rep < 2; rep++) {
    const int row0 = quarter * 512 + (rep * 4 + wg) * 64 + wwarp * 16 + g;
    uint32_t qa[8];
    {
      const bf16* q0 = g_img + (size_t)head * IMG_HEAD_ELEMS + (size_t)(row0 >> 3) * 192 + g * 8 + c4 * 2;
      const bf16* q1 = q0 + 192;
      qa[0] = *reinterpret_cast<const uint32_t*>(q0);
      qa[1] = *reinterpret_cast<const uint32_t*>(q1);
      qa[2] = *reinterpret_cast<const uint32_t*>(q0 + 64);
      qa[3] = *reinterpret_cast<const uint32_t*>(q1 + 64);
      qa[4] = *reinterpret_cast<const uint32_t*>(q0 + 128);
      qa[5] = *reinterpret_cast<const uint32_t*>(q1 + 128);
      qa[6] = 0u;
      qa[7] = 0u;
    }
    float o[12];
#pragma unroll
    for (int i = 0; i < 12; i++) o[i] = 0.f;
    float m0 = -INFINITY, m1 = -INFINITY;
#pragma unroll 1
    for (int t = 0; t < 16; t++) {
      if (rep == 0) mbar_wait(sBar + 8 * (t >> 1), 0);
      float s[64];
      wgmma_fence();
      {
        const uint64_t dk0 = make_desc(sK + t * 6144, 128, 384, 0);
        const uint64_t dk1 = make_desc(sK + t * 6144 + 256, 128, 384, 0);
        wgmma_rs_n128(s, qa[0], qa[1], qa[2], qa[3], dk0, 0);
        wgmma_rs_n128(s, qa[4], qa[5], qa[6], qa[7], dk1, 1);
      }
      wgmma_commit();
      wgmma_wait<0>();
      float mx0 = s[0], mx1 = s[2];
#pragma unroll
      for (int j = 0; j < 16; j++) {
        mx0 = fmaxf(mx0, fmaxf(s[4 * j], s[4 * j + 1]));
        mx1 = fmaxf(mx1, fmaxf(s[4 * j + 2], s[4 * j + 3]));
      }
      mx0 = fmaxf(mx0, __shfl_xor_sync(0xffffffffu, mx0, 1));
      mx1 = fmaxf(mx1, __shfl_xor_sync(0xffffffffu, mx1, 1));
      mx0 = fmaxf(mx0, __shfl_xor_sync(0xffffffffu, mx0, 2));
      mx1 = fmaxf(mx1, __shfl_xor_sync(0xffffffffu, mx1, 2));
      const float mn0 = fmaxf(m0, mx0), mn1 = fmaxf(m1, mx1);
      const float al0 = ex2((m0 - mn0) * SC), al1 = ex2((m1 - mn1) * SC);
      m0 = mn0; m1 = mn1;
      const float mc0 = -mn0 * SC, mc1 = -mn1 * SC;
      const float b0 = fmaf(mc0, 1.0f / 64.0f, 1.0f), b1 = fmaf(mc1, 1.0f / 64.0f, 1.0f);
      uint32_t p[32];
#pragma unroll
      for (int j = 0; j < 16; j++) {
        float e0, e1, e2, e3;
        e0 = ex2(fmaf(s[4 * j], SC, mc0));
        e1 = ex2(fmaf(s[4 * j + 1], SC, mc0));
        e2 = ex2(fmaf(s[4 * j + 2], SC, mc1));
        if ((j & 1) == 0) e3 = exp2_poly(s[4 * j + 3], SC64, b1);
        else { e3 = ex2(fmaf(s[4 * j + 3], SC, mc1)); e0 = exp2_poly(s[4 * j], SC64, b0); }
        p[2 * j] = pack_bf16(e0, e1);
        p[2 * j + 1] = pack_bf16(e2, e3);
      }
#pragma unroll
      for (int j = 0; j < 3; j++) {
        o[4 * j] *= al0; o[4 * j + 1] *= al0;
        o[4 * j + 2] *= al1; o[4 * j + 3] *= al1;
      }
      wgmma_fence();
#pragma unroll
      for (int kk = 0; kk < 8; kk++) {
        const uint64_t dv = make_desc(sV + t * 6144 + kk * 768, 384, 128, 0);
        wgmma_rs_n24_tb(o, p[4 * kk], p[4 * kk + 1], p[4 * kk + 2], p[4 * kk + 3], dv, 1);
      }
      wgmma_commit();
      wgmma_wait<0>();
    }
    TS(1, 3 + rep);
    const float l0 = __shfl_sync(0xffffffffu, o[8], (lane & ~3) | 2);
    const float l1 = __shfl_sync(0xffffffffu, o[10], (lane & ~3) | 2);
    const float i0 = 1.0f / l0, i1 = 1.0f / l1;
    bf16* o0 = g_o + (size_t)row0 * DM + head * DH;
    bf16* o1 = o0 + 8 * DM;
#pragma unroll
    for (int j = 0; j < 3; j++) {
      if (j < 2 || c4 < 2) {
        *reinterpret_cast<uint32_t*>(o0 + j * 8 + c4 * 2) = pack_bf16(o[4 * j] * i0, o[4 * j + 1] * i0);
        *reinterpret_cast<uint32_t*>(o1 + j * 8 + c4 * 2) = pack_bf16(o[4 * j + 2] * i1, o[4 * j + 3] * i1);
      }
    }
  }
}

typedef CUresult (*EncodeTiledFn)(CUtensorMap*, CUtensorMapDataType, cuuint32_t, void*, const cuuint64_t*, const cuuint64_t*,
                                  const cuuint32_t*, const cuuint32_t*, CUtensorMapInterleave, CUtensorMapSwizzle,
                                  CUtensorMapL2promotion, CUtensorMapFloatOOBfill);

static void make_map(EncodeTiledFn fn, CUtensorMap* tm, const void* ptr, uint64_t rows, uint64_t cols, uint32_t box_rows,
                     uint32_t box_cols, CUtensorMapSwizzle sw) {
  cuuint64_t dims[2] = {cols, rows};
  cuuint64_t strides[1] = {cols * 2};
  cuuint32_t box[2] = {box_cols, box_rows};
  cuuint32_t es[2] = {1, 1};
  fn(tm, CU_TENSOR_MAP_DATA_TYPE_BFLOAT16, 2, const_cast<void*>(ptr), dims, strides, box, es, CU_TENSOR_MAP_INTERLEAVE_NONE, sw,
     CU_TENSOR_MAP_L2_PROMOTION_L2_256B, CU_TENSOR_MAP_FLOAT_OOB_FILL_NONE);
}

template <typename... KArgs, typename... Args>
static void launch(void (*kern)(KArgs...), int grid, int block, int smem, int cluster, bool pdl, Args... args) {
  cudaLaunchConfig_t cfg = {};
  cfg.gridDim = dim3(grid);
  cfg.blockDim = dim3(block);
  cfg.dynamicSmemBytes = smem;
  cfg.stream = cudaStreamPerThread;
  cudaLaunchAttribute at[2];
  int n = 0;
  if (cluster > 1) {
    at[n].id = cudaLaunchAttributeClusterDimension;
    at[n].val.clusterDim.x = cluster; at[n].val.clusterDim.y = 1; at[n].val.clusterDim.z = 1;
    n++;
  }
  if (pdl) {
    at[n].id = cudaLaunchAttributeProgrammaticStreamSerialization;
    at[n].val.programmaticStreamSerializationAllowed = 1;
    n++;
  }
  cfg.attrs = at;
  cfg.numAttrs = n;
  cudaLaunchKernelEx(&cfg, kern, KArgs(args)...);
}

extern "C" void kernel_launch(void* const* d_in, const int* in_sizes, int n_in, void* d_out, int out_size) {
  const bf16* x = (const bf16*)d_in[0];
  const bf16* wqkv = (const bf16*)d_in[1];
  const bf16* wo = (const bf16*)d_in[2];
  const bf16* wg = (const bf16*)d_in[4];
  const bf16* wu = (const bf16*)d_in[5];
  const bf16* wd = (const bf16*)d_in[6];
  bf16* out = (bf16*)d_out;

  static EncodeTiledFn enc = nullptr;
  static void *p_o = nullptr, *p_h = nullptr, *p_hh = nullptr, *p_xn = nullptr;
  if (!enc) {
    void* fn = nullptr;
    cudaDriverEntryPointQueryResult qr;
    cudaGetDriverEntryPoint("cuTensorMapEncodeTiled", &fn, cudaEnableDefault, &qr);
    enc = (EncodeTiledFn)fn;
    cudaGetSymbolAddress(&p_o, g_o);
    cudaGetSymbolAddress(&p_h, g_h);
    cudaGetSymbolAddress(&p_hh, g_hh);
    cudaGetSymbolAddress(&p_xn, g_xn);
    cudaFuncSetAttribute(big_gemm_kernel<0>, cudaFuncAttributeMaxDynamicSharedMemorySize, LGCfg<0>::SMEM);
    cudaFuncSetAttribute(big_gemm_kernel<1>, cudaFuncAttributeMaxDynamicSharedMemorySize, LGCfg<1>::SMEM);
    cudaFuncSetAttribute(res_gemm_kernel<DM>, cudaFuncAttributeMaxDynamicSharedMemorySize, RG_SMEM);
    cudaFuncSetAttribute(res_gemm_kernel<FF>, cudaFuncAttributeMaxDynamicSharedMemorySize, RG_SMEM);
    cudaFuncSetAttribute(attn_kernel, cudaFuncAttributeMaxDynamicSharedMemorySize, AT_SMEM);
  }
  CUtensorMap tm_wqkv, tm_wg, tm_wu, tm_wo64, tm_wo16, tm_wd64, tm_wd16, tm_o, tm_hh, tm_xn;
  make_map(enc, &tm_wqkv, wqkv, DM, 3 * DM, 32, 64, CU_TENSOR_MAP_SWIZZLE_128B);
  make_map(enc, &tm_wg, wg, DM, FF, 32, 64, CU_TENSOR_MAP_SWIZZLE_128B);
  make_map(enc, &tm_wu, wu, DM, FF, 32, 64, CU_TENSOR_MAP_SWIZZLE_128B);
  make_map(enc, &tm_wo64, wo, DM, DM, 64, 64, CU_TENSOR_MAP_SWIZZLE_128B);
  make_map(enc, &tm_wo16, wo, DM, DM, 64, 16, CU_TENSOR_MAP_SWIZZLE_32B);
  make_map(enc, &tm_wd64, wd, FF, DM, 64, 64, CU_TENSOR_MAP_SWIZZLE_128B);
  make_map(enc, &tm_wd16, wd, FF, DM, 64, 16, CU_TENSOR_MAP_SWIZZLE_32B);
  make_map(enc, &tm_o, p_o, SEQ, DM, 64, 64, CU_TENSOR_MAP_SWIZZLE_128B);
  make_map(enc, &tm_hh, p_hh, SEQ, FF, 64, 64, CU_TENSOR_MAP_SWIZZLE_128B);
  make_map(enc, &tm_xn, p_xn, SEQ, DM, 128, 32, CU_TENSOR_MAP_SWIZZLE_64B);

  launch(ln_kernel, 128, 256, 0, 1, false, x, (bf16*)p_xn, 0);
  launch(big_gemm_kernel<0>, 128, LG_THREADS, LGCfg<0>::SMEM, 2, true, tm_xn, tm_wqkv, tm_wqkv, tm_wqkv);
  launch(attn_kernel, 128, AT_THREADS, AT_SMEM, 1, true, wo, wg, wu, wd);
  launch(res_gemm_kernel<DM>, 128, RG_THREADS, RG_SMEM, 2, true, tm_o, tm_wo64, tm_wo16, x, (bf16*)p_h);
  launch(ln_kernel, 128, 256, 0, 1, true, (const bf16*)p_h, (bf16*)p_xn, 1);
  launch(big_gemm_kernel<1>, 128, LG_THREADS, LGCfg<1>::SMEM, 2, true, tm_xn, tm_wg, tm_wu, tm_hh);
  launch(res_gemm_kernel<FF>, 128, RG_THREADS, RG_SMEM, 2, true, tm_hh, tm_wd64, tm_wd16, (const bf16*)p_h, out);
}
```

```cpp
#include <cuda_runtime.h>
#include <cuda_bf16.h>
#include <cuda.h>
#include <stdint.h>

typedef __nv_bfloat16 bf16;

constexpr int SEQ = 2048, DM = 640, NH = 32, DH = 20, FF = 1536;
constexpr float ATT_SCALE_LOG2E = 0.22360679774997896f * 1.4426950408889634f;
constexpr int IMG_HEAD_ELEMS = (SEQ / 8) * 192;

__device__ __align__(1024) bf16 g_img[3 * NH * IMG_HEAD_ELEMS];
__device__ __align__(1024) bf16 g_o[SEQ * DM];
__device__ __align__(1024) bf16 g_h[SEQ * DM];
__device__ __align__(1024) bf16 g_xn[SEQ * DM];
__device__ __align__(1024) bf16 g_hh[SEQ * FF];

#define TS(k, i)
__device__ __forceinline__ uint32_t smem_u32(const void* p) { return (uint32_t)__cvta_generic_to_shared(p); }
__device__ __forceinline__ void mbar_init(uint32_t bar, uint32_t cnt) {
  asm volatile("mbarrier.init.shared::cta.b64 [%0], %1;" ::"r"(bar), "r"(cnt) : "memory");
}
__device__ __forceinline__ void mbar_expect_tx(uint32_t bar, uint32_t bytes) {
  asm volatile("mbarrier.arrive.expect_tx.shared::cta.b64 _, [%0], %1;" ::"r"(bar), "r"(bytes) : "memory");
}
__device__ __forceinline__ void mbar_arrive(uint32_t bar) {
  asm volatile("mbarrier.arrive.shared::cta.b64 _, [%0];" ::"r"(bar) : "memory");
}
__device__ __forceinline__ void mbar_arrive_cluster(uint32_t bar, uint32_t cta) {
  asm volatile(
      "{\n.reg .b32 r;\nmapa.shared::cluster.u32 r, %0, %1;\n"
      "mbarrier.arrive.shared::cluster.b64 _, [r];\n}\n" ::"r"(bar), "r"(cta)
      : "memory");
}
__device__ __forceinline__ void mbar_wait(uint32_t bar, uint32_t parity) {
  asm volatile(
      "{\n.reg .pred p;\nLAB_WAIT:\n"
      "mbarrier.try_wait.parity.shared::cta.b64 p, [%0], %1;\n"
      "@p bra DONE;\nbra LAB_WAIT;\nDONE:\n}\n" ::"r"(bar), "r"(parity)
      : "memory");
}
__device__ __forceinline__ void mbar_wait_cluster(uint32_t bar, uint32_t parity) {
  asm volatile(
      "{\n.reg .pred p;\nLAB_WAIT:\n"
      "mbarrier.try_wait.parity.acquire.cluster.shared::cta.b64 p, [%0], %1;\n"
      "@p bra DONE;\nbra LAB_WAIT;\nDONE:\n}\n" ::"r"(bar), "r"(parity)
      : "memory");
}
__device__ __forceinline__ void fence_mbar_init() { asm volatile("fence.mbarrier_init.release.cluster;" ::: "memory"); }
__device__ __forceinline__ void fence_proxy_async() { asm volatile("fence.proxy.async.shared::cta;" ::: "memory"); }
__device__ __forceinline__ void cluster_sync_all() {
  asm volatile("barrier.cluster.arrive.release.aligned;\nbarrier.cluster.wait.acquire.aligned;" ::: "memory");
}
__device__ __forceinline__ void cluster_sync_relaxed() {
  asm volatile("barrier.cluster.arrive.relaxed.aligned;\nbarrier.cluster.wait.aligned;" ::: "memory");
}
__device__ __forceinline__ void named_bar_sync(int id, int n) { asm volatile("bar.sync %0, %1;" ::"r"(id), "r"(n) : "memory"); }
__device__ __forceinline__ bool wg_any(bool pred, int id) {
  uint32_t r;
  asm volatile("{\n.reg .pred p, q;\nsetp.ne.u32 p, %1, 0;\nbar.red.or.pred q, %2, 128, p;\nselp.u32 %0, 1, 0, q;\n}\n" : "=r"(r) : "r"((uint32_t)pred), "r"(id) : "memory");
  return r != 0;
}
__device__ __forceinline__ void pdl_launch() { asm volatile("griddepcontrol.launch_dependents;" ::: "memory"); }
__device__ __forceinline__ void pdl_wait() { asm volatile("griddepcontrol.wait;" ::: "memory"); }

__device__ __forceinline__ void tma_load_2d(uint32_t dst, const CUtensorMap* tm, int c0, int c1, uint32_t bar) {
  asm volatile(
      "cp.async.bulk.tensor.2d.shared::cluster.global.mbarrier::complete_tx::bytes [%0], [%1, {%3, %4}], [%2];" ::"r"(dst),
      "l"((uint64_t)tm), "r"(bar), "r"(c0), "r"(c1)
      : "memory");
}
__device__ __forceinline__ void tma_load_2d_mc(uint32_t dst, const CUtensorMap* tm, int c0, int c1, uint32_t bar, uint16_t mask) {
  asm volatile(
      "cp.async.bulk.tensor.2d.shared::cluster.global.mbarrier::complete_tx::bytes.multicast::cluster [%0], [%1, {%3, %4}], [%2], %5;" ::"r"(dst),
      "l"((uint64_t)tm), "r"(bar), "r"(c0), "r"(c1), "h"(mask)
      : "memory");
}
__device__ __forceinline__ void bulk_g2s(uint32_t dst, const void* src, uint32_t bytes, uint32_t bar) {
  asm volatile("cp.async.bulk.shared::cluster.global.mbarrier::complete_tx::bytes [%0], [%1], %2, [%3];" ::"r"(dst), "l"(src),
               "r"(bytes), "r"(bar)
               : "memory");
}
__device__ __forceinline__ void bulk_s2g(void* dst, uint32_t src, uint32_t bytes) {
  asm volatile("cp.async.bulk.global.shared::cta.bulk_group [%0], [%1], %2;" ::"l"(dst), "r"(src), "r"(bytes) : "memory");
}
__device__ __forceinline__ void tma_store_2d(const CUtensorMap* tm, uint32_t src, int c0, int c1) {
  asm volatile("cp.async.bulk.tensor.2d.global.shared::cta.bulk_group [%0, {%2, %3}], [%1];" ::"l"((uint64_t)tm), "r"(src), "r"(c0), "r"(c1) : "memory");
}
__device__ __forceinline__ void bulk_commit() { asm volatile("cp.async.bulk.commit_group;" ::: "memory"); }
__device__ __forceinline__ void bulk_wait_read() { asm volatile("cp.async.bulk.wait_group.read 0;" ::: "memory"); }
__device__ __forceinline__ void prefetch_l2(const void* p, uint32_t bytes) {
  asm volatile("cp.async.bulk.prefetch.L2.global [%0], %1;" ::"l"(p), "r"(bytes) : "memory");
}
__device__ __forceinline__ void bulk_wait_all() { asm volatile("cp.async.bulk.wait_group 0;" ::: "memory"); }
__device__ __forceinline__ void st_shared_b32(uint32_t addr, uint32_t v) { asm volatile("st.shared.b32 [%0], %1;" ::"r"(addr), "r"(v) : "memory"); }
__device__ __forceinline__ void st_shared_v2(uint32_t addr, uint32_t a, uint32_t b) { asm volatile("st.shared.v2.b32 [%0], {%1, %2};" ::"r"(addr), "r"(a), "r"(b) : "memory"); }
__device__ __forceinline__ void prefetch_tmap(const CUtensorMap* tm) {
  asm volatile("prefetch.tensormap [%0];" ::"l"((uint64_t)tm) : "memory");
}
__device__ __forceinline__ void wgmma_fence() { asm volatile("wgmma.fence.sync.aligned;" ::: "memory"); }
__device__ __forceinline__ void wgmma_commit() { asm volatile("wgmma.commit_group.sync.aligned;" ::: "memory"); }
template <int N>
__device__ __forceinline__ void wgmma_wait() { asm volatile("wgmma.wait_group.sync.aligned %0;" ::"n"(N) : "memory"); }

__device__ __forceinline__ uint64_t make_desc(uint32_t addr, uint32_t lbo, uint32_t sbo, uint32_t layout) {
  return (uint64_t)((addr & 0x3FFFF) >> 4) | ((uint64_t)((lbo & 0x3FFFF) >> 4) << 16) | ((uint64_t)((sbo & 0x3FFFF) >> 4) << 32) |
         ((uint64_t)layout << 62);
}
__device__ __forceinline__ uint32_t pack_bf16(float lo, float hi) {
  uint32_t r;
  asm("cvt.rn.bf16x2.f32 %0, %1, %2;" : "=r"(r) : "f"(hi), "f"(lo));
  return r;
}
__device__ __forceinline__ float bf16_round(float x) { return __bfloat162float(__float2bfloat16_rn(x)); }
__device__ __forceinline__ float bf_lo(uint32_t u) { return __uint_as_float(u << 16); }
__device__ __forceinline__ float bf_hi(uint32_t u) { return __uint_as_float(u & 0xffff0000u); }
__device__ __forceinline__ float ex2(float x) {
  float y;
  asm("ex2.approx.ftz.f32 %0, %1;" : "=f"(y) : "f"(x));
  return y;
}

__device__ __forceinline__ void wgmma_ss_n240_tb(float (&d)[120], uint64_t descA, uint64_t descB, int scaleD) {
  asm volatile("{\n.reg .pred p;\nsetp.ne.b32 p, %122, 0;\n"
    "wgmma.mma_async.sync.aligned.m64n240k16.f32.bf16.bf16 {%0, %1, %2, %3, %4, %5, %6, %7, %8, %9, %10, %11, %12, %13, %14, %15, %16, %17, %18, %19, %20, %21, %22, %23, %24, %25, %26, %27, %28, %29, %30, %31, %32, %33, %34, %35, %36, %37, %38, %39, %40, %41, %42, %43, %44, %45, %46, %47, %48, %49, %50, %51, %52, %53, %54, %55, %56, %57, %58, %59, %60, %61, %62, %63, %64, %65, %66, %67, %68, %69, %70, %71, %72, %73, %74, %75, %76, %77, %78, %79, %80, %81, %82, %83, %84, %85, %86, %87, %88, %89, %90, %91, %92, %93, %94, %95, %96, %97, %98, %99, %100, %101, %102, %103, %104, %105, %106, %107, %108, %109, %110, %111, %112, %113, %114, %115, %116, %117, %118, %119}, %120, %121, p, 1, 1, 0, 1;\n}\n"
    : "+f"(d[0]), "+f"(d[1]), "+f"(d[2]), "+f"(d[3]), "+f"(d[4]), "+f"(d[5]), "+f"(d[6]), "+f"(d[7]), "+f"(d[8]), "+f"(d[9]), "+f"(d[10]), "+f"(d[11]), "+f"(d[12]), "+f"(d[13]), "+f"(d[14]), "+f"(d[15]), "+f"(d[16]), "+f"(d[17]), "+f"(d[18]), "+f"(d[19]), "+f"(d[20]), "+f"(d[21]), "+f"(d[22]), "+f"(d[23]), "+f"(d[24]), "+f"(d[25]), "+f"(d[26]), "+f"(d[27]), "+f"(d[28]), "+f"(d[29]), "+f"(d[30]), "+f"(d[31]), "+f"(d[32]), "+f"(d[33]), "+f"(d[34]), "+f"(d[35]), "+f"(d[36]), "+f"(d[37]), "+f"(d[38]), "+f"(d[39]), "+f"(d[40]), "+f"(d[41]), "+f"(d[42]), "+f"(d[43]), "+f"(d[44]), "+f"(d[45]), "+f"(d[46]), "+f"(d[47]), "+f"(d[48]), "+f"(d[49]), "+f"(d[50]), "+f"(d[51]), "+f"(d[52]), "+f"(d[53]), "+f"(d[54]), "+f"(d[55]), "+f"(d[56]), "+f"(d[57]), "+f"(d[58]), "+f"(d[59]), "+f"(d[60]), "+f"(d[61]), "+f"(d[62]), "+f"(d[63]), "+f"(d[64]), "+f"(d[65]), "+f"(d[66]), "+f"(d[67]), "+f"(d[68]), "+f"(d[69]), "+f"(d[70]), "+f"(d[71]), "+f"(d[72]), "+f"(d[73]), "+f"(d[74]), "+f"(d[75]), "+f"(d[76]), "+f"(d[77]), "+f"(d[78]), "+f"(d[79]), "+f"(d[80]), "+f"(d[81]), "+f"(d[82]), "+f"(d[83]), "+f"(d[84]), "+f"(d[85]), "+f"(d[86]), "+f"(d[87]), "+f"(d[88]), "+f"(d[89]), "+f"(d[90]), "+f"(d[91]), "+f"(d[92]), "+f"(d[93]), "+f"(d[94]), "+f"(d[95]), "+f"(d[96]), "+f"(d[97]), "+f"(d[98]), "+f"(d[99]), "+f"(d[100]), "+f"(d[101]), "+f"(d[102]), "+f"(d[103]), "+f"(d[104]), "+f"(d[105]), "+f"(d[106]), "+f"(d[107]), "+f"(d[108]), "+f"(d[109]), "+f"(d[110]), "+f"(d[111]), "+f"(d[112]), "+f"(d[113]), "+f"(d[114]), "+f"(d[115]), "+f"(d[116]), "+f"(d[117]), "+f"(d[118]), "+f"(d[119])
    : "l"(descA), "l"(descB), "r"(scaleD));
}
__device__ __forceinline__ void wgmma_ss_n192_tb(float (&d)[96], uint64_t descA, uint64_t descB, int scaleD) {
  asm volatile("{\n.reg .pred p;\nsetp.ne.b32 p, %98, 0;\n"
    "wgmma.mma_async.sync.aligned.m64n192k16.f32.bf16.bf16 {%0, %1, %2, %3, %4, %5, %6, %7, %8, %9, %10, %11, %12, %13, %14, %15, %16, %17, %18, %19, %20, %21, %22, %23, %24, %25, %26, %27, %28, %29, %30, %31, %32, %33, %34, %35, %36, %37, %38, %39, %40, %41, %42, %43, %44, %45, %46, %47, %48, %49, %50, %51, %52, %53, %54, %55, %56, %57, %58, %59, %60, %61, %62, %63, %64, %65, %66, %67, %68, %69, %70, %71, %72, %73, %74, %75, %76, %77, %78, %79, %80, %81, %82, %83, %84, %85, %86, %87, %88, %89, %90, %91, %92, %93, %94, %95}, %96, %97, p, 1, 1, 0, 1;\n}\n"
    : "+f"(d[0]), "+f"(d[1]), "+f"(d[2]), "+f"(d[3]), "+f"(d[4]), "+f"(d[5]), "+f"(d[6]), "+f"(d[7]), "+f"(d[8]), "+f"(d[9]), "+f"(d[10]), "+f"(d[11]), "+f"(d[12]), "+f"(d[13]), "+f"(d[14]), "+f"(d[15]), "+f"(d[16]), "+f"(d[17]), "+f"(d[18]), "+f"(d[19]), "+f"(d[20]), "+f"(d[21]), "+f"(d[22]), "+f"(d[23]), "+f"(d[24]), "+f"(d[25]), "+f"(d[26]), "+f"(d[27]), "+f"(d[28]), "+f"(d[29]), "+f"(d[30]), "+f"(d[31]), "+f"(d[32]), "+f"(d[33]), "+f"(d[34]), "+f"(d[35]), "+f"(d[36]), "+f"(d[37]), "+f"(d[38]), "+f"(d[39]), "+f"(d[40]), "+f"(d[41]), "+f"(d[42]), "+f"(d[43]), "+f"(d[44]), "+f"(d[45]), "+f"(d[46]), "+f"(d[47]), "+f"(d[48]), "+f"(d[49]), "+f"(d[50]), "+f"(d[51]), "+f"(d[52]), "+f"(d[53]), "+f"(d[54]), "+f"(d[55]), "+f"(d[56]), "+f"(d[57]), "+f"(d[58]), "+f"(d[59]), "+f"(d[60]), "+f"(d[61]), "+f"(d[62]), "+f"(d[63]), "+f"(d[64]), "+f"(d[65]), "+f"(d[66]), "+f"(d[67]), "+f"(d[68]), "+f"(d[69]), "+f"(d[70]), "+f"(d[71]), "+f"(d[72]), "+f"(d[73]), "+f"(d[74]), "+f"(d[75]), "+f"(d[76]), "+f"(d[77]), "+f"(d[78]), "+f"(d[79]), "+f"(d[80]), "+f"(d[81]), "+f"(d[82]), "+f"(d[83]), "+f"(d[84]), "+f"(d[85]), "+f"(d[86]), "+f"(d[87]), "+f"(d[88]), "+f"(d[89]), "+f"(d[90]), "+f"(d[91]), "+f"(d[92]), "+f"(d[93]), "+f"(d[94]), "+f"(d[95])
    : "l"(descA), "l"(descB), "r"(scaleD));
}
__device__ __forceinline__ void wgmma_ss_n64_tb(float (&d)[32], uint64_t descA, uint64_t descB, int scaleD) {
  asm volatile("{\n.reg .pred p;\nsetp.ne.b32 p, %34, 0;\n"
    "wgmma.mma_async.sync.aligned.m64n64k16.f32.bf16.bf16 {%0, %1, %2, %3, %4, %5, %6, %7, %8, %9, %10, %11, %12, %13, %14, %15, %16, %17, %18, %19, %20, %21, %22, %23, %24, %25, %26, %27, %28, %29, %30, %31}, %32, %33, p, 1, 1, 0, 1;\n}\n"
    : "+f"(d[0]), "+f"(d[1]), "+f"(d[2]), "+f"(d[3]), "+f"(d[4]), "+f"(d[5]), "+f"(d[6]), "+f"(d[7]), "+f"(d[8]), "+f"(d[9]), "+f"(d[10]), "+f"(d[11]), "+f"(d[12]), "+f"(d[13]), "+f"(d[14]), "+f"(d[15]), "+f"(d[16]), "+f"(d[17]), "+f"(d[18]), "+f"(d[19]), "+f"(d[20]), "+f"(d[21]), "+f"(d[22]), "+f"(d[23]), "+f"(d[24]), "+f"(d[25]), "+f"(d[26]), "+f"(d[27]), "+f"(d[28]), "+f"(d[29]), "+f"(d[30]), "+f"(d[31])
    : "l"(descA), "l"(descB), "r"(scaleD));
}
__device__ __forceinline__ void wgmma_ss_n16_tb(float (&d)[8], uint64_t descA, uint64_t descB, int scaleD) {
  asm volatile("{\n.reg .pred p;\nsetp.ne.b32 p, %10, 0;\n"
    "wgmma.mma_async.sync.aligned.m64n16k16.f32.bf16.bf16 {%0, %1, %2, %3, %4, %5, %6, %7}, %8, %9, p, 1, 1, 0, 1;\n}\n"
    : "+f"(d[0]), "+f"(d[1]), "+f"(d[2]), "+f"(d[3]), "+f"(d[4]), "+f"(d[5]), "+f"(d[6]), "+f"(d[7])
    : "l"(descA), "l"(descB), "r"(scaleD));
}
__device__ __forceinline__ void wgmma_rs_n128(float (&d)[64], uint32_t a0, uint32_t a1, uint32_t a2, uint32_t a3, uint64_t descB, int scaleD) {
  asm volatile("{\n.reg .pred p;\nsetp.ne.b32 p, %69, 0;\n"
    "wgmma.mma_async.sync.aligned.m64n128k16.f32.bf16.bf16 {%0, %1, %2, %3, %4, %5, %6, %7, %8, %9, %10, %11, %12, %13, %14, %15, %16, %17, %18, %19, %20, %21, %22, %23, %24, %25, %26, %27, %28, %29, %30, %31, %32, %33, %34, %35, %36, %37, %38, %39, %40, %41, %42, %43, %44, %45, %46, %47, %48, %49, %50, %51, %52, %53, %54, %55, %56, %57, %58, %59, %60, %61, %62, %63}, {%64, %65, %66, %67}, %68, p, 1, 1, 0;\n}\n"
    : "+f"(d[0]), "+f"(d[1]), "+f"(d[2]), "+f"(d[3]), "+f"(d[4]), "+f"(d[5]), "+f"(d[6]), "+f"(d[7]), "+f"(d[8]), "+f"(d[9]), "+f"(d[10]), "+f"(d[11]), "+f"(d[12]), "+f"(d[13]), "+f"(d[14]), "+f"(d[15]), "+f"(d[16]), "+f"(d[17]), "+f"(d[18]), "+f"(d[19]), "+f"(d[20]), "+f"(d[21]), "+f"(d[22]), "+f"(d[23]), "+f"(d[24]), "+f"(d[25]), "+f"(d[26]), "+f"(d[27]), "+f"(d[28]), "+f"(d[29]), "+f"(d[30]), "+f"(d[31]), "+f"(d[32]), "+f"(d[33]), "+f"(d[34]), "+f"(d[35]), "+f"(d[36]), "+f"(d[37]), "+f"(d[38]), "+f"(d[39]), "+f"(d[40]), "+f"(d[41]), "+f"(d[42]), "+f"(d[43]), "+f"(d[44]), "+f"(d[45]), "+f"(d[46]), "+f"(d[47]), "+f"(d[48]), "+f"(d[49]), "+f"(d[50]), "+f"(d[51]), "+f"(d[52]), "+f"(d[53]), "+f"(d[54]), "+f"(d[55]), "+f"(d[56]), "+f"(d[57]), "+f"(d[58]), "+f"(d[59]), "+f"(d[60]), "+f"(d[61]), "+f"(d[62]), "+f"(d[63])
    : "r"(a0), "r"(a1), "r"(a2), "r"(a3), "l"(descB), "r"(scaleD));
}
__device__ __forceinline__ void wgmma_rs_n64(float (&d)[32], uint32_t a0, uint32_t a1, uint32_t a2, uint32_t a3, uint64_t descB, int scaleD) {
  asm volatile("{\n.reg .pred p;\nsetp.ne.b32 p, %37, 0;\n"
    "wgmma.mma_async.sync.aligned.m64n64k16.f32.bf16.bf16 {%0, %1, %2, %3, %4, %5, %6, %7, %8, %9, %10, %11, %12, %13, %14, %15, %16, %17, %18, %19, %20, %21, %22, %23, %24, %25, %26, %27, %28, %29, %30, %31}, {%32, %33, %34, %35}, %36, p, 1, 1, 0;\n}\n"
    : "+f"(d[0]), "+f"(d[1]), "+f"(d[2]), "+f"(d[3]), "+f"(d[4]), "+f"(d[5]), "+f"(d[6]), "+f"(d[7]), "+f"(d[8]), "+f"(d[9]), "+f"(d[10]), "+f"(d[11]), "+f"(d[12]), "+f"(d[13]), "+f"(d[14]), "+f"(d[15]), "+f"(d[16]), "+f"(d[17]), "+f"(d[18]), "+f"(d[19]), "+f"(d[20]), "+f"(d[21]), "+f"(d[22]), "+f"(d[23]), "+f"(d[24]), "+f"(d[25]), "+f"(d[26]), "+f"(d[27]), "+f"(d[28]), "+f"(d[29]), "+f"(d[30]), "+f"(d[31])
    : "r"(a0), "r"(a1), "r"(a2), "r"(a3), "l"(descB), "r"(scaleD));
}
__device__ __forceinline__ void wgmma_rs_n24_tb(float (&d)[12], uint32_t a0, uint32_t a1, uint32_t a2, uint32_t a3, uint64_t descB, int scaleD) {
  asm volatile("{\n.reg .pred p;\nsetp.ne.b32 p, %17, 0;\n"
    "wgmma.mma_async.sync.aligned.m64n24k16.f32.bf16.bf16 {%0, %1, %2, %3, %4, %5, %6, %7, %8, %9, %10, %11}, {%12, %13, %14, %15}, %16, p, 1, 1, 1;\n}\n"
    : "+f"(d[0]), "+f"(d[1]), "+f"(d[2]), "+f"(d[3]), "+f"(d[4]), "+f"(d[5]), "+f"(d[6]), "+f"(d[7]), "+f"(d[8]), "+f"(d[9]), "+f"(d[10]), "+f"(d[11])
    : "r"(a0), "r"(a1), "r"(a2), "r"(a3), "l"(descB), "r"(scaleD));
}

__global__ void __launch_bounds__(256) ln_kernel(const bf16* __restrict__ xin, bf16* __restrict__ xout, int tsk) {
  const int warp = threadIdx.x >> 5, lane = threadIdx.x & 31;
  const int hw = lane >> 4, l16 = lane & 15;
  const int row = (blockIdx.x * 8 + warp) * 2 + hw;
  pdl_launch();
  pdl_wait();
  const uint4* src = reinterpret_cast<const uint4*>(xin + (size_t)row * DM);
  uint4 v[5];
#pragma unroll
  for (int j = 0; j < 5; j++) v[j] = __ldg(src + j * 16 + l16);
  float s0 = 0.f, s1 = 0.f, s2 = 0.f, s3 = 0.f;
#pragma unroll
  for (int j = 0; j < 5; j++) {
    s0 += bf_lo(v[j].x) + bf_hi(v[j].x);
    s1 += bf_lo(v[j].y) + bf_hi(v[j].y);
    s2 += bf_lo(v[j].z) + bf_hi(v[j].z);
    s3 += bf_lo(v[j].w) + bf_hi(v[j].w);
  }
  float mean = (s0 + s1) + (s2 + s3);
#pragma unroll
  for (int o = 1; o < 16; o <<= 1) mean += __shfl_xor_sync(0xffffffffu, mean, o);
  mean *= (1.0f / DM);
  s0 = s1 = s2 = s3 = 0.f;
#pragma unroll
  for (int j = 0; j < 5; j++) {
    float d;
    d = bf_lo(v[j].x) - mean; s0 = fmaf(d, d, s0);
    d = bf_hi(v[j].x) - mean; s1 = fmaf(d, d, s1);
    d = bf_lo(v[j].y) - mean; s2 = fmaf(d, d, s2);
    d = bf_hi(v[j].y) - mean; s3 = fmaf(d, d, s3);
    d = bf_lo(v[j].z) - mean; s0 = fmaf(d, d, s0);
    d = bf_hi(v[j].z) - mean; s1 = fmaf(d, d, s1);
    d = bf_lo(v[j].w) - mean; s2 = fmaf(d, d, s2);
    d = bf_hi(v[j].w) - mean; s3 = fmaf(d, d, s3);
  }
  float sq = (s0 + s1) + (s2 + s3);
#pragma unroll
  for (int o = 1; o < 16; o <<= 1) sq += __shfl_xor_sync(0xffffffffu, sq, o);
  const float var_b = bf16_round(sq * (1.0f / DM));
  const float den = bf16_round(sqrtf(bf16_round(var_b + 1e-5f)));
  const float iv = __frcp_rn(den);
  const float mb = bf16_round(mean);
  uint4* dst = reinterpret_cast<uint4*>(xout + (size_t)row * DM);
#pragma unroll
  for (int j = 0; j < 5; j++) {
    uint4 w;
    uint32_t t;
    t = pack_bf16(bf_lo(v[j].x) - mb, bf_hi(v[j].x) - mb); w.x = pack_bf16(bf_lo(t) * iv, bf_hi(t) * iv);
    t = pack_bf16(bf_lo(v[j].y) - mb, bf_hi(v[j].y) - mb); w.y = pack_bf16(bf_lo(t) * iv, bf_hi(t) * iv);
    t = pack_bf16(bf_lo(v[j].z) - mb, bf_hi(v[j].z) - mb); w.z = pack_bf16(bf_lo(t) * iv, bf_hi(t) * iv);
    t = pack_bf16(bf_lo(v[j].w) - mb, bf_hi(v[j].w) - mb); w.w = pack_bf16(bf_lo(t) * iv, bf_hi(t) * iv);
    dst[j * 16 + l16] = w;
  }
}

constexpr int LG_THREADS = 384;
constexpr int LG_STAGES = 5;
template <int MODE>
struct LGCfg {
  static constexpr int NSLAB = MODE == 0 ? 4 : 6;
  static constexpr int STAGE_BYTES = 8192 + NSLAB * 4096;
  static constexpr int SMEM = LG_STAGES * STAGE_BYTES + 128 + 1024;
};

template <int WG>
__device__ __forceinline__ void qkv_mainloop(float (&acc)[120], uint32_t sbase, uint32_t sBar, bool leader) {
  constexpr int STAGE_BYTES = LGCfg<0>::STAGE_BYTES, NST = LG_STAGES;
  const uint64_t da_base = make_desc(sbase + WG * 4096, 16, 512, 2);
  const uint64_t db_base = make_desc(sbase + 8192, 4096, 1024, 1);
#pragma unroll 1
  for (int r = 0; r < 20 / NST; r++) {
#pragma unroll
    for (int s = 0; s < NST; s++) {
      mbar_wait(sBar + 8 * s, r & 1);
      wgmma_fence();
#pragma unroll
      for (int ks = 0; ks < 2; ks++)
        wgmma_ss_n240_tb(acc, da_base + (uint64_t)((s * STAGE_BYTES + ks * 32) >> 4), db_base + (uint64_t)((s * STAGE_BYTES + ks * 2048) >> 4), 1);
      wgmma_commit();
      wgmma_wait<1>();
      if (leader && (s > 0 || r > 0)) {
        const int ps = (s + NST - 1) % NST;
        mbar_arrive_cluster(sBar + 8 * (NST + ps), 0);
        mbar_arrive_cluster(sBar + 8 * (NST + ps), 1);
      }
    }
  }
}
template <int WG>
__device__ __forceinline__ void glu_mainloop(float (&accg)[96], float (&accu)[96], uint32_t sbase, uint32_t sBar, bool leader) {
  constexpr int STAGE_BYTES = LGCfg<1>::STAGE_BYTES, NST = LG_STAGES;
  const uint64_t da_base = make_desc(sbase + WG * 4096, 16, 512, 2);
  const uint64_t db_base = make_desc(sbase + 8192, 4096, 1024, 1);
#pragma unroll 1
  for (int r = 0; r < 20 / NST; r++) {
#pragma unroll
    for (int s = 0; s < NST; s++) {
      mbar_wait(sBar + 8 * s, r & 1);
      wgmma_fence();
#pragma unroll
      for (int ks = 0; ks < 2; ks++) {
        const uint64_t da = da_base + (uint64_t)((s * STAGE_BYTES + ks * 32) >> 4);
        wgmma_ss_n192_tb(accg, da, db_base + (uint64_t)((s * STAGE_BYTES + ks * 2048) >> 4), 1);
        wgmma_ss_n192_tb(accu, da, db_base + (uint64_t)((s * STAGE_BYTES + 3 * 4096 + ks * 2048) >> 4), 1);
      }
      wgmma_commit();
      wgmma_wait<1>();
      if (leader && (s > 0 || r > 0)) {
        const int ps = (s + NST - 1) % NST;
        mbar_arrive_cluster(sBar + 8 * (NST + ps), 0);
        mbar_arrive_cluster(sBar + 8 * (NST + ps), 1);
      }
    }
  }
}

template <int MODE>
__global__ void __launch_bounds__(LG_THREADS, 1)
big_gemm_kernel(const __grid_constant__ CUtensorMap tmA, const __grid_constant__ CUtensorMap tmB0, const __grid_constant__ CUtensorMap tmB1,
                const __grid_constant__ CUtensorMap tmOut) {
  using C = LGCfg<MODE>;
  constexpr int STAGE_BYTES = C::STAGE_BYTES, NST = LG_STAGES, NKB = 20;
  extern __shared__ uint8_t smem_raw[];
  const uint32_t sbase = (smem_u32(smem_raw) + 1023u) & ~1023u;
  const uint32_t sBar = sbase + NST * STAGE_BYTES;
  const int tid = threadIdx.x, warp = tid >> 5, lane = tid & 31;
  const int rank = blockIdx.x & 1;
  const int pair = blockIdx.x >> 1;
  const int n_blk = pair & 7;
  const int m_blk = (pair >> 3) * 2 + rank;
  TS(MODE * 3, 0);
  if (tid == 256) {
    prefetch_tmap(&tmA);
    prefetch_tmap(&tmB0);
    if (MODE == 1) { prefetch_tmap(&tmB1); prefetch_tmap(&tmOut); }
  }
  if (tid == 0) {
    for (int s = 0; s < NST; s++) {
      mbar_init(sBar + 8 * s, 1);
      mbar_init(sBar + 8 * (NST + s), 4);
    }
    fence_mbar_init();
  }
  pdl_launch();
  cluster_sync_all();

  if (warp >= 8) {
    asm volatile("setmaxnreg.dec.sync.aligned.u32 40;");
    if (tid == 256) {
      auto issue_b = [&](int kb) {
        const int s = kb % NST;
        const uint32_t full = sBar + 8 * s;
        mbar_expect_tx(full, STAGE_BYTES);
        const uint32_t dst = sbase + s * STAGE_BYTES + 8192;
        if (MODE == 0) {
#pragma unroll
          for (int j = 0; j < 2; j++) {
            const int sl = rank * 2 + j;
            tma_load_2d_mc(dst + sl * 4096, &tmB0, n_blk * 240 + sl * 64, kb * 32, full, (uint16_t)3);
          }
        } else {
#pragma unroll
          for (int j = 0; j < 3; j++)
            tma_load_2d_mc(dst + (rank * 3 + j) * 4096, rank == 0 ? &tmB0 : &tmB1, n_blk * 192 + j * 64, kb * 32, full, (uint16_t)3);
        }
      };
      for (int kb = 0; kb < NST; kb++) issue_b(kb);
      pdl_wait();
      for (int kb = 0; kb < NKB; kb++) {
        const int s = kb % NST;
        if (kb >= NST) {
          mbar_wait(sBar + 8 * (NST + s), ((kb / NST) & 1) ^ 1);
          issue_b(kb);
        }
        tma_load_2d(sbase + s * STAGE_BYTES, &tmA, kb * 32, m_blk * 128, sBar + 8 * s);
      }
    }
  } else {
    asm volatile("setmaxnreg.inc.sync.aligned.u32 232;");
    const int wg = __shfl_sync(0xffffffffu, warp >> 2, 0);
    const int wwarp = warp & 3;
    TS(MODE * 3, 1);
    mbar_wait(sBar, 0);
    TS(MODE * 3, 3);
    if (MODE == 0) {
      float acc[120];
#pragma unroll
      for (int i = 0; i < 120; i++) acc[i] = 0.f;
      if (wg == 0) qkv_mainloop<0>(acc, sbase, sBar, (tid & 127) == 0);
      else qkv_mainloop<1>(acc, sbase, sBar, (tid & 127) == 0);
      wgmma_wait<0>();
      TS(0, 4);
      named_bar_sync(3, 256);
      const int g = lane >> 2, c4 = lane & 3;
      const uint32_t stg = sbase + wg * (12 * 3072) + (wwarp * 2) * 384 + g * 16;
      const int hbase = n_blk * 12;
#pragma unroll
      for (int j = 0; j < 30; j++) {
        const int cb = (j * 8) % 20;
        const int hb = (j * 8) / 20;
        int d = cb + c4 * 2;
        int hl = hb;
        if (cb == 16 && c4 >= 2) { d -= 20; hl += 1; }
        const uint32_t a0 = stg + hl * 3072 + (d >> 3) * 128 + (d & 7) * 2;
        const int hg = hbase + hl;
        const float sc = hg < 32 ? ATT_SCALE_LOG2E : 1.0f;
        st_shared_b32(a0, pack_bf16(acc[4 * j] * sc, acc[4 * j + 1] * sc));
        st_shared_b32(a0 + 384, pack_bf16(acc[4 * j + 2] * sc, acc[4 * j + 3] * sc));
        if (d == 18) {
          const uint32_t pad0 = hg < 32 ? 0u : (hg < 64 ? 0x3f803f80u : 0x00003f80u);
          const uint32_t pad1 = (hg >= 32 && hg < 64) ? 0x00003f80u : 0u;
          st_shared_v2(a0 + 4, pad0, pad1);
          st_shared_v2(a0 + 388, pad0, pad1);
        }
      }
      fence_proxy_async();
      named_bar_sync(1 + wg, 128);
      if ((tid & 127) < 12) {
        const int hl = tid & 127;
        bf16* dst = g_img + (size_t)(hbase + hl) * IMG_HEAD_ELEMS + (size_t)(m_blk * 16 + wg * 8) * 192;
        bulk_s2g(dst, sbase + wg * (12 * 3072) + hl * 3072, 3072);
        bulk_commit();
        bulk_wait_read();
      }
    } else {
      float accg[96], accu[96];
#pragma unroll
      for (int i = 0; i < 96; i++) { accg[i] = 0.f; accu[i] = 0.f; }
      if (wg == 0) glu_mainloop<0>(accg, accu, sbase, sBar, (tid & 127) == 0);
      else glu_mainloop<1>(accg, accu, sbase, sBar, (tid & 127) == 0);
      wgmma_wait<0>();
      TS(3, 4);
      named_bar_sync(3, 256);
      const int g = lane >> 2, c4 = lane & 3;
      const uint32_t stg = sbase + wg * 24576 + (wwarp * 16 + g) * 128 + c4 * 4;
#pragma unroll
      for (int j = 0; j < 24; j++) {
        uint32_t pk[2];
#pragma unroll
        for (int h = 0; h < 2; h++) {
          const uint32_t gp = pack_bf16(accg[4 * j + 2 * h], accg[4 * j + 2 * h + 1]);
          const uint32_t up = pack_bf16(accu[4 * j + 2 * h], accu[4 * j + 2 * h + 1]);
          const float g0 = bf_lo(gp), g1 = bf_hi(gp);
          const float r0 = (g0 * (g0 > 0.f ? 1.f : 0.f)) * bf_lo(up);
          const float r1 = (g1 * (g1 > 0.f ? 1.f : 0.f)) * bf_hi(up);
          pk[h] = pack_bf16(r0, r1);
        }
        const uint32_t a0 = stg + (j >> 3) * 8192 + (((j & 7) ^ g) << 4);
        st_shared_b32(a0, pk[0]);
        st_shared_b32(a0 + 1024, pk[1]);
      }
      fence_proxy_async();
      named_bar_sync(1 + wg, 128);
      if ((tid & 127) == 0) {
#pragma unroll
        for (int sl = 0; sl < 3; sl++) tma_store_2d(&tmOut, sbase + wg * 24576 + sl * 8192, n_blk * 192 + sl * 64, m_blk * 128 + wg * 64);
        bulk_commit();
        bulk_wait_read();
      }
    }
  }
  __syncwarp();
  TS(MODE * 3, 5);
  cluster_sync_relaxed();
  TS(MODE * 3, 6);
}

constexpr int RG_THREADS = 288;
constexpr int RG_STAGES = 8;
constexpr int RG_STAGE_BYTES = 16384 + 8192 + 2048;
constexpr int RG_SMEM = RG_STAGES * RG_STAGE_BYTES + 256 + 1024;

template <int NKB, int NST, int WG>
__device__ __forceinline__ void res_mainloop(float (&acc0)[32], float (&acc1)[8], uint32_t sbase, uint32_t sBar, bool leader) {
  const uint64_t da_base = make_desc(sbase + WG * 8192, 16, 1024, 1);
  const uint64_t db0_base = make_desc(sbase + 16384, 8192, 1024, 1);
  const uint64_t db1_base = make_desc(sbase + 16384 + 8192, 2048, 256, 3);
#pragma unroll 1
  for (int r = 0; r < NKB / NST; r++) {
#pragma unroll
    for (int s = 0; s < NST; s++) {
      const uint64_t so = (uint64_t)(s * (RG_STAGE_BYTES >> 4));
      mbar_wait(sBar + 8 * s, r & 1);
      wgmma_fence();
#pragma unroll
      for (int ks = 0; ks < 4; ks++) {
        wgmma_ss_n64_tb(acc0, da_base + so + ks * 2, db0_base + so + ks * 128, 1);
        wgmma_ss_n16_tb(acc1, da_base + so + ks * 2, db1_base + so + ks * 32, 1);
      }
      wgmma_commit();
      wgmma_wait<1>();
      if (leader && (s > 0 || r > 0)) {
        const int ps = (s + NST - 1) % NST;
        mbar_arrive_cluster(sBar + 8 * (NST + ps), 0);
        mbar_arrive_cluster(sBar + 8 * (NST + ps), 1);
      }
    }
  }
}

template <int KTOT>
__global__ void __launch_bounds__(RG_THREADS, 1)
res_gemm_kernel(const __grid_constant__ CUtensorMap tmA, const __grid_constant__ CUtensorMap tmB64, const __grid_constant__ CUtensorMap tmB16,
                const bf16* __restrict__ resid, bf16* __restrict__ out) {
  constexpr int NKB = KTOT / 64;
  constexpr int NST = (KTOT == DM) ? 5 : 8;
  extern __shared__ uint8_t smem_raw[];
  const uint32_t sbase = (smem_u32(smem_raw) + 1023u) & ~1023u;
  const uint32_t sBar = sbase + NST * RG_STAGE_BYTES;
  const int tid = threadIdx.x, warp = tid >> 5, lane = tid & 31;
  const int rank = blockIdx.x & 1;
  const int pair = blockIdx.x >> 1;
  const int m_blk = pair >> 2;
  const int n_blk = (pair & 3) * 2 + rank;
  const int n0 = n_blk * 80;
  constexpr int TSK = KTOT == DM ? 2 : 4;
  TS(TSK, 0);

  if (tid == 0) {
    for (int s = 0; s < NST; s++) {
      mbar_init(sBar + 8 * s, 1);
      mbar_init(sBar + 8 * (NST + s), 4);
    }
    fence_mbar_init();
  }
  pdl_launch();
  cluster_sync_all();

  if (warp == 8) {
    if (lane == 0) {
      prefetch_tmap(&tmA); prefetch_tmap(&tmB64); prefetch_tmap(&tmB16);
      constexpr int PRE = NKB < NST ? NKB : NST;
      for (int kb = 0; kb < PRE; kb++) {
        const uint32_t full = sBar + 8 * kb;
        const uint32_t st = sbase + kb * RG_STAGE_BYTES;
        mbar_expect_tx(full, RG_STAGE_BYTES);
        tma_load_2d(st + 16384, &tmB64, n0, kb * 64, full);
        tma_load_2d(st + 16384 + 8192, &tmB16, n0 + 64, kb * 64, full);
      }
      pdl_wait();
      for (int kb = 0; kb < NKB; kb++) {
        const int s = kb % NST;
        const uint32_t full = sBar + 8 * s;
        const uint32_t st = sbase + s * RG_STAGE_BYTES;
        if (kb >= PRE) {
          const uint32_t ph = (kb / NST) & 1;
          mbar_wait(sBar + 8 * (NST + s), ph ^ 1);
          mbar_expect_tx(full, RG_STAGE_BYTES);
          tma_load_2d(st + 16384, &tmB64, n0, kb * 64, full);
          tma_load_2d(st + 16384 + 8192, &tmB16, n0 + 64, kb * 64, full);
        }
        tma_load_2d_mc(st + rank * 8192, &tmA, kb * 64, m_blk * 128 + rank * 64, full, (uint16_t)3);
      }
    }
  } else {
    const int wg = __shfl_sync(0xffffffffu, warp >> 2, 0), wwarp = warp & 3;
    const int g = lane >> 2, c4 = lane & 3;
    const int row0 = m_blk * 128 + wg * 64 + wwarp * 16 + g;
    TS(TSK, 1);
    pdl_wait();
    TS(TSK, 2);
    uint32_t res[20];
#pragma unroll
    for (int j = 0; j < 10; j++) {
      res[2 * j] = __ldg(reinterpret_cast<const uint32_t*>(resid + (size_t)row0 * DM + n0 + j * 8 + c4 * 2));
      res[2 * j + 1] = __ldg(reinterpret_cast<const uint32_t*>(resid + (size_t)(row0 + 8) * DM + n0 + j * 8 + c4 * 2));
    }
    float acc0[32], acc1[8];
#pragma unroll
    for (int i = 0; i < 32; i++) acc0[i] = 0.f;
#pragma unroll
    for (int i = 0; i < 8; i++) acc1[i] = 0.f;
    mbar_wait(sBar, 0);
    TS(TSK, 3);
    if (wg == 0) res_mainloop<NKB, NST, 0>(acc0, acc1, sbase, sBar, (tid & 127) == 0);
    else res_mainloop<NKB, NST, 1>(acc0, acc1, sbase, sBar, (tid & 127) == 0);
    wgmma_wait<0>();
    TS(TSK, 4);
#pragma unroll
    for (int j = 0; j < 10; j++) {
      float a[4];
#pragma unroll
      for (int e = 0; e < 4; e++) a[e] = bf16_round(j < 8 ? acc0[4 * j + e] : acc1[4 * (j - 8) + e]);
      const uint32_t o0 = pack_bf16(bf_lo(res[2 * j]) + a[0], bf_hi(res[2 * j]) + a[1]);
      const uint32_t o1 = pack_bf16(bf_lo(res[2 * j + 1]) + a[2], bf_hi(res[2 * j + 1]) + a[3]);
      *reinterpret_cast<uint32_t*>(out + (size_t)row0 * DM + n0 + j * 8 + c4 * 2) = o0;
      *reinterpret_cast<uint32_t*>(out + (size_t)(row0 + 8) * DM + n0 + j * 8 + c4 * 2) = o1;
    }
  }
  __syncwarp();
  TS(TSK, 5);
  cluster_sync_relaxed();
  TS(TSK, 6);
}

constexpr int AT_THREADS = 512;
constexpr int AT_KV_BYTES = IMG_HEAD_ELEMS * 2;
constexpr int AT_SMEM = 2 * AT_KV_BYTES + 256 + 1024;
constexpr int AT_CHUNKS = 8;

__device__ __forceinline__ float exp2_poly(float x) {
  const float u = __saturatef(fmaf(x, 1.0f / 64.0f, 62.0f / 64.0f));
  const float MAGIC = 12582912.0f - 62.0f;
  const float r = fmaf(u, 64.0f, MAGIC);
  const float q = MAGIC - r;
  const float fr = fmaf(u, 64.0f, q);
  float p = fmaf(fr, 0.009570102207362652f, 0.05591785907745361f);
  p = fmaf(p, fr, 0.240247443318367f);
  p = fmaf(p, fr, 0.6931217908859253f);
  p = fmaf(p, fr, 0.9999992847442627f);
  return __uint_as_float(__float_as_uint(p) + (__float_as_uint(r) << 23));
}
__device__ __forceinline__ bool use_poly(int e) { return ((e & 7) == 1) || ((e & 7) == 4) || ((e & 7) == 6); }

__global__ void __launch_bounds__(AT_THREADS, 1) attn_kernel(const bf16* __restrict__ wo, const bf16* __restrict__ wgt, const bf16* __restrict__ wup, const bf16* __restrict__ wdn) {
  extern __shared__ uint8_t smem_raw[];
  const uint32_t sbase = (smem_u32(smem_raw) + 1023u) & ~1023u;
  const uint32_t sK = sbase, sV = sbase + AT_KV_BYTES;
  const uint32_t sBar = sV + AT_KV_BYTES;
  const int tid = threadIdx.x, warp = tid >> 5, lane = tid & 31;
  const int head = blockIdx.x >> 2, quarter = blockIdx.x & 3;
  TS(1, 0);
  if (tid == 0) {
    for (int i = 0; i < AT_CHUNKS; i++) mbar_init(sBar + 8 * i, 1);
    fence_mbar_init();
  }
  pdl_launch();
  if (tid == 32) {
    prefetch_l2(reinterpret_cast<const uint8_t*>(wo) + blockIdx.x * 6400, 6400);
    prefetch_l2(reinterpret_cast<const uint8_t*>(wgt) + blockIdx.x * 15360, 15360);
    prefetch_l2(reinterpret_cast<const uint8_t*>(wup) + blockIdx.x * 15360, 15360);
    prefetch_l2(reinterpret_cast<const uint8_t*>(wdn) + blockIdx.x * 15360, 15360);
  }
  __syncthreads();
  TS(1, 1);
  pdl_wait();
  TS(1, 2);
  if (tid == 0) {
    const uint8_t* kg = reinterpret_cast<const uint8_t*>(g_img + (size_t)(32 + head) * IMG_HEAD_ELEMS);
    const uint8_t* vg = reinterpret_cast<const uint8_t*>(g_img + (size_t)(64 + head) * IMG_HEAD_ELEMS);
    constexpr int CB = AT_KV_BYTES / AT_CHUNKS;
    for (int i = 0; i < AT_CHUNKS; i++) {
      mbar_expect_tx(sBar + 8 * i, 2 * CB);
      bulk_g2s(sK + i * CB, kg + i * CB, CB, sBar + 8 * i);
      bulk_g2s(sV + i * CB, vg + i * CB, CB, sBar + 8 * i);
    }
  }
  const int wg = warp >> 2, wwarp = warp & 3;
  const int g = lane >> 2, c4 = lane & 3;
  const uint64_t dk_base = make_desc(sK, 128, 384, 0);
  const uint64_t dv_base = make_desc(sV, 384, 128, 0);

#pragma unroll 1
  for (int rep = 0; rep < 2; rep++) {
    const int row0 = quarter * 512 + (rep * 4 + wg) * 64 + wwarp * 16 + g;
    uint32_t qa0, qa1, qa2, qa3, qa4, qa5;
    {
      const bf16* q0 = g_img + (size_t)head * IMG_HEAD_ELEMS + (size_t)(row0 >> 3) * 192 + g * 8 + c4 * 2;
      const bf16* q1 = q0 + 192;
      qa0 = *reinterpret_cast<const uint32_t*>(q0);
      qa1 = *reinterpret_cast<const uint32_t*>(q1);
      qa2 = *reinterpret_cast<const uint32_t*>(q0 + 64);
      qa3 = *reinterpret_cast<const uint32_t*>(q1 + 64);
      qa4 = *reinterpret_cast<const uint32_t*>(q0 + 128);
      qa5 = *reinterpret_cast<const uint32_t*>(q1 + 128);
    }
    float o[12];
#pragma unroll
    for (int i = 0; i < 12; i++) o[i] = 0.f;
    float M0 = 0.f, M1 = 0.f;
#pragma unroll 1
    for (int t = 0; t < 16; t++) {
      if (rep == 0) mbar_wait(sBar + 8 * (t >> 1), 0);
      const uint64_t dk = dk_base + (uint64_t)(uint32_t)(t * 384);
      const uint64_t dv = dv_base + (uint64_t)(uint32_t)(t * 384);
      float s[64];
      uint32_t p[32];
      wgmma_fence();
      wgmma_rs_n128(s, qa0, qa1, qa2, qa3, dk, 0);
      wgmma_rs_n128(s, qa4, qa5, 0u, 0u, dk + 16, 1);
      wgmma_commit();
      wgmma_wait<0>();
      bool redo = (t == 0);
      if (!redo) {
#pragma unroll
        for (int j = 0; j < 32; j++) {
          const float e0 = use_poly(2 * j) ? exp2_poly(s[2 * j]) : ex2(s[2 * j]);
          const float e1 = use_poly(2 * j + 1) ? exp2_poly(s[2 * j + 1]) : ex2(s[2 * j + 1]);
          p[j] = pack_bf16(e0, e1);
        }
        uint32_t acc_or = 0;
#pragma unroll
        for (int j = 0; j < 32; j++) acc_or |= p[j];
        redo = wg_any((acc_or & 0x40004000u) != 0, 1 + wg);
        if (redo) {
          wgmma_fence();
          wgmma_rs_n128(s, qa0, qa1, qa2, qa3, dk, 0);
          wgmma_rs_n128(s, qa4, qa5, 0u, 0u, dk + 16, 1);
          wgmma_commit();
          wgmma_wait<0>();
        }
      }
      if (redo) {
        float mx0 = fmaxf(s[0], s[1]), mx1 = fmaxf(s[2], s[3]);
#pragma unroll
        for (int j = 1; j < 16; j++) {
          mx0 = fmaxf(mx0, fmaxf(s[4 * j], s[4 * j + 1]));
          mx1 = fmaxf(mx1, fmaxf(s[4 * j + 2], s[4 * j + 3]));
        }
        mx0 = fmaxf(mx0, __shfl_xor_sync(0xffffffffu, mx0, 1));
        mx1 = fmaxf(mx1, __shfl_xor_sync(0xffffffffu, mx1, 1));
        mx0 = fmaxf(mx0, __shfl_xor_sync(0xffffffffu, mx0, 2));
        mx1 = fmaxf(mx1, __shfl_xor_sync(0xffffffffu, mx1, 2));
        float d0 = mx0 + 7.0f, d1 = mx1 + 7.0f;
        if (t > 0) { d0 = fmaxf(d0, 0.f); d1 = fmaxf(d1, 0.f); }
        const float T0 = M0 + d0, T1 = M1 + d1;
        const float h0 = bf16_round(T0), h1 = bf16_round(T1);
        const float i0 = bf16_round(T0 - h0), i1 = bf16_round(T1 - h1);
        const float l0 = bf16_round((T0 - h0) - i0), l1 = bf16_round((T1 - h1) - i1);
        const float N0 = (h0 + i0) + l0, N1 = (h1 + i1) + l1;
        d0 = N0 - M0; d1 = N1 - M1;
        M0 = N0; M1 = N1;
        if (c4 == 2) { qa4 = pack_bf16(-h0, -i0); qa5 = pack_bf16(-h1, -i1); }
        if (c4 == 3) { qa4 = pack_bf16(-l0, 0.f); qa5 = pack_bf16(-l1, 0.f); }
        if (t > 0) {
          const float al0 = ex2(-d0), al1 = ex2(-d1);
#pragma unroll
          for (int j = 0; j < 3; j++) {
            o[4 * j] *= al0; o[4 * j + 1] *= al0;
            o[4 * j + 2] *= al1; o[4 * j + 3] *= al1;
          }
        }
#pragma unroll
        for (int j = 0; j < 16; j++) {
          p[2 * j] = pack_bf16(ex2(s[4 * j] - d0), ex2(s[4 * j + 1] - d0));
          p[2 * j + 1] = pack_bf16(ex2(s[4 * j + 2] - d1), ex2(s[4 * j + 3] - d1));
        }
      }
      wgmma_fence();
#pragma unroll
      for (int kk = 0; kk < 8; kk++) wgmma_rs_n24_tb(o, p[4 * kk], p[4 * kk + 1], p[4 * kk + 2], p[4 * kk + 3], dv + kk * 48, 1);
      wgmma_commit();
      wgmma_wait<0>();
    }
    TS(1, 3 + rep);
    const float l0 = __shfl_sync(0xffffffffu, o[8], (lane & ~3) | 2);
    const float l1 = __shfl_sync(0xffffffffu, o[10], (lane & ~3) | 2);
    const float i0 = 1.0f / l0, i1 = 1.0f / l1;
    bf16* o0 = g_o + (size_t)row0 * DM + head * DH;
    bf16* o1 = o0 + 8 * DM;
#pragma unroll
    for (int j = 0; j < 3; j++) {
      if (j < 2 || c4 < 2) {
        *reinterpret_cast<uint32_t*>(o0 + j * 8 + c4 * 2) = pack_bf16(o[4 * j] * i0, o[4 * j + 1] * i0);
        *reinterpret_cast<uint32_t*>(o1 + j * 8 + c4 * 2) = pack_bf16(o[4 * j + 2] * i1, o[4 * j + 3] * i1);
      }
    }
  }
}

typedef CUresult (*EncodeTiledFn)(CUtensorMap*, CUtensorMapDataType, cuuint32_t, void*, const cuuint64_t*, const cuuint64_t*,
                                  const cuuint32_t*, const cuuint32_t*, CUtensorMapInterleave, CUtensorMapSwizzle,
                                  CUtensorMapL2promotion, CUtensorMapFloatOOBfill);

static void make_map(EncodeTiledFn fn, CUtensorMap* tm, const void* ptr, uint64_t rows, uint64_t cols, uint32_t box_rows,
                     uint32_t box_cols, CUtensorMapSwizzle sw) {
  cuuint64_t dims[2] = {cols, rows};
  cuuint64_t strides[1] = {cols * 2};
  cuuint32_t box[2] = {box_cols, box_rows};
  cuuint32_t es[2] = {1, 1};
  fn(tm, CU_TENSOR_MAP_DATA_TYPE_BFLOAT16, 2, const_cast<void*>(ptr), dims, strides, box, es, CU_TENSOR_MAP_INTERLEAVE_NONE, sw,
     CU_TENSOR_MAP_L2_PROMOTION_L2_256B, CU_TENSOR_MAP_FLOAT_OOB_FILL_NONE);
}

template <typename... KArgs, typename... Args>
static void launch(void (*kern)(KArgs...), int grid, int block, int smem, int cluster, bool pdl, Args... args) {
  cudaLaunchConfig_t cfg = {};
  cfg.gridDim = dim3(grid);
  cfg.blockDim = dim3(block);
  cfg.dynamicSmemBytes = smem;
  cfg.stream = cudaStreamPerThread;
  cudaLaunchAttribute at[2];
  int n = 0;
  if (cluster > 1) {
    at[n].id = cudaLaunchAttributeClusterDimension;
    at[n].val.clusterDim.x = cluster; at[n].val.clusterDim.y = 1; at[n].val.clusterDim.z = 1;
    n++;
  }
  if (pdl) {
    at[n].id = cudaLaunchAttributeProgrammaticStreamSerialization;
    at[n].val.programmaticStreamSerializationAllowed = 1;
    n++;
  }
  cfg.attrs = at;
  cfg.numAttrs = n;
  cudaLaunchKernelEx(&cfg, kern, KArgs(args)...);
}

extern "C" void kernel_launch(void* const* d_in, const int* in_sizes, int n_in, void* d_out, int out_size) {
  const bf16* x = (const bf16*)d_in[0];
  const bf16* wqkv = (const bf16*)d_in[1];
  const bf16* wo = (const bf16*)d_in[2];
  const bf16* wg = (const bf16*)d_in[4];
  const bf16* wu = (const bf16*)d_in[5];
  const bf16* wd = (const bf16*)d_in[6];
  bf16* out = (bf16*)d_out;

  static EncodeTiledFn enc = nullptr;
  static void *p_o = nullptr, *p_h = nullptr, *p_hh = nullptr, *p_xn = nullptr;
  if (!enc) {
    void* fn = nullptr;
    cudaDriverEntryPointQueryResult qr;
    cudaGetDriverEntryPoint("cuTensorMapEncodeTiled", &fn, cudaEnableDefault, &qr);
    enc = (EncodeTiledFn)fn;
    cudaGetSymbolAddress(&p_o, g_o);
    cudaGetSymbolAddress(&p_h, g_h);
    cudaGetSymbolAddress(&p_hh, g_hh);
    cudaGetSymbolAddress(&p_xn, g_xn);
    cudaFuncSetAttribute(big_gemm_kernel<0>, cudaFuncAttributeMaxDynamicSharedMemorySize, LGCfg<0>::SMEM);
    cudaFuncSetAttribute(big_gemm_kernel<1>, cudaFuncAttributeMaxDynamicSharedMemorySize, LGCfg<1>::SMEM);
    cudaFuncSetAttribute(res_gemm_kernel<DM>, cudaFuncAttributeMaxDynamicSharedMemorySize, RG_SMEM);
    cudaFuncSetAttribute(res_gemm_kernel<FF>, cudaFuncAttributeMaxDynamicSharedMemorySize, RG_SMEM);
    cudaFuncSetAttribute(attn_kernel, cudaFuncAttributeMaxDynamicSharedMemorySize, AT_SMEM);
  }
  CUtensorMap tm_wqkv, tm_wg, tm_wu, tm_wo64, tm_wo16, tm_wd64, tm_wd16, tm_o, tm_hh, tm_xn;
  make_map(enc, &tm_wqkv, wqkv, DM, 3 * DM, 32, 64, CU_TENSOR_MAP_SWIZZLE_128B);
  make_map(enc, &tm_wg, wg, DM, FF, 32, 64, CU_TENSOR_MAP_SWIZZLE_128B);
  make_map(enc, &tm_wu, wu, DM, FF, 32, 64, CU_TENSOR_MAP_SWIZZLE_128B);
  make_map(enc, &tm_wo64, wo, DM, DM, 64, 64, CU_TENSOR_MAP_SWIZZLE_128B);
  make_map(enc, &tm_wo16, wo, DM, DM, 64, 16, CU_TENSOR_MAP_SWIZZLE_32B);
  make_map(enc, &tm_wd64, wd, FF, DM, 64, 64, CU_TENSOR_MAP_SWIZZLE_128B);
  make_map(enc, &tm_wd16, wd, FF, DM, 64, 16, CU_TENSOR_MAP_SWIZZLE_32B);
  make_map(enc, &tm_o, p_o, SEQ, DM, 64, 64, CU_TENSOR_MAP_SWIZZLE_128B);
  make_map(enc, &tm_hh, p_hh, SEQ, FF, 64, 64, CU_TENSOR_MAP_SWIZZLE_128B);
  make_map(enc, &tm_xn, p_xn, SEQ, DM, 128, 32, CU_TENSOR_MAP_SWIZZLE_64B);

  launch(ln_kernel, 128, 256, 0, 1, false, x, (bf16*)p_xn, 0);
  launch(big_gemm_kernel<0>, 128, LG_THREADS, LGCfg<0>::SMEM, 2, true, tm_xn, tm_wqkv, tm_wqkv, tm_wqkv);
  launch(attn_kernel, 128, AT_THREADS, AT_SMEM, 1, true, wo, wg, wu, wd);
  launch(res_gemm_kernel<DM>, 128, RG_THREADS, RG_SMEM, 2, true, tm_o, tm_wo64, tm_wo16, x, (bf16*)p_h);
  launch(ln_kernel, 128, 256, 0, 1, true, (const bf16*)p_h, (bf16*)p_xn, 1);
  launch(big_gemm_kernel<1>, 128, LG_THREADS, LGCfg<1>::SMEM, 2, true, tm_xn, tm_wg, tm_wu, tm_hh);
  launch(res_gemm_kernel<FF>, 128, RG_THREADS, RG_SMEM, 2, true, tm_hh, tm_wd64, tm_wd16, (const bf16*)p_h, out);
}
```

```cpp
#include <cuda_runtime.h>
#include <cuda_bf16.h>
#include <cuda.h>
#include <stdint.h>

typedef __nv_bfloat16 bf16;

constexpr int SEQ = 2048, DM = 640, NH = 32, DH = 20, FF = 1536;
constexpr float ATT_SCALE_LOG2E = 0.22360679774997896f * 1.4426950408889634f;
constexpr int IMG_HEAD_ELEMS = (SEQ / 8) * 192;

__device__ __align__(1024) bf16 g_img[3 * NH * IMG_HEAD_ELEMS];
__device__ __align__(1024) bf16 g_o[SEQ * DM];
__device__ __align__(1024) bf16 g_h[SEQ * DM];
__device__ __align__(1024) bf16 g_xn[SEQ * DM];
__device__ __align__(1024) bf16 g_hh[SEQ * FF];

#define TS(k, i)
__device__ __forceinline__ uint32_t smem_u32(const void* p) { return (uint32_t)__cvta_generic_to_shared(p); }
__device__ __forceinline__ void mbar_init(uint32_t bar, uint32_t cnt) {
  asm volatile("mbarrier.init.shared::cta.b64 [%0], %1;" ::"r"(bar), "r"(cnt) : "memory");
}
__device__ __forceinline__ void mbar_expect_tx(uint32_t bar, uint32_t bytes) {
  asm volatile("mbarrier.arrive.expect_tx.shared::cta.b64 _, [%0], %1;" ::"r"(bar), "r"(bytes) : "memory");
}
__device__ __forceinline__ void mbar_arrive(uint32_t bar) {
  asm volatile("mbarrier.arrive.shared::cta.b64 _, [%0];" ::"r"(bar) : "memory");
}
__device__ __forceinline__ void mbar_arrive_cluster(uint32_t bar, uint32_t cta) {
  asm volatile(
      "{\n.reg .b32 r;\nmapa.shared::cluster.u32 r, %0, %1;\n"
      "mbarrier.arrive.shared::cluster.b64 _, [r];\n}\n" ::"r"(bar), "r"(cta)
      : "memory");
}
__device__ __forceinline__ void mbar_wait(uint32_t bar, uint32_t parity) {
  asm volatile(
      "{\n.reg .pred p;\nLAB_WAIT:\n"
      "mbarrier.try_wait.parity.shared::cta.b64 p, [%0], %1;\n"
      "@p bra DONE;\nbra LAB_WAIT;\nDONE:\n}\n" ::"r"(bar), "r"(parity)
      : "memory");
}
__device__ __forceinline__ void mbar_wait_cluster(uint32_t bar, uint32_t parity) {
  asm volatile(
      "{\n.reg .pred p;\nLAB_WAIT:\n"
      "mbarrier.try_wait.parity.acquire.cluster.shared::cta.b64 p, [%0], %1;\n"
      "@p bra DONE;\nbra LAB_WAIT;\nDONE:\n}\n" ::"r"(bar), "r"(parity)
      : "memory");
}
__device__ __forceinline__ void fence_mbar_init() { asm volatile("fence.mbarrier_init.release.cluster;" ::: "memory"); }
__device__ __forceinline__ void fence_proxy_async() { asm volatile("fence.proxy.async.shared::cta;" ::: "memory"); }
__device__ __forceinline__ void cluster_sync_all() {
  asm volatile("barrier.cluster.arrive.release.aligned;\nbarrier.cluster.wait.acquire.aligned;" ::: "memory");
}
__device__ __forceinline__ void cluster_sync_relaxed() {
  asm volatile("barrier.cluster.arrive.relaxed.aligned;\nbarrier.cluster.wait.aligned;" ::: "memory");
}
__device__ __forceinline__ void named_bar_sync(int id, int n) { asm volatile("bar.sync %0, %1;" ::"r"(id), "r"(n) : "memory"); }
__device__ __forceinline__ bool wg_any(bool pred, int id) {
  uint32_t r;
  asm volatile("{\n.reg .pred p, q;\nsetp.ne.u32 p, %1, 0;\nbar.red.or.pred q, %2, 128, p;\nselp.u32 %0, 1, 0, q;\n}\n" : "=r"(r) : "r"((uint32_t)pred), "r"(id) : "memory");
  return r != 0;
}
__device__ __forceinline__ void pdl_launch() { asm volatile("griddepcontrol.launch_dependents;" ::: "memory"); }
__device__ __forceinline__ void pdl_wait() { asm volatile("griddepcontrol.wait;" ::: "memory"); }

__device__ __forceinline__ void tma_load_2d(uint32_t dst, const CUtensorMap* tm, int c0, int c1, uint32_t bar) {
  asm volatile(
      "cp.async.bulk.tensor.2d.shared::cluster.global.mbarrier::complete_tx::bytes [%0], [%1, {%3, %4}], [%2];" ::"r"(dst),
      "l"((uint64_t)tm), "r"(bar), "r"(c0), "r"(c1)
      : "memory");
}
__device__ __forceinline__ void tma_load_2d_mc(uint32_t dst, const CUtensorMap* tm, int c0, int c1, uint32_t bar, uint16_t mask) {
  asm volatile(
      "cp.async.bulk.tensor.2d.shared::cluster.global.mbarrier::complete_tx::bytes.multicast::cluster [%0], [%1, {%3, %4}], [%2], %5;" ::"r"(dst),
      "l"((uint64_t)tm), "r"(bar), "r"(c0), "r"(c1), "h"(mask)
      : "memory");
}
__device__ __forceinline__ void bulk_g2s(uint32_t dst, const void* src, uint32_t bytes, uint32_t bar) {
  asm volatile("cp.async.bulk.shared::cluster.global.mbarrier::complete_tx::bytes [%0], [%1], %2, [%3];" ::"r"(dst), "l"(src),
               "r"(bytes), "r"(bar)
               : "memory");
}
__device__ __forceinline__ void bulk_s2g(void* dst, uint32_t src, uint32_t bytes) {
  asm volatile("cp.async.bulk.global.shared::cta.bulk_group [%0], [%1], %2;" ::"l"(dst), "r"(src), "r"(bytes) : "memory");
}
__device__ __forceinline__ void tma_store_2d(const CUtensorMap* tm, uint32_t src, int c0, int c1) {
  asm volatile("cp.async.bulk.tensor.2d.global.shared::cta.bulk_group [%0, {%2, %3}], [%1];" ::"l"((uint64_t)tm), "r"(src), "r"(c0), "r"(c1) : "memory");
}
__device__ __forceinline__ void bulk_commit() { asm volatile("cp.async.bulk.commit_group;" ::: "memory"); }
__device__ __forceinline__ void bulk_wait_read() { asm volatile("cp.async.bulk.wait_group.read 0;" ::: "memory"); }
__device__ __forceinline__ void prefetch_l2(const void* p, uint32_t bytes) {
  asm volatile("cp.async.bulk.prefetch.L2.global [%0], %1;" ::"l"(p), "r"(bytes) : "memory");
}
__device__ __forceinline__ void bulk_wait_all() { asm volatile("cp.async.bulk.wait_group 0;" ::: "memory"); }
__device__ __forceinline__ void st_shared_b32(uint32_t addr, uint32_t v) { asm volatile("st.shared.b32 [%0], %1;" ::"r"(addr), "r"(v) : "memory"); }
__device__ __forceinline__ void st_shared_v2(uint32_t addr, uint32_t a, uint32_t b) { asm volatile("st.shared.v2.b32 [%0], {%1, %2};" ::"r"(addr), "r"(a), "r"(b) : "memory"); }
__device__ __forceinline__ void prefetch_tmap(const CUtensorMap* tm) {
  asm volatile("prefetch.tensormap [%0];" ::"l"((uint64_t)tm) : "memory");
}
__device__ __forceinline__ void wgmma_fence() { asm volatile("wgmma.fence.sync.aligned;" ::: "memory"); }
__device__ __forceinline__ void wgmma_commit() { asm volatile("wgmma.commit_group.sync.aligned;" ::: "memory"); }
template <int N>
__device__ __forceinline__ void wgmma_wait() { asm volatile("wgmma.wait_group.sync.aligned %0;" ::"n"(N) : "memory"); }

template <int N>
__device__ __forceinline__ void fence_regs(float (&r)[N]) {
#pragma unroll
  for (int i = 0; i < N; i++) asm volatile("" : "+f"(r[i])::"memory");
}
template <int N>
__device__ __forceinline__ void fence_regs(uint32_t (&r)[N]) {
#pragma unroll
  for (int i = 0; i < N; i++) asm volatile("" : "+r"(r[i])::"memory");
}
__device__ __forceinline__ uint64_t make_desc(uint32_t addr, uint32_t lbo, uint32_t sbo, uint32_t layout) {
  return (uint64_t)((addr & 0x3FFFF) >> 4) | ((uint64_t)((lbo & 0x3FFFF) >> 4) << 16) | ((uint64_t)((sbo & 0x3FFFF) >> 4) << 32) |
         ((uint64_t)layout << 62);
}
__device__ __forceinline__ uint32_t pack_bf16(float lo, float hi) {
  uint32_t r;
  asm("cvt.rn.bf16x2.f32 %0, %1, %2;" : "=r"(r) : "f"(hi), "f"(lo));
  return r;
}
__device__ __forceinline__ float bf16_round(float x) { return __bfloat162float(__float2bfloat16_rn(x)); }
__device__ __forceinline__ float bf_lo(uint32_t u) { return __uint_as_float(u << 16); }
__device__ __forceinline__ float bf_hi(uint32_t u) { return __uint_as_float(u & 0xffff0000u); }
__device__ __forceinline__ float ex2(float x) {
  float y;
  asm("ex2.approx.ftz.f32 %0, %1;" : "=f"(y) : "f"(x));
  return y;
}

__device__ __forceinline__ void wgmma_ss_n240_tb(float (&d)[120], uint64_t descA, uint64_t descB, int scaleD) {
  asm volatile("{\n.reg .pred p;\nsetp.ne.b32 p, %122, 0;\n"
    "wgmma.mma_async.sync.aligned.m64n240k16.f32.bf16.bf16 {%0, %1, %2, %3, %4, %5, %6, %7, %8, %9, %10, %11, %12, %13, %14, %15, %16, %17, %18, %19, %20, %21, %22, %23, %24, %25, %26, %27, %28, %29, %30, %31, %32, %33, %34, %35, %36, %37, %38, %39, %40, %41, %42, %43, %44, %45, %46, %47, %48, %49, %50, %51, %52, %53, %54, %55, %56, %57, %58, %59, %60, %61, %62, %63, %64, %65, %66, %67, %68, %69, %70, %71, %72, %73, %74, %75, %76, %77, %78, %79, %80, %81, %82, %83, %84, %85, %86, %87, %88, %89, %90, %91, %92, %93, %94, %95, %96, %97, %98, %99, %100, %101, %102, %103, %104, %105, %106, %107, %108, %109, %110, %111, %112, %113, %114, %115, %116, %117, %118, %119}, %120, %121, p, 1, 1, 0, 1;\n}\n"
    : "+f"(d[0]), "+f"(d[1]), "+f"(d[2]), "+f"(d[3]), "+f"(d[4]), "+f"(d[5]), "+f"(d[6]), "+f"(d[7]), "+f"(d[8]), "+f"(d[9]), "+f"(d[10]), "+f"(d[11]), "+f"(d[12]), "+f"(d[13]), "+f"(d[14]), "+f"(d[15]), "+f"(d[16]), "+f"(d[17]), "+f"(d[18]), "+f"(d[19]), "+f"(d[20]), "+f"(d[21]), "+f"(d[22]), "+f"(d[23]), "+f"(d[24]), "+f"(d[25]), "+f"(d[26]), "+f"(d[27]), "+f"(d[28]), "+f"(d[29]), "+f"(d[30]), "+f"(d[31]), "+f"(d[32]), "+f"(d[33]), "+f"(d[34]), "+f"(d[35]), "+f"(d[36]), "+f"(d[37]), "+f"(d[38]), "+f"(d[39]), "+f"(d[40]), "+f"(d[41]), "+f"(d[42]), "+f"(d[43]), "+f"(d[44]), "+f"(d[45]), "+f"(d[46]), "+f"(d[47]), "+f"(d[48]), "+f"(d[49]), "+f"(d[50]), "+f"(d[51]), "+f"(d[52]), "+f"(d[53]), "+f"(d[54]), "+f"(d[55]), "+f"(d[56]), "+f"(d[57]), "+f"(d[58]), "+f"(d[59]), "+f"(d[60]), "+f"(d[61]), "+f"(d[62]), "+f"(d[63]), "+f"(d[64]), "+f"(d[65]), "+f"(d[66]), "+f"(d[67]), "+f"(d[68]), "+f"(d[69]), "+f"(d[70]), "+f"(d[71]), "+f"(d[72]), "+f"(d[73]), "+f"(d[74]), "+f"(d[75]), "+f"(d[76]), "+f"(d[77]), "+f"(d[78]), "+f"(d[79]), "+f"(d[80]), "+f"(d[81]), "+f"(d[82]), "+f"(d[83]), "+f"(d[84]), "+f"(d[85]), "+f"(d[86]), "+f"(d[87]), "+f"(d[88]), "+f"(d[89]), "+f"(d[90]), "+f"(d[91]), "+f"(d[92]), "+f"(d[93]), "+f"(d[94]), "+f"(d[95]), "+f"(d[96]), "+f"(d[97]), "+f"(d[98]), "+f"(d[99]), "+f"(d[100]), "+f"(d[101]), "+f"(d[102]), "+f"(d[103]), "+f"(d[104]), "+f"(d[105]), "+f"(d[106]), "+f"(d[107]), "+f"(d[108]), "+f"(d[109]), "+f"(d[110]), "+f"(d[111]), "+f"(d[112]), "+f"(d[113]), "+f"(d[114]), "+f"(d[115]), "+f"(d[116]), "+f"(d[117]), "+f"(d[118]), "+f"(d[119])
    : "l"(descA), "l"(descB), "r"(scaleD));
}
__device__ __forceinline__ void wgmma_ss_n192_tb(float (&d)[96], uint64_t descA, uint64_t descB, int scaleD) {
  asm volatile("{\n.reg .pred p;\nsetp.ne.b32 p, %98, 0;\n"
    "wgmma.mma_async.sync.aligned.m64n192k16.f32.bf16.bf16 {%0, %1, %2, %3, %4, %5, %6, %7, %8, %9, %10, %11, %12, %13, %14, %15, %16, %17, %18, %19, %20, %21, %22, %23, %24, %25, %26, %27, %28, %29, %30, %31, %32, %33, %34, %35, %36, %37, %38, %39, %40, %41, %42, %43, %44, %45, %46, %47, %48, %49, %50, %51, %52, %53, %54, %55, %56, %57, %58, %59, %60, %61, %62, %63, %64, %65, %66, %67, %68, %69, %70, %71, %72, %73, %74, %75, %76, %77, %78, %79, %80, %81, %82, %83, %84, %85, %86, %87, %88, %89, %90, %91, %92, %93, %94, %95}, %96, %97, p, 1, 1, 0, 1;\n}\n"
    : "+f"(d[0]), "+f"(d[1]), "+f"(d[2]), "+f"(d[3]), "+f"(d[4]), "+f"(d[5]), "+f"(d[6]), "+f"(d[7]), "+f"(d[8]), "+f"(d[9]), "+f"(d[10]), "+f"(d[11]), "+f"(d[12]), "+f"(d[13]), "+f"(d[14]), "+f"(d[15]), "+f"(d[16]), "+f"(d[17]), "+f"(d[18]), "+f"(d[19]), "+f"(d[20]), "+f"(d[21]), "+f"(d[22]), "+f"(d[23]), "+f"(d[24]), "+f"(d[25]), "+f"(d[26]), "+f"(d[27]), "+f"(d[28]), "+f"(d[29]), "+f"(d[30]), "+f"(d[31]), "+f"(d[32]), "+f"(d[33]), "+f"(d[34]), "+f"(d[35]), "+f"(d[36]), "+f"(d[37]), "+f"(d[38]), "+f"(d[39]), "+f"(d[40]), "+f"(d[41]), "+f"(d[42]), "+f"(d[43]), "+f"(d[44]), "+f"(d[45]), "+f"(d[46]), "+f"(d[47]), "+f"(d[48]), "+f"(d[49]), "+f"(d[50]), "+f"(d[51]), "+f"(d[52]), "+f"(d[53]), "+f"(d[54]), "+f"(d[55]), "+f"(d[56]), "+f"(d[57]), "+f"(d[58]), "+f"(d[59]), "+f"(d[60]), "+f"(d[61]), "+f"(d[62]), "+f"(d[63]), "+f"(d[64]), "+f"(d[65]), "+f"(d[66]), "+f"(d[67]), "+f"(d[68]), "+f"(d[69]), "+f"(d[70]), "+f"(d[71]), "+f"(d[72]), "+f"(d[73]), "+f"(d[74]), "+f"(d[75]), "+f"(d[76]), "+f"(d[77]), "+f"(d[78]), "+f"(d[79]), "+f"(d[80]), "+f"(d[81]), "+f"(d[82]), "+f"(d[83]), "+f"(d[84]), "+f"(d[85]), "+f"(d[86]), "+f"(d[87]), "+f"(d[88]), "+f"(d[89]), "+f"(d[90]), "+f"(d[91]), "+f"(d[92]), "+f"(d[93]), "+f"(d[94]), "+f"(d[95])
    : "l"(descA), "l"(descB), "r"(scaleD));
}
__device__ __forceinline__ void wgmma_ss_n64_tb(float (&d)[32], uint64_t descA, uint64_t descB, int scaleD) {
  asm volatile("{\n.reg .pred p;\nsetp.ne.b32 p, %34, 0;\n"
    "wgmma.mma_async.sync.aligned.m64n64k16.f32.bf16.bf16 {%0, %1, %2, %3, %4, %5, %6, %7, %8, %9, %10, %11, %12, %13, %14, %15, %16, %17, %18, %19, %20, %21, %22, %23, %24, %25, %26, %27, %28, %29, %30, %31}, %32, %33, p, 1, 1, 0, 1;\n}\n"
    : "+f"(d[0]), "+f"(d[1]), "+f"(d[2]), "+f"(d[3]), "+f"(d[4]), "+f"(d[5]), "+f"(d[6]), "+f"(d[7]), "+f"(d[8]), "+f"(d[9]), "+f"(d[10]), "+f"(d[11]), "+f"(d[12]), "+f"(d[13]), "+f"(d[14]), "+f"(d[15]), "+f"(d[16]), "+f"(d[17]), "+f"(d[18]), "+f"(d[19]), "+f"(d[20]), "+f"(d[21]), "+f"(d[22]), "+f"(d[23]), "+f"(d[24]), "+f"(d[25]), "+f"(d[26]), "+f"(d[27]), "+f"(d[28]), "+f"(d[29]), "+f"(d[30]), "+f"(d[31])
    : "l"(descA), "l"(descB), "r"(scaleD));
}
__device__ __forceinline__ void wgmma_ss_n16_tb(float (&d)[8], uint64_t descA, uint64_t descB, int scaleD) {
  asm volatile("{\n.reg .pred p;\nsetp.ne.b32 p, %10, 0;\n"
    "wgmma.mma_async.sync.aligned.m64n16k16.f32.bf16.bf16 {%0, %1, %2, %3, %4, %5, %6, %7}, %8, %9, p, 1, 1, 0, 1;\n}\n"
    : "+f"(d[0]), "+f"(d[1]), "+f"(d[2]), "+f"(d[3]), "+f"(d[4]), "+f"(d[5]), "+f"(d[6]), "+f"(d[7])
    : "l"(descA), "l"(descB), "r"(scaleD));
}
__device__ __forceinline__ void wgmma_rs_n128(float (&d)[64], uint32_t a0, uint32_t a1, uint32_t a2, uint32_t a3, uint64_t descB, int scaleD) {
  asm volatile("{\n.reg .pred p;\nsetp.ne.b32 p, %69, 0;\n"
    "wgmma.mma_async.sync.aligned.m64n128k16.f32.bf16.bf16 {%0, %1, %2, %3, %4, %5, %6, %7, %8, %9, %10, %11, %12, %13, %14, %15, %16, %17, %18, %19, %20, %21, %22, %23, %24, %25, %26, %27, %28, %29, %30, %31, %32, %33, %34, %35, %36, %37, %38, %39, %40, %41, %42, %43, %44, %45, %46, %47, %48, %49, %50, %51, %52, %53, %54, %55, %56, %57, %58, %59, %60, %61, %62, %63}, {%64, %65, %66, %67}, %68, p, 1, 1, 0;\n}\n"
    : "+f"(d[0]), "+f"(d[1]), "+f"(d[2]), "+f"(d[3]), "+f"(d[4]), "+f"(d[5]), "+f"(d[6]), "+f"(d[7]), "+f"(d[8]), "+f"(d[9]), "+f"(d[10]), "+f"(d[11]), "+f"(d[12]), "+f"(d[13]), "+f"(d[14]), "+f"(d[15]), "+f"(d[16]), "+f"(d[17]), "+f"(d[18]), "+f"(d[19]), "+f"(d[20]), "+f"(d[21]), "+f"(d[22]), "+f"(d[23]), "+f"(d[24]), "+f"(d[25]), "+f"(d[26]), "+f"(d[27]), "+f"(d[28]), "+f"(d[29]), "+f"(d[30]), "+f"(d[31]), "+f"(d[32]), "+f"(d[33]), "+f"(d[34]), "+f"(d[35]), "+f"(d[36]), "+f"(d[37]), "+f"(d[38]), "+f"(d[39]), "+f"(d[40]), "+f"(d[41]), "+f"(d[42]), "+f"(d[43]), "+f"(d[44]), "+f"(d[45]), "+f"(d[46]), "+f"(d[47]), "+f"(d[48]), "+f"(d[49]), "+f"(d[50]), "+f"(d[51]), "+f"(d[52]), "+f"(d[53]), "+f"(d[54]), "+f"(d[55]), "+f"(d[56]), "+f"(d[57]), "+f"(d[58]), "+f"(d[59]), "+f"(d[60]), "+f"(d[61]), "+f"(d[62]), "+f"(d[63])
    : "r"(a0), "r"(a1), "r"(a2), "r"(a3), "l"(descB), "r"(scaleD));
}
__device__ __forceinline__ void wgmma_rs_n64(float (&d)[32], uint32_t a0, uint32_t a1, uint32_t a2, uint32_t a3, uint64_t descB, int scaleD) {
  asm volatile("{\n.reg .pred p;\nsetp.ne.b32 p, %37, 0;\n"
    "wgmma.mma_async.sync.aligned.m64n64k16.f32.bf16.bf16 {%0, %1, %2, %3, %4, %5, %6, %7, %8, %9, %10, %11, %12, %13, %14, %15, %16, %17, %18, %19, %20, %21, %22, %23, %24, %25, %26, %27, %28, %29, %30, %31}, {%32, %33, %34, %35}, %36, p, 1, 1, 0;\n}\n"
    : "+f"(d[0]), "+f"(d[1]), "+f"(d[2]), "+f"(d[3]), "+f"(d[4]), "+f"(d[5]), "+f"(d[6]), "+f"(d[7]), "+f"(d[8]), "+f"(d[9]), "+f"(d[10]), "+f"(d[11]), "+f"(d[12]), "+f"(d[13]), "+f"(d[14]), "+f"(d[15]), "+f"(d[16]), "+f"(d[17]), "+f"(d[18]), "+f"(d[19]), "+f"(d[20]), "+f"(d[21]), "+f"(d[22]), "+f"(d[23]), "+f"(d[24]), "+f"(d[25]), "+f"(d[26]), "+f"(d[27]), "+f"(d[28]), "+f"(d[29]), "+f"(d[30]), "+f"(d[31])
    : "r"(a0), "r"(a1), "r"(a2), "r"(a3), "l"(descB), "r"(scaleD));
}
__device__ __forceinline__ void wgmma_rs_n24_tb(float (&d)[12], uint32_t a0, uint32_t a1, uint32_t a2, uint32_t a3, uint64_t descB, int scaleD) {
  asm volatile("{\n.reg .pred p;\nsetp.ne.b32 p, %17, 0;\n"
    "wgmma.mma_async.sync.aligned.m64n24k16.f32.bf16.bf16 {%0, %1, %2, %3, %4, %5, %6, %7, %8, %9, %10, %11}, {%12, %13, %14, %15}, %16, p, 1, 1, 1;\n}\n"
    : "+f"(d[0]), "+f"(d[1]), "+f"(d[2]), "+f"(d[3]), "+f"(d[4]), "+f"(d[5]), "+f"(d[6]), "+f"(d[7]), "+f"(d[8]), "+f"(d[9]), "+f"(d[10]), "+f"(d[11])
    : "r"(a0), "r"(a1), "r"(a2), "r"(a3), "l"(descB), "r"(scaleD));
}

__global__ void __launch_bounds__(256) ln_kernel(const bf16* __restrict__ xin, bf16* __restrict__ xout, int tsk) {
  const int warp = threadIdx.x >> 5, lane = threadIdx.x & 31;
  const int hw = lane >> 4, l16 = lane & 15;
  const int row = (blockIdx.x * 8 + warp) * 2 + hw;
  pdl_launch();
  pdl_wait();
  const uint4* src = reinterpret_cast<const uint4*>(xin + (size_t)row * DM);
  uint4 v[5];
#pragma unroll
  for (int j = 0; j < 5; j++) v[j] = __ldg(src + j * 16 + l16);
  float s0 = 0.f, s1 = 0.f, s2 = 0.f, s3 = 0.f;
#pragma unroll
  for (int j = 0; j < 5; j++) {
    s0 += bf_lo(v[j].x) + bf_hi(v[j].x);
    s1 += bf_lo(v[j].y) + bf_hi(v[j].y);
    s2 += bf_lo(v[j].z) + bf_hi(v[j].z);
    s3 += bf_lo(v[j].w) + bf_hi(v[j].w);
  }
  float mean = (s0 + s1) + (s2 + s3);
#pragma unroll
  for (int o = 1; o < 16; o <<= 1) mean += __shfl_xor_sync(0xffffffffu, mean, o);
  mean *= (1.0f / DM);
  s0 = s1 = s2 = s3 = 0.f;
#pragma unroll
  for (int j = 0; j < 5; j++) {
    float d;
    d = bf_lo(v[j].x) - mean; s0 = fmaf(d, d, s0);
    d = bf_hi(v[j].x) - mean; s1 = fmaf(d, d, s1);
    d = bf_lo(v[j].y) - mean; s2 = fmaf(d, d, s2);
    d = bf_hi(v[j].y) - mean; s3 = fmaf(d, d, s3);
    d = bf_lo(v[j].z) - mean; s0 = fmaf(d, d, s0);
    d = bf_hi(v[j].z) - mean; s1 = fmaf(d, d, s1);
    d = bf_lo(v[j].w) - mean; s2 = fmaf(d, d, s2);
    d = bf_hi(v[j].w) - mean; s3 = fmaf(d, d, s3);
  }
  float sq = (s0 + s1) + (s2 + s3);
#pragma unroll
  for (int o = 1; o < 16; o <<= 1) sq += __shfl_xor_sync(0xffffffffu, sq, o);
  const float var_b = bf16_round(sq * (1.0f / DM));
  const float den = bf16_round(sqrtf(bf16_round(var_b + 1e-5f)));
  const float iv = __frcp_rn(den);
  const float mb = bf16_round(mean);
  uint4* dst = reinterpret_cast<uint4*>(xout + (size_t)row * DM);
#pragma unroll
  for (int j = 0; j < 5; j++) {
    uint4 w;
    uint32_t t;
    t = pack_bf16(bf_lo(v[j].x) - mb, bf_hi(v[j].x) - mb); w.x = pack_bf16(bf_lo(t) * iv, bf_hi(t) * iv);
    t = pack_bf16(bf_lo(v[j].y) - mb, bf_hi(v[j].y) - mb); w.y = pack_bf16(bf_lo(t) * iv, bf_hi(t) * iv);
    t = pack_bf16(bf_lo(v[j].z) - mb, bf_hi(v[j].z) - mb); w.z = pack_bf16(bf_lo(t) * iv, bf_hi(t) * iv);
    t = pack_bf16(bf_lo(v[j].w) - mb, bf_hi(v[j].w) - mb); w.w = pack_bf16(bf_lo(t) * iv, bf_hi(t) * iv);
    dst[j * 16 + l16] = w;
  }
}

constexpr int LG_THREADS = 384;
constexpr int LG_STAGES = 5;
template <int MODE>
struct LGCfg {
  static constexpr int NSLAB = MODE == 0 ? 4 : 6;
  static constexpr int STAGE_BYTES = 8192 + NSLAB * 4096;
  static constexpr int SMEM = LG_STAGES * STAGE_BYTES + 128 + 1024;
};

template <int WG>
__device__ __forceinline__ void qkv_mainloop(float (&acc)[120], uint32_t sbase, uint32_t sBar, bool leader) {
  constexpr int STAGE_BYTES = LGCfg<0>::STAGE_BYTES, NST = LG_STAGES;
  const uint64_t da_base = make_desc(sbase + WG * 4096, 16, 512, 2);
  const uint64_t db_base = make_desc(sbase + 8192, 4096, 1024, 1);
#pragma unroll 1
  for (int r = 0; r < 20 / NST; r++) {
#pragma unroll
    for (int s = 0; s < NST; s++) {
      mbar_wait(sBar + 8 * s, r & 1);
      wgmma_fence();
#pragma unroll
      for (int ks = 0; ks < 2; ks++)
        wgmma_ss_n240_tb(acc, da_base + (uint64_t)((s * STAGE_BYTES + ks * 32) >> 4), db_base + (uint64_t)((s * STAGE_BYTES + ks * 2048) >> 4), 1);
      wgmma_commit();
      wgmma_wait<1>();
      if (leader && (s > 0 || r > 0)) {
        const int ps = (s + NST - 1) % NST;
        mbar_arrive_cluster(sBar + 8 * (NST + ps), 0);
        mbar_arrive_cluster(sBar + 8 * (NST + ps), 1);
      }
    }
  }
}
template <int WG>
__device__ __forceinline__ void glu_mainloop(float (&accg)[96], float (&accu)[96], uint32_t sbase, uint32_t sBar, bool leader) {
  constexpr int STAGE_BYTES = LGCfg<1>::STAGE_BYTES, NST = LG_STAGES;
  const uint64_t da_base = make_desc(sbase + WG * 4096, 16, 512, 2);
  const uint64_t db_base = make_desc(sbase + 8192, 4096, 1024, 1);
#pragma unroll 1
  for (int r = 0; r < 20 / NST; r++) {
#pragma unroll
    for (int s = 0; s < NST; s++) {
      mbar_wait(sBar + 8 * s, r & 1);
      wgmma_fence();
#pragma unroll
      for (int ks = 0; ks < 2; ks++) {
        const uint64_t da = da_base + (uint64_t)((s * STAGE_BYTES + ks * 32) >> 4);
        wgmma_ss_n192_tb(accg, da, db_base + (uint64_t)((s * STAGE_BYTES + ks * 2048) >> 4), 1);
        wgmma_ss_n192_tb(accu, da, db_base + (uint64_t)((s * STAGE_BYTES + 3 * 4096 + ks * 2048) >> 4), 1);
      }
      wgmma_commit();
      wgmma_wait<1>();
      if (leader && (s > 0 || r > 0)) {
        const int ps = (s + NST - 1) % NST;
        mbar_arrive_cluster(sBar + 8 * (NST + ps), 0);
        mbar_arrive_cluster(sBar + 8 * (NST + ps), 1);
      }
    }
  }
}

template <int MODE>
__global__ void __launch_bounds__(LG_THREADS, 1)
big_gemm_kernel(const __grid_constant__ CUtensorMap tmA, const __grid_constant__ CUtensorMap tmB0, const __grid_constant__ CUtensorMap tmB1,
                const __grid_constant__ CUtensorMap tmOut) {
  using C = LGCfg<MODE>;
  constexpr int STAGE_BYTES = C::STAGE_BYTES, NST = LG_STAGES, NKB = 20;
  extern __shared__ uint8_t smem_raw[];
  const uint32_t sbase = (smem_u32(smem_raw) + 1023u) & ~1023u;
  const uint32_t sBar = sbase + NST * STAGE_BYTES;
  const int tid = threadIdx.x, warp = tid >> 5, lane = tid & 31;
  const int rank = blockIdx.x & 1;
  const int pair = blockIdx.x >> 1;
  const int n_blk = pair & 7;
  const int m_blk = (pair >> 3) * 2 + rank;
  TS(MODE * 3, 0);
  if (tid == 256) {
    prefetch_tmap(&tmA);
    prefetch_tmap(&tmB0);
    if (MODE == 1) { prefetch_tmap(&tmB1); prefetch_tmap(&tmOut); }
  }
  if (tid == 0) {
    for (int s = 0; s < NST; s++) {
      mbar_init(sBar + 8 * s, 1);
      mbar_init(sBar + 8 * (NST + s), 4);
    }
    fence_mbar_init();
  }
  pdl_launch();
  cluster_sync_all();

  if (warp >= 8) {
    asm volatile("setmaxnreg.dec.sync.aligned.u32 40;");
    if (tid == 256) {
      auto issue_b = [&](int kb) {
        const int s = kb % NST;
        const uint32_t full = sBar + 8 * s;
        mbar_expect_tx(full, STAGE_BYTES);
        const uint32_t dst = sbase + s * STAGE_BYTES + 8192;
        if (MODE == 0) {
#pragma unroll
          for (int j = 0; j < 2; j++) {
            const int sl = rank * 2 + j;
            tma_load_2d_mc(dst + sl * 4096, &tmB0, n_blk * 240 + sl * 64, kb * 32, full, (uint16_t)3);
          }
        } else {
#pragma unroll
          for (int j = 0; j < 3; j++)
            tma_load_2d_mc(dst + (rank * 3 + j) * 4096, rank == 0 ? &tmB0 : &tmB1, n_blk * 192 + j * 64, kb * 32, full, (uint16_t)3);
        }
      };
      for (int kb = 0; kb < NST; kb++) issue_b(kb);
      pdl_wait();
      for (int kb = 0; kb < NKB; kb++) {
        const int s = kb % NST;
        if (kb >= NST) {
          mbar_wait(sBar + 8 * (NST + s), ((kb / NST) & 1) ^ 1);
          issue_b(kb);
        }
        tma_load_2d(sbase + s * STAGE_BYTES, &tmA, kb * 32, m_blk * 128, sBar + 8 * s);
      }
    }
  } else {
    asm volatile("setmaxnreg.inc.sync.aligned.u32 232;");
    const int wg = __shfl_sync(0xffffffffu, warp >> 2, 0);
    const int wwarp = warp & 3;
    TS(MODE * 3, 1);
    mbar_wait(sBar, 0);
    TS(MODE * 3, 3);
    if (MODE == 0) {
      float acc[120];
#pragma unroll
      for (int i = 0; i < 120; i++) acc[i] = 0.f;
      if (wg == 0) qkv_mainloop<0>(acc, sbase, sBar, (tid & 127) == 0);
      else qkv_mainloop<1>(acc, sbase, sBar, (tid & 127) == 0);
      wgmma_wait<0>();
      fence_regs(acc);
      TS(0, 4);
      named_bar_sync(3, 256);
      const int g = lane >> 2, c4 = lane & 3;
      const uint32_t stg = sbase + wg * (12 * 3072) + (wwarp * 2) * 384 + g * 16;
      const int hbase = n_blk * 12;
#pragma unroll
      for (int j = 0; j < 30; j++) {
        const int cb = (j * 8) % 20;
        const int hb = (j * 8) / 20;
        int d = cb + c4 * 2;
        int hl = hb;
        if (cb == 16 && c4 >= 2) { d -= 20; hl += 1; }
        const uint32_t a0 = stg + hl * 3072 + (d >> 3) * 128 + (d & 7) * 2;
        const int hg = hbase + hl;
        const float sc = hg < 32 ? ATT_SCALE_LOG2E : 1.0f;
        st_shared_b32(a0, pack_bf16(acc[4 * j] * sc, acc[4 * j + 1] * sc));
        st_shared_b32(a0 + 384, pack_bf16(acc[4 * j + 2] * sc, acc[4 * j + 3] * sc));
        if (d == 18) {
          const uint32_t pad0 = hg < 32 ? 0u : (hg < 64 ? 0x3f803f80u : 0x00003f80u);
          const uint32_t pad1 = (hg >= 32 && hg < 64) ? 0x00003f80u : 0u;
          st_shared_v2(a0 + 4, pad0, pad1);
          st_shared_v2(a0 + 388, pad0, pad1);
        }
      }
      fence_proxy_async();
      named_bar_sync(1 + wg, 128);
      if ((tid & 127) < 12) {
        const int hl = tid & 127;
        bf16* dst = g_img + (size_t)(hbase + hl) * IMG_HEAD_ELEMS + (size_t)(m_blk * 16 + wg * 8) * 192;
        bulk_s2g(dst, sbase + wg * (12 * 3072) + hl * 3072, 3072);
        bulk_commit();
        bulk_wait_read();
      }
    } else {
      float accg[96], accu[96];
#pragma unroll
      for (int i = 0; i < 96; i++) { accg[i] = 0.f; accu[i] = 0.f; }
      if (wg == 0) glu_mainloop<0>(accg, accu, sbase, sBar, (tid & 127) == 0);
      else glu_mainloop<1>(accg, accu, sbase, sBar, (tid & 127) == 0);
      wgmma_wait<0>();
      fence_regs(accg); fence_regs(accu);
      TS(3, 4);
      named_bar_sync(3, 256);
      const int g = lane >> 2, c4 = lane & 3;
      const uint32_t stg = sbase + wg * 24576 + (wwarp * 16 + g) * 128 + c4 * 4;
#pragma unroll
      for (int j = 0; j < 24; j++) {
        uint32_t pk[2];
#pragma unroll
        for (int h = 0; h < 2; h++) {
          const uint32_t gp = pack_bf16(accg[4 * j + 2 * h], accg[4 * j + 2 * h + 1]);
          const uint32_t up = pack_bf16(accu[4 * j + 2 * h], accu[4 * j + 2 * h + 1]);
          const float g0 = bf_lo(gp), g1 = bf_hi(gp);
          const float r0 = (g0 * (g0 > 0.f ? 1.f : 0.f)) * bf_lo(up);
          const float r1 = (g1 * (g1 > 0.f ? 1.f : 0.f)) * bf_hi(up);
          pk[h] = pack_bf16(r0, r1);
        }
        const uint32_t a0 = stg + (j >> 3) * 8192 + (((j & 7) ^ g) << 4);
        st_shared_b32(a0, pk[0]);
        st_shared_b32(a0 + 1024, pk[1]);
      }
      fence_proxy_async();
      named_bar_sync(1 + wg, 128);
      if ((tid & 127) == 0) {
#pragma unroll
        for (int sl = 0; sl < 3; sl++) tma_store_2d(&tmOut, sbase + wg * 24576 + sl * 8192, n_blk * 192 + sl * 64, m_blk * 128 + wg * 64);
        bulk_commit();
        bulk_wait_read();
      }
    }
  }
  __syncwarp();
  TS(MODE * 3, 5);
  cluster_sync_relaxed();
  TS(MODE * 3, 6);
}

constexpr int RG_THREADS = 288;
constexpr int RG_STAGES = 8;
constexpr int RG_STAGE_BYTES = 16384 + 8192 + 2048;
constexpr int RG_SMEM = RG_STAGES * RG_STAGE_BYTES + 256 + 1024;

template <int NKB, int NST, int WG>
__device__ __forceinline__ void res_mainloop(float (&acc0)[32], float (&acc1)[8], uint32_t sbase, uint32_t sBar, bool leader) {
  const uint64_t da_base = make_desc(sbase + WG * 8192, 16, 1024, 1);
  const uint64_t db0_base = make_desc(sbase + 16384, 8192, 1024, 1);
  const uint64_t db1_base = make_desc(sbase + 16384 + 8192, 2048, 256, 3);
#pragma unroll 1
  for (int r = 0; r < NKB / NST; r++) {
#pragma unroll
    for (int s = 0; s < NST; s++) {
      const uint64_t so = (uint64_t)(s * (RG_STAGE_BYTES >> 4));
      mbar_wait(sBar + 8 * s, r & 1);
      wgmma_fence();
#pragma unroll
      for (int ks = 0; ks < 4; ks++) {
        wgmma_ss_n64_tb(acc0, da_base + so + ks * 2, db0_base + so + ks * 128, 1);
        wgmma_ss_n16_tb(acc1, da_base + so + ks * 2, db1_base + so + ks * 32, 1);
      }
      wgmma_commit();
      wgmma_wait<1>();
      if (leader && (s > 0 || r > 0)) {
        const int ps = (s + NST - 1) % NST;
        mbar_arrive_cluster(sBar + 8 * (NST + ps), 0);
        mbar_arrive_cluster(sBar + 8 * (NST + ps), 1);
      }
    }
  }
}

template <int KTOT>
__global__ void __launch_bounds__(RG_THREADS, 1)
res_gemm_kernel(const __grid_constant__ CUtensorMap tmA, const __grid_constant__ CUtensorMap tmB64, const __grid_constant__ CUtensorMap tmB16,
                const bf16* __restrict__ resid, bf16* __restrict__ out) {
  constexpr int NKB = KTOT / 64;
  constexpr int NST = (KTOT == DM) ? 5 : 8;
  extern __shared__ uint8_t smem_raw[];
  const uint32_t sbase = (smem_u32(smem_raw) + 1023u) & ~1023u;
  const uint32_t sBar = sbase + NST * RG_STAGE_BYTES;
  const int tid = threadIdx.x, warp = tid >> 5, lane = tid & 31;
  const int rank = blockIdx.x & 1;
  const int pair = blockIdx.x >> 1;
  const int m_blk = pair >> 2;
  const int n_blk = (pair & 3) * 2 + rank;
  const int n0 = n_blk * 80;
  constexpr int TSK = KTOT == DM ? 2 : 4;
  TS(TSK, 0);

  if (tid == 0) {
    for (int s = 0; s < NST; s++) {
      mbar_init(sBar + 8 * s, 1);
      mbar_init(sBar + 8 * (NST + s), 4);
    }
    fence_mbar_init();
  }
  pdl_launch();
  cluster_sync_all();

  if (warp == 8) {
    if (lane == 0) {
      prefetch_tmap(&tmA); prefetch_tmap(&tmB64); prefetch_tmap(&tmB16);
      constexpr int PRE = NKB < NST ? NKB : NST;
      for (int kb = 0; kb < PRE; kb++) {
        const uint32_t full = sBar + 8 * kb;
        const uint32_t st = sbase + kb * RG_STAGE_BYTES;
        mbar_expect_tx(full, RG_STAGE_BYTES);
        tma_load_2d(st + 16384, &tmB64, n0, kb * 64, full);
        tma_load_2d(st + 16384 + 8192, &tmB16, n0 + 64, kb * 64, full);
      }
      pdl_wait();
      for (int kb = 0; kb < NKB; kb++) {
        const int s = kb % NST;
        const uint32_t full = sBar + 8 * s;
        const uint32_t st = sbase + s * RG_STAGE_BYTES;
        if (kb >= PRE) {
          const uint32_t ph = (kb / NST) & 1;
          mbar_wait(sBar + 8 * (NST + s), ph ^ 1);
          mbar_expect_tx(full, RG_STAGE_BYTES);
          tma_load_2d(st + 16384, &tmB64, n0, kb * 64, full);
          tma_load_2d(st + 16384 + 8192, &tmB16, n0 + 64, kb * 64, full);
        }
        tma_load_2d_mc(st + rank * 8192, &tmA, kb * 64, m_blk * 128 + rank * 64, full, (uint16_t)3);
      }
    }
  } else {
    const int wg = __shfl_sync(0xffffffffu, warp >> 2, 0), wwarp = warp & 3;
    const int g = lane >> 2, c4 = lane & 3;
    const int row0 = m_blk * 128 + wg * 64 + wwarp * 16 + g;
    TS(TSK, 1);
    pdl_wait();
    TS(TSK, 2);
    uint32_t res[20];
#pragma unroll
    for (int j = 0; j < 10; j++) {
      res[2 * j] = __ldg(reinterpret_cast<const uint32_t*>(resid + (size_t)row0 * DM + n0 + j * 8 + c4 * 2));
      res[2 * j + 1] = __ldg(reinterpret_cast<const uint32_t*>(resid + (size_t)(row0 + 8) * DM + n0 + j * 8 + c4 * 2));
    }
    float acc0[32], acc1[8];
#pragma unroll
    for (int i = 0; i < 32; i++) acc0[i] = 0.f;
#pragma unroll
    for (int i = 0; i < 8; i++) acc1[i] = 0.f;
    mbar_wait(sBar, 0);
    TS(TSK, 3);
    if (wg == 0) res_mainloop<NKB, NST, 0>(acc0, acc1, sbase, sBar, (tid & 127) == 0);
    else res_mainloop<NKB, NST, 1>(acc0, acc1, sbase, sBar, (tid & 127) == 0);
    wgmma_wait<0>();
    fence_regs(acc0); fence_regs(acc1);
    TS(TSK, 4);
#pragma unroll
    for (int j = 0; j < 10; j++) {
      float a[4];
#pragma unroll
      for (int e = 0; e < 4; e++) a[e] = bf16_round(j < 8 ? acc0[4 * j + e] : acc1[4 * (j - 8) + e]);
      const uint32_t o0 = pack_bf16(bf_lo(res[2 * j]) + a[0], bf_hi(res[2 * j]) + a[1]);
      const uint32_t o1 = pack_bf16(bf_lo(res[2 * j + 1]) + a[2], bf_hi(res[2 * j + 1]) + a[3]);
      *reinterpret_cast<uint32_t*>(out + (size_t)row0 * DM + n0 + j * 8 + c4 * 2) = o0;
      *reinterpret_cast<uint32_t*>(out + (size_t)(row0 + 8) * DM + n0 + j * 8 + c4 * 2) = o1;
    }
  }
  __syncwarp();
  TS(TSK, 5);
  cluster_sync_relaxed();
  TS(TSK, 6);
}

constexpr int AT_THREADS = 512;
constexpr int AT_WGS = AT_THREADS / 128;
#define AT_CHUNK_MASK 3
#define AT_STAGGER 0
constexpr int AT_KV_BYTES = IMG_HEAD_ELEMS * 2;
constexpr int AT_SMEM = 2 * AT_KV_BYTES + 256 + 1024;
constexpr int AT_CHUNKS = 8;

__device__ __forceinline__ float exp2_poly(float x) {
  const float u = __saturatef(fmaf(x, 1.0f / 64.0f, 62.0f / 64.0f));
  const float MAGIC = 12582912.0f - 62.0f;
  const float r = fmaf(u, 64.0f, MAGIC);
  const float q = MAGIC - r;
  const float fr = fmaf(u, 64.0f, q);
  float p = fmaf(fr, 0.009570102207362652f, 0.05591785907745361f);
  p = fmaf(p, fr, 0.240247443318367f);
  p = fmaf(p, fr, 0.6931217908859253f);
  p = fmaf(p, fr, 0.9999992847442627f);
  return __uint_as_float(__float_as_uint(p) + (__float_as_uint(r) << 23));
}
#define AT_VARIANT 0
__device__ __forceinline__ bool use_poly(int e) {
  return ((e & 7) == 1) || ((e & 7) == 4) || ((e & 7) == 6);
}

struct AttnState {
  uint32_t qa0, qa1, qa2, qa3, qa4, qa5;
  float M0, M1;
};

__device__ __forceinline__ bool attn_exp_fast(const float (&s)[32], uint32_t (&p)[16]) {
#pragma unroll
  for (int j = 0; j < 16; j++) {
    const float e0 = use_poly(2 * j) ? exp2_poly(s[2 * j]) : ex2(s[2 * j]);
    const float e1 = use_poly(2 * j + 1) ? exp2_poly(s[2 * j + 1]) : ex2(s[2 * j + 1]);
    p[j] = pack_bf16(e0, e1);
  }
  uint32_t acc_or = 0;
#pragma unroll
  for (int j = 0; j < 16; j++) acc_or |= p[j];
  return __any_sync(0xffffffffu, (acc_or & 0x40004000u) != 0);
}
__device__ __forceinline__ void attn_exp_exact(const float (&s)[32], uint32_t (&p)[16], float (&o)[12], AttnState& st, bool first, int c4) {
  float mx0 = fmaxf(s[0], s[1]), mx1 = fmaxf(s[2], s[3]);
#pragma unroll
  for (int j = 1; j < 8; j++) {
    mx0 = fmaxf(mx0, fmaxf(s[4 * j], s[4 * j + 1]));
    mx1 = fmaxf(mx1, fmaxf(s[4 * j + 2], s[4 * j + 3]));
  }
  mx0 = fmaxf(mx0, __shfl_xor_sync(0xffffffffu, mx0, 1));
  mx1 = fmaxf(mx1, __shfl_xor_sync(0xffffffffu, mx1, 1));
  mx0 = fmaxf(mx0, __shfl_xor_sync(0xffffffffu, mx0, 2));
  mx1 = fmaxf(mx1, __shfl_xor_sync(0xffffffffu, mx1, 2));
  float d0 = mx0 + 7.0f, d1 = mx1 + 7.0f;
  if (!first) { d0 = fmaxf(d0, 0.f); d1 = fmaxf(d1, 0.f); }
  const float T0 = st.M0 + d0, T1 = st.M1 + d1;
  const float h0 = bf16_round(T0), h1 = bf16_round(T1);
  const float i0 = bf16_round(T0 - h0), i1 = bf16_round(T1 - h1);
  const float l0 = bf16_round((T0 - h0) - i0), l1 = bf16_round((T1 - h1) - i1);
  const float N0 = (h0 + i0) + l0, N1 = (h1 + i1) + l1;
  d0 = N0 - st.M0; d1 = N1 - st.M1;
  st.M0 = N0; st.M1 = N1;
  if (c4 == 2) { st.qa4 = pack_bf16(-h0, -i0); st.qa5 = pack_bf16(-h1, -i1); }
  if (c4 == 3) { st.qa4 = pack_bf16(-l0, 0.f); st.qa5 = pack_bf16(-l1, 0.f); }
  if (!first) {
    const float al0 = ex2(-d0), al1 = ex2(-d1);
#pragma unroll
    for (int j = 0; j < 3; j++) {
      o[4 * j] *= al0; o[4 * j + 1] *= al0;
      o[4 * j + 2] *= al1; o[4 * j + 3] *= al1;
    }
  }
#pragma unroll
  for (int j = 0; j < 8; j++) {
    p[2 * j] = pack_bf16(ex2(s[4 * j] - d0), ex2(s[4 * j + 1] - d0));
    p[2 * j + 1] = pack_bf16(ex2(s[4 * j + 2] - d1), ex2(s[4 * j + 3] - d1));
  }
}
__device__ __forceinline__ void attn_step(float (&s)[32], const uint32_t (&pp)[16], uint32_t (&pn)[16], float (&o)[12], AttnState& st,
                                          uint64_t dk, uint64_t dv_prev, int keep, int c4) {
  wgmma_fence();
  wgmma_rs_n64(s, st.qa0, st.qa1, st.qa2, st.qa3, dk, 0);
  wgmma_rs_n64(s, st.qa4, st.qa5, 0u, 0u, dk + 16, 1);
  wgmma_commit();
#pragma unroll
  for (int kk = 0; kk < 4; kk++) wgmma_rs_n24_tb(o, pp[4 * kk], pp[4 * kk + 1], pp[4 * kk + 2], pp[4 * kk + 3], dv_prev + kk * 48, kk == 0 ? keep : 1);
  wgmma_commit();
  wgmma_wait<1>();
  fence_regs(s);
  const bool redo = attn_exp_fast(s, pn);
  wgmma_wait<0>();
  fence_regs(o);
  if (redo) attn_exp_exact(s, pn, o, st, false, c4);
}

__global__ void __launch_bounds__(AT_THREADS, 1) attn_kernel(const bf16* __restrict__ wo, const bf16* __restrict__ wgt, const bf16* __restrict__ wup, const bf16* __restrict__ wdn) {
  extern __shared__ uint8_t smem_raw[];
  const uint32_t sbase = (smem_u32(smem_raw) + 1023u) & ~1023u;
  const uint32_t sK = sbase, sV = sbase + AT_KV_BYTES;
  const uint32_t sBar = sV + AT_KV_BYTES;
  const int tid = threadIdx.x, warp = tid >> 5, lane = tid & 31;
  const int head = blockIdx.x >> 2, quarter = blockIdx.x & 3;
  TS(1, 0);
  if (tid == 0) {
    for (int i = 0; i < AT_CHUNKS; i++) mbar_init(sBar + 8 * i, 1);
    fence_mbar_init();
  }
  pdl_launch();
  if (tid == 32) {
    prefetch_l2(reinterpret_cast<const uint8_t*>(wo) + blockIdx.x * 6400, 6400);
    prefetch_l2(reinterpret_cast<const uint8_t*>(wgt) + blockIdx.x * 15360, 15360);
    prefetch_l2(reinterpret_cast<const uint8_t*>(wup) + blockIdx.x * 15360, 15360);
    prefetch_l2(reinterpret_cast<const uint8_t*>(wdn) + blockIdx.x * 15360, 15360);
  }
  __syncthreads();
  TS(1, 1);
  pdl_wait();
  TS(1, 2);
  if (tid == 0) {
    const uint8_t* kg = reinterpret_cast<const uint8_t*>(g_img + (size_t)(32 + head) * IMG_HEAD_ELEMS);
    const uint8_t* vg = reinterpret_cast<const uint8_t*>(g_img + (size_t)(64 + head) * IMG_HEAD_ELEMS);
    constexpr int CB = AT_KV_BYTES / AT_CHUNKS;
    for (int i = 0; i < AT_CHUNKS; i++) {
      mbar_expect_tx(sBar + 8 * i, 2 * CB);
      bulk_g2s(sK + i * CB, kg + i * CB, CB, sBar + 8 * i);
      bulk_g2s(sV + i * CB, vg + i * CB, CB, sBar + 8 * i);
    }
  }
  const int wg = warp >> 2, wwarp = warp & 3;
  const int g = lane >> 2, c4 = lane & 3;
  const uint64_t dk_base = make_desc(sK, 128, 384, 0);
  const uint64_t dv_base = make_desc(sV, 384, 128, 0);

#pragma unroll 1
  for (int rep = 0; rep * AT_WGS + wg < 8; rep++) {
    const int row0 = quarter * 512 + (rep * AT_WGS + wg) * 64 + wwarp * 16 + g;
    AttnState st;
    {
      const bf16* q0 = g_img + (size_t)head * IMG_HEAD_ELEMS + (size_t)(row0 >> 3) * 192 + g * 8 + c4 * 2;
      const bf16* q1 = q0 + 192;
      st.qa0 = *reinterpret_cast<const uint32_t*>(q0);
      st.qa1 = *reinterpret_cast<const uint32_t*>(q1);
      st.qa2 = *reinterpret_cast<const uint32_t*>(q0 + 64);
      st.qa3 = *reinterpret_cast<const uint32_t*>(q1 + 64);
      st.qa4 = *reinterpret_cast<const uint32_t*>(q0 + 128);
      st.qa5 = *reinterpret_cast<const uint32_t*>(q1 + 128);
    }
    float o[12];
    float s[32];
    uint32_t pa[16], pb[16];
    st.M0 = st.M1 = 0.f;
    if (rep == 0) mbar_wait(sBar, 0);
    wgmma_fence();
    wgmma_rs_n64(s, st.qa0, st.qa1, st.qa2, st.qa3, dk_base, 0);
    wgmma_rs_n64(s, st.qa4, st.qa5, 0u, 0u, dk_base + 16, 1);
    wgmma_commit();
    wgmma_wait<0>();
    fence_regs(s);
    attn_exp_exact(s, pa, o, st, true, c4);
    attn_step(s, pa, pb, o, st, dk_base + 192, dv_base, 0, c4);
#pragma unroll 1
    for (int tt = 1; tt < 16; tt++) {
      if (rep == 0 && !(tt & 1)) mbar_wait(sBar + 8 * (tt >> 1), 0);
      const uint64_t dk = dk_base + (uint64_t)(uint32_t)(tt * 384);
      const uint64_t dv = dv_base + (uint64_t)(uint32_t)(tt * 384);
      attn_step(s, pb, pa, o, st, dk, dv - 192, 1, c4);
      attn_step(s, pa, pb, o, st, dk + 192, dv, 1, c4);
    }
    wgmma_fence();
#pragma unroll
    for (int kk = 0; kk < 4; kk++) wgmma_rs_n24_tb(o, pb[4 * kk], pb[4 * kk + 1], pb[4 * kk + 2], pb[4 * kk + 3], dv_base + 31 * 192 + kk * 48, 1);
    wgmma_commit();
    wgmma_wait<0>();
    fence_regs(o);
    TS(1, 3 + rep);
    const float l0 = __shfl_sync(0xffffffffu, o[8], (lane & ~3) | 2);
    const float l1 = __shfl_sync(0xffffffffu, o[10], (lane & ~3) | 2);
    const float i0 = 1.0f / l0, i1 = 1.0f / l1;
    bf16* o0 = g_o + (size_t)row0 * DM + head * DH;
    bf16* o1 = o0 + 8 * DM;
#pragma unroll
    for (int j = 0; j < 3; j++) {
      if (j < 2 || c4 < 2) {
        *reinterpret_cast<uint32_t*>(o0 + j * 8 + c4 * 2) = pack_bf16(o[4 * j] * i0, o[4 * j + 1] * i0);
        *reinterpret_cast<uint32_t*>(o1 + j * 8 + c4 * 2) = pack_bf16(o[4 * j + 2] * i1, o[4 * j + 3] * i1);
      }
    }
  }
}

typedef CUresult (*EncodeTiledFn)(CUtensorMap*, CUtensorMapDataType, cuuint32_t, void*, const cuuint64_t*, const cuuint64_t*,
                                  const cuuint32_t*, const cuuint32_t*, CUtensorMapInterleave, CUtensorMapSwizzle,
                                  CUtensorMapL2promotion, CUtensorMapFloatOOBfill);

static void make_map(EncodeTiledFn fn, CUtensorMap* tm, const void* ptr, uint64_t rows, uint64_t cols, uint32_t box_rows,
                     uint32_t box_cols, CUtensorMapSwizzle sw) {
  cuuint64_t dims[2] = {cols, rows};
  cuuint64_t strides[1] = {cols * 2};
  cuuint32_t box[2] = {box_cols, box_rows};
  cuuint32_t es[2] = {1, 1};
  fn(tm, CU_TENSOR_MAP_DATA_TYPE_BFLOAT16, 2, const_cast<void*>(ptr), dims, strides, box, es, CU_TENSOR_MAP_INTERLEAVE_NONE, sw,
     CU_TENSOR_MAP_L2_PROMOTION_L2_256B, CU_TENSOR_MAP_FLOAT_OOB_FILL_NONE);
}

template <typename... KArgs, typename... Args>
static void launch(void (*kern)(KArgs...), int grid, int block, int smem, int cluster, bool pdl, Args... args) {
  cudaLaunchConfig_t cfg = {};
  cfg.gridDim = dim3(grid);
  cfg.blockDim = dim3(block);
  cfg.dynamicSmemBytes = smem;
  cfg.stream = cudaStreamPerThread;
  cudaLaunchAttribute at[2];
  int n = 0;
  if (cluster > 1) {
    at[n].id = cudaLaunchAttributeClusterDimension;
    at[n].val.clusterDim.x = cluster; at[n].val.clusterDim.y = 1; at[n].val.clusterDim.z = 1;
    n++;
  }
  if (pdl) {
    at[n].id = cudaLaunchAttributeProgrammaticStreamSerialization;
    at[n].val.programmaticStreamSerializationAllowed = 1;
    n++;
  }
  cfg.attrs = at;
  cfg.numAttrs = n;
  cudaLaunchKernelEx(&cfg, kern, KArgs(args)...);
}

extern "C" void kernel_launch(void* const* d_in, const int* in_sizes, int n_in, void* d_out, int out_size) {
  const bf16* x = (const bf16*)d_in[0];
  const bf16* wqkv = (const bf16*)d_in[1];
  const bf16* wo = (const bf16*)d_in[2];
  const bf16* wg = (const bf16*)d_in[4];
  const bf16* wu = (const bf16*)d_in[5];
  const bf16* wd = (const bf16*)d_in[6];
  bf16* out = (bf16*)d_out;

  static EncodeTiledFn enc = nullptr;
  static void *p_o = nullptr, *p_h = nullptr, *p_hh = nullptr, *p_xn = nullptr;
  if (!enc) {
    void* fn = nullptr;
    cudaDriverEntryPointQueryResult qr;
    cudaGetDriverEntryPoint("cuTensorMapEncodeTiled", &fn, cudaEnableDefault, &qr);
    enc = (EncodeTiledFn)fn;
    cudaGetSymbolAddress(&p_o, g_o);
    cudaGetSymbolAddress(&p_h, g_h);
    cudaGetSymbolAddress(&p_hh, g_hh);
    cudaGetSymbolAddress(&p_xn, g_xn);
    cudaFuncSetAttribute(big_gemm_kernel<0>, cudaFuncAttributeMaxDynamicSharedMemorySize, LGCfg<0>::SMEM);
    cudaFuncSetAttribute(big_gemm_kernel<1>, cudaFuncAttributeMaxDynamicSharedMemorySize, LGCfg<1>::SMEM);
    cudaFuncSetAttribute(res_gemm_kernel<DM>, cudaFuncAttributeMaxDynamicSharedMemorySize, RG_SMEM);
    cudaFuncSetAttribute(res_gemm_kernel<FF>, cudaFuncAttributeMaxDynamicSharedMemorySize, RG_SMEM);
    cudaFuncSetAttribute(attn_kernel, cudaFuncAttributeMaxDynamicSharedMemorySize, AT_SMEM);
  }
  CUtensorMap tm_wqkv, tm_wg, tm_wu, tm_wo64, tm_wo16, tm_wd64, tm_wd16, tm_o, tm_hh, tm_xn;
  make_map(enc, &tm_wqkv, wqkv, DM, 3 * DM, 32, 64, CU_TENSOR_MAP_SWIZZLE_128B);
  make_map(enc, &tm_wg, wg, DM, FF, 32, 64, CU_TENSOR_MAP_SWIZZLE_128B);
  make_map(enc, &tm_wu, wu, DM, FF, 32, 64, CU_TENSOR_MAP_SWIZZLE_128B);
  make_map(enc, &tm_wo64, wo, DM, DM, 64, 64, CU_TENSOR_MAP_SWIZZLE_128B);
  make_map(enc, &tm_wo16, wo, DM, DM, 64, 16, CU_TENSOR_MAP_SWIZZLE_32B);
  make_map(enc, &tm_wd64, wd, FF, DM, 64, 64, CU_TENSOR_MAP_SWIZZLE_128B);
  make_map(enc, &tm_wd16, wd, FF, DM, 64, 16, CU_TENSOR_MAP_SWIZZLE_32B);
  make_map(enc, &tm_o, p_o, SEQ, DM, 64, 64, CU_TENSOR_MAP_SWIZZLE_128B);
  make_map(enc, &tm_hh, p_hh, SEQ, FF, 64, 64, CU_TENSOR_MAP_SWIZZLE_128B);
  make_map(enc, &tm_xn, p_xn, SEQ, DM, 128, 32, CU_TENSOR_MAP_SWIZZLE_64B);

  launch(ln_kernel, 128, 256, 0, 1, false, x, (bf16*)p_xn, 0);
  launch(big_gemm_kernel<0>, 128, LG_THREADS, LGCfg<0>::SMEM, 2, true, tm_xn, tm_wqkv, tm_wqkv, tm_wqkv);
  launch(attn_kernel, 128, AT_THREADS, AT_SMEM, 1, true, wo, wg, wu, wd);
  launch(res_gemm_kernel<DM>, 128, RG_THREADS, RG_SMEM, 2, true, tm_o, tm_wo64, tm_wo16, x, (bf16*)p_h);
  launch(ln_kernel, 128, 256, 0, 1, true, (const bf16*)p_h, (bf16*)p_xn, 1);
  launch(big_gemm_kernel<1>, 128, LG_THREADS, LGCfg<1>::SMEM, 2, true, tm_xn, tm_wg, tm_wu, tm_hh);
  launch(res_gemm_kernel<FF>, 128, RG_THREADS, RG_SMEM, 2, true, tm_hh, tm_wd64, tm_wd16, (const bf16*)p_h, out);
}
```

```cpp
#include <cuda_runtime.h>
#include <cuda_bf16.h>
#include <cuda.h>
#include <stdint.h>

typedef __nv_bfloat16 bf16;

constexpr int SEQ = 2048, DM = 640, NH = 32, DH = 20, FF = 1536;
constexpr float ATT_SCALE_LOG2E = 0.22360679774997896f * 1.4426950408889634f;
constexpr int IMG_HEAD_ELEMS = (SEQ / 8) * 192;

__device__ __align__(1024) bf16 g_img[3 * NH * IMG_HEAD_ELEMS];
__device__ __align__(1024) bf16 g_o[SEQ * DM];
__device__ __align__(1024) bf16 g_h[SEQ * DM];
__device__ __align__(1024) bf16 g_xn[SEQ * DM];
__device__ float2 g_stats[SEQ * 8];
__device__ float g_cs[2 * FF];
__device__ int g_flag[3 * 16];
__device__ __align__(1024) bf16 g_hh[SEQ * FF];

#define TS(k, i)
#define PH(w, t, i)
__device__ __forceinline__ uint32_t smem_u32(const void* p) { return (uint32_t)__cvta_generic_to_shared(p); }
__device__ __forceinline__ void mbar_init(uint32_t bar, uint32_t cnt) {
  asm volatile("mbarrier.init.shared::cta.b64 [%0], %1;" ::"r"(bar), "r"(cnt) : "memory");
}
__device__ __forceinline__ void mbar_expect_tx(uint32_t bar, uint32_t bytes) {
  asm volatile("mbarrier.arrive.expect_tx.shared::cta.b64 _, [%0], %1;" ::"r"(bar), "r"(bytes) : "memory");
}
__device__ __forceinline__ void mbar_arrive(uint32_t bar) {
  asm volatile("mbarrier.arrive.shared::cta.b64 _, [%0];" ::"r"(bar) : "memory");
}
__device__ __forceinline__ void mbar_arrive_cluster(uint32_t bar, uint32_t cta) {
  asm volatile(
      "{\n.reg .b32 r;\nmapa.shared::cluster.u32 r, %0, %1;\n"
      "mbarrier.arrive.shared::cluster.b64 _, [r];\n}\n" ::"r"(bar), "r"(cta)
      : "memory");
}
__device__ __forceinline__ void mbar_wait(uint32_t bar, uint32_t parity) {
  asm volatile(
      "{\n.reg .pred p;\nLAB_WAIT:\n"
      "mbarrier.try_wait.parity.shared::cta.b64 p, [%0], %1;\n"
      "@p bra DONE;\nbra LAB_WAIT;\nDONE:\n}\n" ::"r"(bar), "r"(parity)
      : "memory");
}
__device__ __forceinline__ void mbar_wait_cluster(uint32_t bar, uint32_t parity) {
  asm volatile(
      "{\n.reg .pred p;\nLAB_WAIT:\n"
      "mbarrier.try_wait.parity.acquire.cluster.shared::cta.b64 p, [%0], %1;\n"
      "@p bra DONE;\nbra LAB_WAIT;\nDONE:\n}\n" ::"r"(bar), "r"(parity)
      : "memory");
}
__device__ __forceinline__ void fence_mbar_init() { asm volatile("fence.mbarrier_init.release.cluster;" ::: "memory"); }
__device__ __forceinline__ void fence_proxy_async() { asm volatile("fence.proxy.async.shared::cta;" ::: "memory"); }
__device__ __forceinline__ void cluster_sync_all() {
  asm volatile("barrier.cluster.arrive.release.aligned;\nbarrier.cluster.wait.acquire.aligned;" ::: "memory");
}
__device__ __forceinline__ void cluster_sync_relaxed() {
  asm volatile("barrier.cluster.arrive.relaxed.aligned;\nbarrier.cluster.wait.aligned;" ::: "memory");
}
__device__ __forceinline__ void named_bar_sync(int id, int n) { asm volatile("bar.sync %0, %1;" ::"r"(id), "r"(n) : "memory"); }
__device__ __forceinline__ bool wg_any(bool pred, int id) {
  uint32_t r;
  asm volatile("{\n.reg .pred p, q;\nsetp.ne.u32 p, %1, 0;\nbar.red.or.pred q, %2, 128, p;\nselp.u32 %0, 1, 0, q;\n}\n" : "=r"(r) : "r"((uint32_t)pred), "r"(id) : "memory");
  return r != 0;
}
__device__ __forceinline__ void fence_proxy_async_all() { asm volatile("fence.proxy.async;" ::: "memory"); }
__device__ __forceinline__ void flag_signal(int* f) {
  __threadfence();
  atomicAdd(f, 1);
}
__device__ __forceinline__ void flag_wait(const int* f, int target) {
  int v;
  unsigned spins = 0;
  do {
    asm volatile("ld.acquire.gpu.global.s32 %0, [%1];" : "=r"(v) : "l"(f) : "memory");
    if (++spins > (1u << 24)) __trap();
  } while (v < target);
}
__device__ __forceinline__ void pdl_launch() { asm volatile("griddepcontrol.launch_dependents;" ::: "memory"); }
__device__ __forceinline__ void pdl_wait() { asm volatile("griddepcontrol.wait;" ::: "memory"); }

__device__ __forceinline__ void tma_load_2d(uint32_t dst, const CUtensorMap* tm, int c0, int c1, uint32_t bar) {
  asm volatile(
      "cp.async.bulk.tensor.2d.shared::cluster.global.mbarrier::complete_tx::bytes [%0], [%1, {%3, %4}], [%2];" ::"r"(dst),
      "l"((uint64_t)tm), "r"(bar), "r"(c0), "r"(c1)
      : "memory");
}
__device__ __forceinline__ void tma_load_2d_mc(uint32_t dst, const CUtensorMap* tm, int c0, int c1, uint32_t bar, uint16_t mask) {
  asm volatile(
      "cp.async.bulk.tensor.2d.shared::cluster.global.mbarrier::complete_tx::bytes.multicast::cluster [%0], [%1, {%3, %4}], [%2], %5;" ::"r"(dst),
      "l"((uint64_t)tm), "r"(bar), "r"(c0), "r"(c1), "h"(mask)
      : "memory");
}
__device__ __forceinline__ void bulk_g2s(uint32_t dst, const void* src, uint32_t bytes, uint32_t bar) {
  asm volatile("cp.async.bulk.shared::cluster.global.mbarrier::complete_tx::bytes [%0], [%1], %2, [%3];" ::"r"(dst), "l"(src),
               "r"(bytes), "r"(bar)
               : "memory");
}
__device__ __forceinline__ void bulk_s2g(void* dst, uint32_t src, uint32_t bytes) {
  asm volatile("cp.async.bulk.global.shared::cta.bulk_group [%0], [%1], %2;" ::"l"(dst), "r"(src), "r"(bytes) : "memory");
}
__device__ __forceinline__ void tma_store_2d(const CUtensorMap* tm, uint32_t src, int c0, int c1) {
  asm volatile("cp.async.bulk.tensor.2d.global.shared::cta.bulk_group [%0, {%2, %3}], [%1];" ::"l"((uint64_t)tm), "r"(src), "r"(c0), "r"(c1) : "memory");
}
__device__ __forceinline__ void bulk_commit() { asm volatile("cp.async.bulk.commit_group;" ::: "memory"); }
__device__ __forceinline__ void bulk_wait_read() { asm volatile("cp.async.bulk.wait_group.read 0;" ::: "memory"); }
__device__ __forceinline__ void prefetch_l2(const void* p, uint32_t bytes) {
  asm volatile("cp.async.bulk.prefetch.L2.global [%0], %1;" ::"l"(p), "r"(bytes) : "memory");
}
__device__ __forceinline__ void bulk_wait_all() { asm volatile("cp.async.bulk.wait_group 0;" ::: "memory"); }
__device__ __forceinline__ void st_shared_b32(uint32_t addr, uint32_t v) { asm volatile("st.shared.b32 [%0], %1;" ::"r"(addr), "r"(v) : "memory"); }
__device__ __forceinline__ void st_shared_v2(uint32_t addr, uint32_t a, uint32_t b) { asm volatile("st.shared.v2.b32 [%0], {%1, %2};" ::"r"(addr), "r"(a), "r"(b) : "memory"); }
__device__ __forceinline__ void prefetch_tmap(const CUtensorMap* tm) {
  asm volatile("prefetch.tensormap [%0];" ::"l"((uint64_t)tm) : "memory");
}
__device__ __forceinline__ void wgmma_fence() { asm volatile("wgmma.fence.sync.aligned;" ::: "memory"); }
__device__ __forceinline__ void wgmma_commit() { asm volatile("wgmma.commit_group.sync.aligned;" ::: "memory"); }
template <int N>
__device__ __forceinline__ void wgmma_wait() { asm volatile("wgmma.wait_group.sync.aligned %0;" ::"n"(N) : "memory"); }

template <int N>
__device__ __forceinline__ void fence_regs(float (&r)[N]) {
#pragma unroll
  for (int i = 0; i < N; i++) asm volatile("" : "+f"(r[i])::"memory");
}
template <int N>
__device__ __forceinline__ void fence_regs(uint32_t (&r)[N]) {
#pragma unroll
  for (int i = 0; i < N; i++) asm volatile("" : "+r"(r[i])::"memory");
}
__device__ __forceinline__ uint64_t make_desc(uint32_t addr, uint32_t lbo, uint32_t sbo, uint32_t layout) {
  return (uint64_t)((addr & 0x3FFFF) >> 4) | ((uint64_t)((lbo & 0x3FFFF) >> 4) << 16) | ((uint64_t)((sbo & 0x3FFFF) >> 4) << 32) |
         ((uint64_t)layout << 62);
}
__device__ __forceinline__ uint32_t pack_bf16(float lo, float hi) {
  uint32_t r;
  asm("cvt.rn.bf16x2.f32 %0, %1, %2;" : "=r"(r) : "f"(hi), "f"(lo));
  return r;
}
__device__ __forceinline__ float bf16_round(float x) { return __bfloat162float(__float2bfloat16_rn(x)); }
__device__ __forceinline__ float bf_lo(uint32_t u) { return __uint_as_float(u << 16); }
__device__ __forceinline__ float bf_hi(uint32_t u) { return __uint_as_float(u & 0xffff0000u); }
__device__ __forceinline__ float ex2(float x) {
  float y;
  asm("ex2.approx.ftz.f32 %0, %1;" : "=f"(y) : "f"(x));
  return y;
}

__device__ __forceinline__ void wgmma_ss_n240_tb(float (&d)[120], uint64_t descA, uint64_t descB, int scaleD) {
  asm volatile("{\n.reg .pred p;\nsetp.ne.b32 p, %122, 0;\n"
    "wgmma.mma_async.sync.aligned.m64n240k16.f32.bf16.bf16 {%0, %1, %2, %3, %4, %5, %6, %7, %8, %9, %10, %11, %12, %13, %14, %15, %16, %17, %18, %19, %20, %21, %22, %23, %24, %25, %26, %27, %28, %29, %30, %31, %32, %33, %34, %35, %36, %37, %38, %39, %40, %41, %42, %43, %44, %45, %46, %47, %48, %49, %50, %51, %52, %53, %54, %55, %56, %57, %58, %59, %60, %61, %62, %63, %64, %65, %66, %67, %68, %69, %70, %71, %72, %73, %74, %75, %76, %77, %78, %79, %80, %81, %82, %83, %84, %85, %86, %87, %88, %89, %90, %91, %92, %93, %94, %95, %96, %97, %98, %99, %100, %101, %102, %103, %104, %105, %106, %107, %108, %109, %110, %111, %112, %113, %114, %115, %116, %117, %118, %119}, %120, %121, p, 1, 1, 0, 1;\n}\n"
    : "+f"(d[0]), "+f"(d[1]), "+f"(d[2]), "+f"(d[3]), "+f"(d[4]), "+f"(d[5]), "+f"(d[6]), "+f"(d[7]), "+f"(d[8]), "+f"(d[9]), "+f"(d[10]), "+f"(d[11]), "+f"(d[12]), "+f"(d[13]), "+f"(d[14]), "+f"(d[15]), "+f"(d[16]), "+f"(d[17]), "+f"(d[18]), "+f"(d[19]), "+f"(d[20]), "+f"(d[21]), "+f"(d[22]), "+f"(d[23]), "+f"(d[24]), "+f"(d[25]), "+f"(d[26]), "+f"(d[27]), "+f"(d[28]), "+f"(d[29]), "+f"(d[30]), "+f"(d[31]), "+f"(d[32]), "+f"(d[33]), "+f"(d[34]), "+f"(d[35]), "+f"(d[36]), "+f"(d[37]), "+f"(d[38]), "+f"(d[39]), "+f"(d[40]), "+f"(d[41]), "+f"(d[42]), "+f"(d[43]), "+f"(d[44]), "+f"(d[45]), "+f"(d[46]), "+f"(d[47]), "+f"(d[48]), "+f"(d[49]), "+f"(d[50]), "+f"(d[51]), "+f"(d[52]), "+f"(d[53]), "+f"(d[54]), "+f"(d[55]), "+f"(d[56]), "+f"(d[57]), "+f"(d[58]), "+f"(d[59]), "+f"(d[60]), "+f"(d[61]), "+f"(d[62]), "+f"(d[63]), "+f"(d[64]), "+f"(d[65]), "+f"(d[66]), "+f"(d[67]), "+f"(d[68]), "+f"(d[69]), "+f"(d[70]), "+f"(d[71]), "+f"(d[72]), "+f"(d[73]), "+f"(d[74]), "+f"(d[75]), "+f"(d[76]), "+f"(d[77]), "+f"(d[78]), "+f"(d[79]), "+f"(d[80]), "+f"(d[81]), "+f"(d[82]), "+f"(d[83]), "+f"(d[84]), "+f"(d[85]), "+f"(d[86]), "+f"(d[87]), "+f"(d[88]), "+f"(d[89]), "+f"(d[90]), "+f"(d[91]), "+f"(d[92]), "+f"(d[93]), "+f"(d[94]), "+f"(d[95]), "+f"(d[96]), "+f"(d[97]), "+f"(d[98]), "+f"(d[99]), "+f"(d[100]), "+f"(d[101]), "+f"(d[102]), "+f"(d[103]), "+f"(d[104]), "+f"(d[105]), "+f"(d[106]), "+f"(d[107]), "+f"(d[108]), "+f"(d[109]), "+f"(d[110]), "+f"(d[111]), "+f"(d[112]), "+f"(d[113]), "+f"(d[114]), "+f"(d[115]), "+f"(d[116]), "+f"(d[117]), "+f"(d[118]), "+f"(d[119])
    : "l"(descA), "l"(descB), "r"(scaleD));
}
__device__ __forceinline__ void wgmma_ss_n192_tb(float (&d)[96], uint64_t descA, uint64_t descB, int scaleD) {
  asm volatile("{\n.reg .pred p;\nsetp.ne.b32 p, %98, 0;\n"
    "wgmma.mma_async.sync.aligned.m64n192k16.f32.bf16.bf16 {%0, %1, %2, %3, %4, %5, %6, %7, %8, %9, %10, %11, %12, %13, %14, %15, %16, %17, %18, %19, %20, %21, %22, %23, %24, %25, %26, %27, %28, %29, %30, %31, %32, %33, %34, %35, %36, %37, %38, %39, %40, %41, %42, %43, %44, %45, %46, %47, %48, %49, %50, %51, %52, %53, %54, %55, %56, %57, %58, %59, %60, %61, %62, %63, %64, %65, %66, %67, %68, %69, %70, %71, %72, %73, %74, %75, %76, %77, %78, %79, %80, %81, %82, %83, %84, %85, %86, %87, %88, %89, %90, %91, %92, %93, %94, %95}, %96, %97, p, 1, 1, 0, 1;\n}\n"
    : "+f"(d[0]), "+f"(d[1]), "+f"(d[2]), "+f"(d[3]), "+f"(d[4]), "+f"(d[5]), "+f"(d[6]), "+f"(d[7]), "+f"(d[8]), "+f"(d[9]), "+f"(d[10]), "+f"(d[11]), "+f"(d[12]), "+f"(d[13]), "+f"(d[14]), "+f"(d[15]), "+f"(d[16]), "+f"(d[17]), "+f"(d[18]), "+f"(d[19]), "+f"(d[20]), "+f"(d[21]), "+f"(d[22]), "+f"(d[23]), "+f"(d[24]), "+f"(d[25]), "+f"(d[26]), "+f"(d[27]), "+f"(d[28]), "+f"(d[29]), "+f"(d[30]), "+f"(d[31]), "+f"(d[32]), "+f"(d[33]), "+f"(d[34]), "+f"(d[35]), "+f"(d[36]), "+f"(d[37]), "+f"(d[38]), "+f"(d[39]), "+f"(d[40]), "+f"(d[41]), "+f"(d[42]), "+f"(d[43]), "+f"(d[44]), "+f"(d[45]), "+f"(d[46]), "+f"(d[47]), "+f"(d[48]), "+f"(d[49]), "+f"(d[50]), "+f"(d[51]), "+f"(d[52]), "+f"(d[53]), "+f"(d[54]), "+f"(d[55]), "+f"(d[56]), "+f"(d[57]), "+f"(d[58]), "+f"(d[59]), "+f"(d[60]), "+f"(d[61]), "+f"(d[62]), "+f"(d[63]), "+f"(d[64]), "+f"(d[65]), "+f"(d[66]), "+f"(d[67]), "+f"(d[68]), "+f"(d[69]), "+f"(d[70]), "+f"(d[71]), "+f"(d[72]), "+f"(d[73]), "+f"(d[74]), "+f"(d[75]), "+f"(d[76]), "+f"(d[77]), "+f"(d[78]), "+f"(d[79]), "+f"(d[80]), "+f"(d[81]), "+f"(d[82]), "+f"(d[83]), "+f"(d[84]), "+f"(d[85]), "+f"(d[86]), "+f"(d[87]), "+f"(d[88]), "+f"(d[89]), "+f"(d[90]), "+f"(d[91]), "+f"(d[92]), "+f"(d[93]), "+f"(d[94]), "+f"(d[95])
    : "l"(descA), "l"(descB), "r"(scaleD));
}
__device__ __forceinline__ void wgmma_ss_n64_tb(float (&d)[32], uint64_t descA, uint64_t descB, int scaleD) {
  asm volatile("{\n.reg .pred p;\nsetp.ne.b32 p, %34, 0;\n"
    "wgmma.mma_async.sync.aligned.m64n64k16.f32.bf16.bf16 {%0, %1, %2, %3, %4, %5, %6, %7, %8, %9, %10, %11, %12, %13, %14, %15, %16, %17, %18, %19, %20, %21, %22, %23, %24, %25, %26, %27, %28, %29, %30, %31}, %32, %33, p, 1, 1, 0, 1;\n}\n"
    : "+f"(d[0]), "+f"(d[1]), "+f"(d[2]), "+f"(d[3]), "+f"(d[4]), "+f"(d[5]), "+f"(d[6]), "+f"(d[7]), "+f"(d[8]), "+f"(d[9]), "+f"(d[10]), "+f"(d[11]), "+f"(d[12]), "+f"(d[13]), "+f"(d[14]), "+f"(d[15]), "+f"(d[16]), "+f"(d[17]), "+f"(d[18]), "+f"(d[19]), "+f"(d[20]), "+f"(d[21]), "+f"(d[22]), "+f"(d[23]), "+f"(d[24]), "+f"(d[25]), "+f"(d[26]), "+f"(d[27]), "+f"(d[28]), "+f"(d[29]), "+f"(d[30]), "+f"(d[31])
    : "l"(descA), "l"(descB), "r"(scaleD));
}
__device__ __forceinline__ void wgmma_ss_n16_tb(float (&d)[8], uint64_t descA, uint64_t descB, int scaleD) {
  asm volatile("{\n.reg .pred p;\nsetp.ne.b32 p, %10, 0;\n"
    "wgmma.mma_async.sync.aligned.m64n16k16.f32.bf16.bf16 {%0, %1, %2, %3, %4, %5, %6, %7}, %8, %9, p, 1, 1, 0, 1;\n}\n"
    : "+f"(d[0]), "+f"(d[1]), "+f"(d[2]), "+f"(d[3]), "+f"(d[4]), "+f"(d[5]), "+f"(d[6]), "+f"(d[7])
    : "l"(descA), "l"(descB), "r"(scaleD));
}
__device__ __forceinline__ void wgmma_rs_n128(float (&d)[64], uint32_t a0, uint32_t a1, uint32_t a2, uint32_t a3, uint64_t descB, int scaleD) {
  asm volatile("{\n.reg .pred p;\nsetp.ne.b32 p, %69, 0;\n"
    "wgmma.mma_async.sync.aligned.m64n128k16.f32.bf16.bf16 {%0, %1, %2, %3, %4, %5, %6, %7, %8, %9, %10, %11, %12, %13, %14, %15, %16, %17, %18, %19, %20, %21, %22, %23, %24, %25, %26, %27, %28, %29, %30, %31, %32, %33, %34, %35, %36, %37, %38, %39, %40, %41, %42, %43, %44, %45, %46, %47, %48, %49, %50, %51, %52, %53, %54, %55, %56, %57, %58, %59, %60, %61, %62, %63}, {%64, %65, %66, %67}, %68, p, 1, 1, 0;\n}\n"
    : "+f"(d[0]), "+f"(d[1]), "+f"(d[2]), "+f"(d[3]), "+f"(d[4]), "+f"(d[5]), "+f"(d[6]), "+f"(d[7]), "+f"(d[8]), "+f"(d[9]), "+f"(d[10]), "+f"(d[11]), "+f"(d[12]), "+f"(d[13]), "+f"(d[14]), "+f"(d[15]), "+f"(d[16]), "+f"(d[17]), "+f"(d[18]), "+f"(d[19]), "+f"(d[20]), "+f"(d[21]), "+f"(d[22]), "+f"(d[23]), "+f"(d[24]), "+f"(d[25]), "+f"(d[26]), "+f"(d[27]), "+f"(d[28]), "+f"(d[29]), "+f"(d[30]), "+f"(d[31]), "+f"(d[32]), "+f"(d[33]), "+f"(d[34]), "+f"(d[35]), "+f"(d[36]), "+f"(d[37]), "+f"(d[38]), "+f"(d[39]), "+f"(d[40]), "+f"(d[41]), "+f"(d[42]), "+f"(d[43]), "+f"(d[44]), "+f"(d[45]), "+f"(d[46]), "+f"(d[47]), "+f"(d[48]), "+f"(d[49]), "+f"(d[50]), "+f"(d[51]), "+f"(d[52]), "+f"(d[53]), "+f"(d[54]), "+f"(d[55]), "+f"(d[56]), "+f"(d[57]), "+f"(d[58]), "+f"(d[59]), "+f"(d[60]), "+f"(d[61]), "+f"(d[62]), "+f"(d[63])
    : "r"(a0), "r"(a1), "r"(a2), "r"(a3), "l"(descB), "r"(scaleD));
}
__device__ __forceinline__ void wgmma_rs_n64(float (&d)[32], uint32_t a0, uint32_t a1, uint32_t a2, uint32_t a3, uint64_t descB, int scaleD) {
  asm volatile("{\n.reg .pred p;\nsetp.ne.b32 p, %37, 0;\n"
    "wgmma.mma_async.sync.aligned.m64n64k16.f32.bf16.bf16 {%0, %1, %2, %3, %4, %5, %6, %7, %8, %9, %10, %11, %12, %13, %14, %15, %16, %17, %18, %19, %20, %21, %22, %23, %24, %25, %26, %27, %28, %29, %30, %31}, {%32, %33, %34, %35}, %36, p, 1, 1, 0;\n}\n"
    : "+f"(d[0]), "+f"(d[1]), "+f"(d[2]), "+f"(d[3]), "+f"(d[4]), "+f"(d[5]), "+f"(d[6]), "+f"(d[7]), "+f"(d[8]), "+f"(d[9]), "+f"(d[10]), "+f"(d[11]), "+f"(d[12]), "+f"(d[13]), "+f"(d[14]), "+f"(d[15]), "+f"(d[16]), "+f"(d[17]), "+f"(d[18]), "+f"(d[19]), "+f"(d[20]), "+f"(d[21]), "+f"(d[22]), "+f"(d[23]), "+f"(d[24]), "+f"(d[25]), "+f"(d[26]), "+f"(d[27]), "+f"(d[28]), "+f"(d[29]), "+f"(d[30]), "+f"(d[31])
    : "r"(a0), "r"(a1), "r"(a2), "r"(a3), "l"(descB), "r"(scaleD));
}
__device__ __forceinline__ void wgmma_rs_n24_tb(float (&d)[12], uint32_t a0, uint32_t a1, uint32_t a2, uint32_t a3, uint64_t descB, int scaleD) {
  asm volatile("{\n.reg .pred p;\nsetp.ne.b32 p, %17, 0;\n"
    "wgmma.mma_async.sync.aligned.m64n24k16.f32.bf16.bf16 {%0, %1, %2, %3, %4, %5, %6, %7, %8, %9, %10, %11}, {%12, %13, %14, %15}, %16, p, 1, 1, 1;\n}\n"
    : "+f"(d[0]), "+f"(d[1]), "+f"(d[2]), "+f"(d[3]), "+f"(d[4]), "+f"(d[5]), "+f"(d[6]), "+f"(d[7]), "+f"(d[8]), "+f"(d[9]), "+f"(d[10]), "+f"(d[11])
    : "r"(a0), "r"(a1), "r"(a2), "r"(a3), "l"(descB), "r"(scaleD));
}

constexpr int GT = 384;

__device__ __forceinline__ void release_stage(uint32_t bar, bool leader) {
  if (leader) {
    mbar_arrive_cluster(bar, 0);
    mbar_arrive_cluster(bar, 1);
  }
}

__device__ __forceinline__ void ln_row(const bf16* __restrict__ xin, bf16* __restrict__ xout, int l16) {
  const uint4* src = reinterpret_cast<const uint4*>(xin);
  uint4 v[5];
#pragma unroll
  for (int j = 0; j < 5; j++) v[j] = __ldg(src + j * 16 + l16);
  float s0 = 0.f, s1 = 0.f, s2 = 0.f, s3 = 0.f;
#pragma unroll
  for (int j = 0; j < 5; j++) {
    s0 += bf_lo(v[j].x) + bf_hi(v[j].x);
    s1 += bf_lo(v[j].y) + bf_hi(v[j].y);
    s2 += bf_lo(v[j].z) + bf_hi(v[j].z);
    s3 += bf_lo(v[j].w) + bf_hi(v[j].w);
  }
  float mean = (s0 + s1) + (s2 + s3);
#pragma unroll
  for (int o = 1; o < 16; o <<= 1) mean += __shfl_xor_sync(0xffffffffu, mean, o);
  mean *= (1.0f / DM);
  s0 = s1 = s2 = s3 = 0.f;
#pragma unroll
  for (int j = 0; j < 5; j++) {
    float d;
    d = bf_lo(v[j].x) - mean; s0 = fmaf(d, d, s0);
    d = bf_hi(v[j].x) - mean; s1 = fmaf(d, d, s1);
    d = bf_lo(v[j].y) - mean; s2 = fmaf(d, d, s2);
    d = bf_hi(v[j].y) - mean; s3 = fmaf(d, d, s3);
    d = bf_lo(v[j].z) - mean; s0 = fmaf(d, d, s0);
    d = bf_hi(v[j].z) - mean; s1 = fmaf(d, d, s1);
    d = bf_lo(v[j].w) - mean; s2 = fmaf(d, d, s2);
    d = bf_hi(v[j].w) - mean; s3 = fmaf(d, d, s3);
  }
  float sq = (s0 + s1) + (s2 + s3);
#pragma unroll
  for (int o = 1; o < 16; o <<= 1) sq += __shfl_xor_sync(0xffffffffu, sq, o);
  const float var_b = bf16_round(sq * (1.0f / DM));
  const float den = bf16_round(sqrtf(bf16_round(var_b + 1e-5f)));
  const float iv = __frcp_rn(den);
  const float mb = bf16_round(mean);
  uint4* dst = reinterpret_cast<uint4*>(xout);
#pragma unroll
  for (int j = 0; j < 5; j++) {
    uint4 w;
    uint32_t t;
    t = pack_bf16(bf_lo(v[j].x) - mb, bf_hi(v[j].x) - mb); w.x = pack_bf16(bf_lo(t) * iv, bf_hi(t) * iv);
    t = pack_bf16(bf_lo(v[j].y) - mb, bf_hi(v[j].y) - mb); w.y = pack_bf16(bf_lo(t) * iv, bf_hi(t) * iv);
    t = pack_bf16(bf_lo(v[j].z) - mb, bf_hi(v[j].z) - mb); w.z = pack_bf16(bf_lo(t) * iv, bf_hi(t) * iv);
    t = pack_bf16(bf_lo(v[j].w) - mb, bf_hi(v[j].w) - mb); w.w = pack_bf16(bf_lo(t) * iv, bf_hi(t) * iv);
    dst[j * 16 + l16] = w;
  }
}

constexpr int LG_STAGES = 5;
constexpr int QKV_STAGE = 8192 + 4 * 4096;
constexpr int GLU_STAGE = 8192 + 6 * 4096;

template <int WG>
__device__ __forceinline__ void qkv_mainloop(float (&acc)[120], uint32_t sbase, uint32_t sBar, bool leader) {
  constexpr int STAGE_BYTES = QKV_STAGE, NST = LG_STAGES;
  const uint64_t da_base = make_desc(sbase + WG * 4096, 16, 512, 2);
  const uint64_t db_base = make_desc(sbase + 8192, 4096, 1024, 1);
#pragma unroll 1
  for (int r = 0; r < 20 / NST; r++) {
#pragma unroll
    for (int s = 0; s < NST; s++) {
      mbar_wait(sBar + 8 * s, r & 1);
      wgmma_fence();
#pragma unroll
      for (int ks = 0; ks < 2; ks++)
        wgmma_ss_n240_tb(acc, da_base + (uint64_t)((s * STAGE_BYTES + ks * 32) >> 4), db_base + (uint64_t)((s * STAGE_BYTES + ks * 2048) >> 4), 1);
      wgmma_commit();
      wgmma_wait<1>();
      release_stage(sBar + 8 * (NST + (s + NST - 1) % NST), leader && (s > 0 || r > 0));
    }
  }
}
template <int WG>
__device__ __forceinline__ void glu_mainloop(float (&accg)[96], float (&accu)[96], uint32_t sbase, uint32_t sBar, bool leader) {
  constexpr int STAGE_BYTES = GLU_STAGE, NST = LG_STAGES;
  const uint64_t da_base = make_desc(sbase + WG * 4096, 16, 512, 2);
  const uint64_t db_base = make_desc(sbase + 8192, 4096, 1024, 1);
#pragma unroll 1
  for (int r = 0; r < 20 / NST; r++) {
#pragma unroll
    for (int s = 0; s < NST; s++) {
      mbar_wait(sBar + 8 * s, r & 1);
      wgmma_fence();
#pragma unroll
      for (int ks = 0; ks < 2; ks++) {
        const uint64_t da = da_base + (uint64_t)((s * STAGE_BYTES + ks * 32) >> 4);
        wgmma_ss_n192_tb(accg, da, db_base + (uint64_t)((s * STAGE_BYTES + ks * 2048) >> 4), 1);
        wgmma_ss_n192_tb(accu, da, db_base + (uint64_t)((s * STAGE_BYTES + 3 * 4096 + ks * 2048) >> 4), 1);
      }
      wgmma_commit();
      wgmma_wait<1>();
      release_stage(sBar + 8 * (NST + (s + NST - 1) % NST), leader && (s > 0 || r > 0));
    }
  }
}
constexpr int RG_STAGE_BYTES = 16384 + 8192 + 2048;
template <int NKB, int NST, int WG>
__device__ __forceinline__ void res_mainloop(float (&acc0)[32], float (&acc1)[8], uint32_t sbase, uint32_t sBar, bool leader) {
  const uint64_t da_base = make_desc(sbase + WG * 8192, 16, 1024, 1);
  const uint64_t db0_base = make_desc(sbase + 16384, 8192, 1024, 1);
  const uint64_t db1_base = make_desc(sbase + 16384 + 8192, 2048, 256, 3);
#pragma unroll 1
  for (int r = 0; r < NKB / NST; r++) {
#pragma unroll
    for (int s = 0; s < NST; s++) {
      const uint64_t so = (uint64_t)(s * (RG_STAGE_BYTES >> 4));
      mbar_wait(sBar + 8 * s, r & 1);
      wgmma_fence();
#pragma unroll
      for (int ks = 0; ks < 4; ks++) {
        wgmma_ss_n64_tb(acc0, da_base + so + ks * 2, db0_base + so + ks * 128, 1);
        wgmma_ss_n16_tb(acc1, da_base + so + ks * 2, db1_base + so + ks * 32, 1);
      }
      wgmma_commit();
      wgmma_wait<1>();
      release_stage(sBar + 8 * (NST + (s + NST - 1) % NST), leader && (s > 0 || r > 0));
    }
  }
}

constexpr int KA_SMEM = LG_STAGES * QKV_STAGE + 128 + 1024;

__global__ void __launch_bounds__(GT, 1)
qkv_kernel(const __grid_constant__ CUtensorMap tmA, const __grid_constant__ CUtensorMap tmB, const bf16* __restrict__ x) {
  constexpr int STAGE_BYTES = QKV_STAGE, NST = LG_STAGES, NKB = 20;
  extern __shared__ uint8_t smem_raw[];
  const uint32_t sbase = (smem_u32(smem_raw) + 1023u) & ~1023u;
  const uint32_t sBar = sbase + NST * STAGE_BYTES;
  const int tid = threadIdx.x, warp = tid >> 5, lane = tid & 31;
  const int rank = blockIdx.x & 1;
  const int pair = blockIdx.x >> 1;
  const int n_blk = pair & 7;
  const int m_blk = (pair >> 3) * 2 + rank;
  TS(0, 0);
  if (tid == 256) {
    prefetch_tmap(&tmA);
    prefetch_tmap(&tmB);
  }
  if (tid == 0) {
    for (int s = 0; s < NST; s++) {
      mbar_init(sBar + 8 * s, 1);
      mbar_init(sBar + 8 * (NST + s), 4);
    }
    fence_mbar_init();
    if (blockIdx.x < 32) g_flag[16 + blockIdx.x] = 0;
  }
  pdl_launch();
  cluster_sync_all();

  if (warp >= 8) {
    asm volatile("setmaxnreg.dec.sync.aligned.u32 40;");
    if (tid == 256) {
      auto issue_b = [&](int kb) {
        const int s = kb % NST;
        const uint32_t full = sBar + 8 * s;
        mbar_expect_tx(full, STAGE_BYTES);
        const uint32_t dst = sbase + s * STAGE_BYTES + 8192;
#pragma unroll
        for (int j = 0; j < 2; j++) {
          const int sl = rank * 2 + j;
          tma_load_2d_mc(dst + sl * 4096, &tmB, n_blk * 240 + sl * 64, kb * 32, full, (uint16_t)3);
        }
      };
      for (int kb = 0; kb < NST; kb++) issue_b(kb);
      flag_wait(&g_flag[m_blk], 8);
      fence_proxy_async_all();
      for (int kb = 0; kb < NKB; kb++) {
        const int s = kb % NST;
        if (kb >= NST) {
          mbar_wait(sBar + 8 * (NST + s), ((kb / NST) & 1) ^ 1);
          issue_b(kb);
        }
        tma_load_2d(sbase + s * STAGE_BYTES, &tmA, kb * 32, m_blk * 128, sBar + 8 * s);
      }
    }
  } else {
    asm volatile("setmaxnreg.inc.sync.aligned.u32 232;");
    const int wg = __shfl_sync(0xffffffffu, warp >> 2, 0);
    const int wwarp = warp & 3;
    {
      const int row = m_blk * 128 + n_blk * 16 + warp * 2 + (lane >> 4);
      ln_row(x + (size_t)row * DM, g_xn + (size_t)row * DM, lane & 15);
      __threadfence();
      named_bar_sync(3, 256);
      if (tid == 0) atomicAdd(&g_flag[m_blk], 1);
    }
    TS(0, 1);
    mbar_wait(sBar, 0);
    TS(0, 3);
    float acc[120];
#pragma unroll
    for (int i = 0; i < 120; i++) acc[i] = 0.f;
    if (wg == 0) qkv_mainloop<0>(acc, sbase, sBar, (tid & 127) == 0);
    else qkv_mainloop<1>(acc, sbase, sBar, (tid & 127) == 0);
    wgmma_wait<0>();
    fence_regs(acc);
    TS(0, 4);
    named_bar_sync(3, 256);
    const int g = lane >> 2, c4 = lane & 3;
    const uint32_t stg = sbase + wg * (12 * 3072) + (wwarp * 2) * 384 + g * 16;
    const int hbase = n_blk * 12;
#pragma unroll
    for (int j = 0; j < 30; j++) {
      const int cb = (j * 8) % 20;
      const int hb = (j * 8) / 20;
      int d = cb + c4 * 2;
      int hl = hb;
      if (cb == 16 && c4 >= 2) { d -= 20; hl += 1; }
      const uint32_t a0 = stg + hl * 3072 + (d >> 3) * 128 + (d & 7) * 2;
      const int hg = hbase + hl;
      const float sc = hg < 32 ? ATT_SCALE_LOG2E : 1.0f;
      st_shared_b32(a0, pack_bf16(acc[4 * j] * sc, acc[4 * j + 1] * sc));
      st_shared_b32(a0 + 384, pack_bf16(acc[4 * j + 2] * sc, acc[4 * j + 3] * sc));
      if (d == 18) {
        const uint32_t pad0 = hg < 32 ? 0u : (hg < 64 ? 0x3f803f80u : 0x00003f80u);
        const uint32_t pad1 = (hg >= 32 && hg < 64) ? 0x00003f80u : 0u;
        st_shared_v2(a0 + 4, pad0, pad1);
        st_shared_v2(a0 + 388, pad0, pad1);
      }
    }
    fence_proxy_async();
    named_bar_sync(1 + wg, 128);
    if ((tid & 127) < 12) {
      const int hl = tid & 127;
      bf16* dst = g_img + (size_t)(hbase + hl) * IMG_HEAD_ELEMS + (size_t)(m_blk * 16 + wg * 8) * 192;
      bulk_s2g(dst, sbase + wg * (12 * 3072) + hl * 3072, 3072);
      bulk_commit();
      bulk_wait_read();
    }
  }
  __syncwarp();
  TS(0, 5);
  cluster_sync_relaxed();
  TS(0, 6);
}

constexpr int KC_NST1 = 5, KC_NST3 = 6;
constexpr int KC_STAGING = 160 * 1024;
constexpr int KC_BAR = KC_STAGING + 48 * 1024;
constexpr int KC_SMEM = KC_BAR + 512 + 1024;

__global__ void __launch_bounds__(GT, 1)
mlp_kernel(const __grid_constant__ CUtensorMap tmO, const __grid_constant__ CUtensorMap tmWo64, const __grid_constant__ CUtensorMap tmWo16,
           const __grid_constant__ CUtensorMap tmH, const __grid_constant__ CUtensorMap tmWg, const __grid_constant__ CUtensorMap tmWu,
           const __grid_constant__ CUtensorMap tmHHs, const __grid_constant__ CUtensorMap tmHH, const __grid_constant__ CUtensorMap tmWd64,
           const __grid_constant__ CUtensorMap tmWd16, const bf16* __restrict__ x, bf16* __restrict__ out) {
  extern __shared__ uint8_t smem_raw[];
  const uint32_t sbase = (smem_u32(smem_raw) + 1023u) & ~1023u;
  const uint32_t bar1 = sbase + KC_BAR;
  const uint32_t bar2 = bar1 + 128;
  const uint32_t bar3 = bar2 + 128;
  const uint32_t barD = bar3 + 128;
  const int tid = threadIdx.x, warp = tid >> 5, lane = tid & 31;
  const int rank = blockIdx.x & 1;
  const int pair = blockIdx.x >> 1;
  const int j_blk = pair & 7;
  const int m_blk = (pair >> 3) * 2 + rank;
  const int n0 = j_blk * 80;
  TS(2, 0);
  if (tid == 256) {
    prefetch_tmap(&tmO); prefetch_tmap(&tmWo64); prefetch_tmap(&tmWo16); prefetch_tmap(&tmH); prefetch_tmap(&tmWg);
    prefetch_tmap(&tmWu); prefetch_tmap(&tmHHs); prefetch_tmap(&tmHH); prefetch_tmap(&tmWd64); prefetch_tmap(&tmWd16);
  }
  if (tid == 0) {
    for (int s = 0; s < 5; s++) {
      mbar_init(bar1 + 8 * s, 1); mbar_init(bar1 + 8 * (5 + s), 4);
      mbar_init(bar2 + 8 * s, 1); mbar_init(bar2 + 8 * (5 + s), 4);
    }
    for (int s = 0; s < 6; s++) { mbar_init(bar3 + 8 * s, 1); mbar_init(bar3 + 8 * (6 + s), 4); }
    mbar_init(barD, 4); mbar_init(barD + 8, 4);
    fence_mbar_init();
  }
  cluster_sync_all();

  if (warp >= 8) {
    asm volatile("setmaxnreg.dec.sync.aligned.u32 40;");
    if (tid == 256) {
      auto issue_b80 = [&](const CUtensorMap* t64, const CUtensorMap* t16, uint32_t bars, int nst, int kb) {
        const int s = kb % nst;
        const uint32_t full = bars + 8 * s;
        const uint32_t st = sbase + s * RG_STAGE_BYTES;
        mbar_expect_tx(full, RG_STAGE_BYTES);
        tma_load_2d_mc(st + 16384 + rank * 4096, t64, n0, kb * 64 + rank * 32, full, (uint16_t)3);
        tma_load_2d_mc(st + 16384 + 8192 + rank * 1024, t16, n0 + 64, kb * 64 + rank * 32, full, (uint16_t)3);
      };
      for (int kb = 0; kb < KC_NST1; kb++) issue_b80(&tmWo64, &tmWo16, bar1, KC_NST1, kb);
      pdl_wait();
      for (int kb = 0; kb < 10; kb++) {
        const int s = kb % KC_NST1;
        if (kb >= KC_NST1) {
          mbar_wait(bar1 + 8 * (KC_NST1 + s), ((kb / KC_NST1) & 1) ^ 1);
          issue_b80(&tmWo64, &tmWo16, bar1, KC_NST1, kb);
        }
        tma_load_2d(sbase + s * RG_STAGE_BYTES, &tmO, kb * 64, m_blk * 128, bar1 + 8 * s);
      }
      auto issue_bglu = [&](int kb) {
        const int s = kb % LG_STAGES;
        const uint32_t full = bar2 + 8 * s;
        mbar_expect_tx(full, GLU_STAGE);
        const uint32_t dst = sbase + s * GLU_STAGE + 8192;
#pragma unroll
        for (int j = 0; j < 3; j++)
          tma_load_2d_mc(dst + (rank * 3 + j) * 4096, rank == 0 ? &tmWg : &tmWu, j_blk * 192 + j * 64, kb * 32, full, (uint16_t)3);
      };
      mbar_wait(barD, 0);
      for (int kb = 0; kb < LG_STAGES; kb++) issue_bglu(kb);
      flag_wait(&g_flag[16 + m_blk], 16);
      fence_proxy_async_all();
      for (int kb = 0; kb < 20; kb++) {
        const int s = kb % LG_STAGES;
        if (kb >= LG_STAGES) {
          mbar_wait(bar2 + 8 * (LG_STAGES + s), ((kb / LG_STAGES) & 1) ^ 1);
          issue_bglu(kb);
        }
        tma_load_2d(sbase + s * GLU_STAGE, &tmH, kb * 32, m_blk * 128, bar2 + 8 * s);
      }
      mbar_wait(barD + 8, 0);
      for (int kb = 0; kb < KC_NST3; kb++) issue_b80(&tmWd64, &tmWd16, bar3, KC_NST3, kb);
      flag_wait(&g_flag[32 + m_blk], 16);
      fence_proxy_async_all();
      for (int kb = 0; kb < 24; kb++) {
        const int s = kb % KC_NST3;
        if (kb >= KC_NST3) {
          mbar_wait(bar3 + 8 * (KC_NST3 + s), ((kb / KC_NST3) & 1) ^ 1);
          issue_b80(&tmWd64, &tmWd16, bar3, KC_NST3, kb);
        }
        tma_load_2d(sbase + s * RG_STAGE_BYTES, &tmHH, kb * 64, m_blk * 128, bar3 + 8 * s);
      }
    }
  } else {
    asm volatile("setmaxnreg.inc.sync.aligned.u32 232;");
    const int wg = __shfl_sync(0xffffffffu, warp >> 2, 0);
    const int wwarp = warp & 3;
    const int g = lane >> 2, c4 = lane & 3;
    const int row0 = m_blk * 128 + wg * 64 + wwarp * 16 + g;
    const bool leader = (tid & 127) == 0;
    {
      uint32_t res[20];
#pragma unroll
      for (int j = 0; j < 10; j++) {
        res[2 * j] = __ldg(reinterpret_cast<const uint32_t*>(x + (size_t)row0 * DM + n0 + j * 8 + c4 * 2));
        res[2 * j + 1] = __ldg(reinterpret_cast<const uint32_t*>(x + (size_t)(row0 + 8) * DM + n0 + j * 8 + c4 * 2));
      }
      float acc0[32], acc1[8];
#pragma unroll
      for (int i = 0; i < 32; i++) acc0[i] = 0.f;
#pragma unroll
      for (int i = 0; i < 8; i++) acc1[i] = 0.f;
      TS(2, 1);
      if (wg == 0) res_mainloop<10, KC_NST1, 0>(acc0, acc1, sbase, bar1, leader);
      else res_mainloop<10, KC_NST1, 1>(acc0, acc1, sbase, bar1, leader);
      wgmma_wait<0>();
      fence_regs(acc0); fence_regs(acc1);
      release_stage(barD, leader);
      TS(2, 4);
      float sum0 = 0.f, sum1 = 0.f;
#pragma unroll
      for (int j = 0; j < 10; j++) {
        const uint32_t a01 = j < 8 ? pack_bf16(acc0[4 * j], acc0[4 * j + 1]) : pack_bf16(acc1[4 * (j - 8)], acc1[4 * (j - 8) + 1]);
        const uint32_t a23 = j < 8 ? pack_bf16(acc0[4 * j + 2], acc0[4 * j + 3]) : pack_bf16(acc1[4 * (j - 8) + 2], acc1[4 * (j - 8) + 3]);
        res[2 * j] = pack_bf16(bf_lo(res[2 * j]) + bf_lo(a01), bf_hi(res[2 * j]) + bf_hi(a01));
        res[2 * j + 1] = pack_bf16(bf_lo(res[2 * j + 1]) + bf_lo(a23), bf_hi(res[2 * j + 1]) + bf_hi(a23));
        *reinterpret_cast<uint32_t*>(g_h + (size_t)row0 * DM + n0 + j * 8 + c4 * 2) = res[2 * j];
        *reinterpret_cast<uint32_t*>(g_h + (size_t)(row0 + 8) * DM + n0 + j * 8 + c4 * 2) = res[2 * j + 1];
        sum0 += bf_lo(res[2 * j]) + bf_hi(res[2 * j]);
        sum1 += bf_lo(res[2 * j + 1]) + bf_hi(res[2 * j + 1]);
      }
      sum0 += __shfl_xor_sync(0xffffffffu, sum0, 1); sum1 += __shfl_xor_sync(0xffffffffu, sum1, 1);
      sum0 += __shfl_xor_sync(0xffffffffu, sum0, 2); sum1 += __shfl_xor_sync(0xffffffffu, sum1, 2);
      const float mu0 = sum0 * (1.0f / 80.0f), mu1 = sum1 * (1.0f / 80.0f);
      float q0 = 0.f, q1 = 0.f;
#pragma unroll
      for (int j = 0; j < 10; j++) {
        float d;
        d = bf_lo(res[2 * j]) - mu0; q0 = fmaf(d, d, q0);
        d = bf_hi(res[2 * j]) - mu0; q0 = fmaf(d, d, q0);
        d = bf_lo(res[2 * j + 1]) - mu1; q1 = fmaf(d, d, q1);
        d = bf_hi(res[2 * j + 1]) - mu1; q1 = fmaf(d, d, q1);
      }
      q0 += __shfl_xor_sync(0xffffffffu, q0, 1); q1 += __shfl_xor_sync(0xffffffffu, q1, 1);
      q0 += __shfl_xor_sync(0xffffffffu, q0, 2); q1 += __shfl_xor_sync(0xffffffffu, q1, 2);
      if (c4 == 0) {
        g_stats[row0 * 8 + j_blk] = make_float2(mu0, q0);
        g_stats[(row0 + 8) * 8 + j_blk] = make_float2(mu1, q1);
      }
      __threadfence();
      named_bar_sync(1 + wg, 128);
      if (leader) atomicAdd(&g_flag[16 + m_blk], 1);
      TS(2, 5);
    }
    {
      pdl_wait();
      flag_wait(&g_flag[16 + m_blk], 16);
      float mb[2], iv[2];
#pragma unroll
      for (int h = 0; h < 2; h++) {
        const float4* sp = reinterpret_cast<const float4*>(g_stats + (row0 + 8 * h) * 8);
        const float4 p0 = sp[0], p1 = sp[1], p2 = sp[2], p3 = sp[3];
        const float mean = (((p0.x + p0.z) + (p1.x + p1.z)) + ((p2.x + p2.z) + (p3.x + p3.z))) * 0.125f;
        float m2 = ((p0.y + p0.w) + (p1.y + p1.w)) + ((p2.y + p2.w) + (p3.y + p3.w));
        float dd = 0.f, d;
        d = p0.x - mean; dd = fmaf(d, d, dd); d = p0.z - mean; dd = fmaf(d, d, dd);
        d = p1.x - mean; dd = fmaf(d, d, dd); d = p1.z - mean; dd = fmaf(d, d, dd);
        d = p2.x - mean; dd = fmaf(d, d, dd); d = p2.z - mean; dd = fmaf(d, d, dd);
        d = p3.x - mean; dd = fmaf(d, d, dd); d = p3.z - mean; dd = fmaf(d, d, dd);
        m2 = fmaf(dd, 80.0f, m2);
        const float var_b = bf16_round(m2 * (1.0f / DM));
        const float den = bf16_round(sqrtf(bf16_round(var_b + 1e-5f)));
        iv[h] = __frcp_rn(den);
        mb[h] = bf16_round(mean);
      }
      float accg[96], accu[96];
#pragma unroll
      for (int i = 0; i < 96; i++) { accg[i] = 0.f; accu[i] = 0.f; }
      TS(3, 3);
      if (wg == 0) glu_mainloop<0>(accg, accu, sbase, bar2, leader);
      else glu_mainloop<1>(accg, accu, sbase, bar2, leader);
      wgmma_wait<0>();
      fence_regs(accg); fence_regs(accu);
      release_stage(barD + 8, leader);
      TS(3, 4);
      const uint32_t stg = sbase + KC_STAGING + wg * 24576 + (wwarp * 16 + g) * 128 + c4 * 4;
      const float* csg = g_cs + j_blk * 192 + c4 * 2;
#pragma unroll
      for (int j = 0; j < 24; j++) {
        const float2 cg = *reinterpret_cast<const float2*>(csg + j * 8);
        const float2 cu = *reinterpret_cast<const float2*>(csg + FF + j * 8);
        uint32_t pk[2];
#pragma unroll
        for (int h = 0; h < 2; h++) {
          const uint32_t gp = pack_bf16(fmaf(-mb[h], cg.x, accg[4 * j + 2 * h]) * iv[h], fmaf(-mb[h], cg.y, accg[4 * j + 2 * h + 1]) * iv[h]);
          const uint32_t up = pack_bf16(fmaf(-mb[h], cu.x, accu[4 * j + 2 * h]) * iv[h], fmaf(-mb[h], cu.y, accu[4 * j + 2 * h + 1]) * iv[h]);
          const float g0 = bf_lo(gp), g1 = bf_hi(gp);
          const float r0 = (g0 * (g0 > 0.f ? 1.f : 0.f)) * bf_lo(up);
          const float r1 = (g1 * (g1 > 0.f ? 1.f : 0.f)) * bf_hi(up);
          pk[h] = pack_bf16(r0, r1);
        }
        const uint32_t a0 = stg + (j >> 3) * 8192 + (((j & 7) ^ g) << 4);
        st_shared_b32(a0, pk[0]);
        st_shared_b32(a0 + 1024, pk[1]);
      }
      fence_proxy_async();
      named_bar_sync(1 + wg, 128);
      if (leader) {
#pragma unroll
        for (int sl = 0; sl < 3; sl++)
          tma_store_2d(&tmHHs, sbase + KC_STAGING + wg * 24576 + sl * 8192, j_blk * 192 + sl * 64, m_blk * 128 + wg * 64);
        bulk_commit();
        bulk_wait_all();
        fence_proxy_async_all();
        flag_signal(&g_flag[32 + m_blk]);
      }
      TS(3, 5);
    }
    {
      uint32_t res[20];
#pragma unroll
      for (int j = 0; j < 10; j++) {
        res[2 * j] = *reinterpret_cast<const uint32_t*>(g_h + (size_t)row0 * DM + n0 + j * 8 + c4 * 2);
        res[2 * j + 1] = *reinterpret_cast<const uint32_t*>(g_h + (size_t)(row0 + 8) * DM + n0 + j * 8 + c4 * 2);
      }
      float acc0[32], acc1[8];
#pragma unroll
      for (int i = 0; i < 32; i++) acc0[i] = 0.f;
#pragma unroll
      for (int i = 0; i < 8; i++) acc1[i] = 0.f;
      mbar_wait(bar3, 0);
      TS(4, 3);
      if (wg == 0) res_mainloop<24, KC_NST3, 0>(acc0, acc1, sbase, bar3, leader);
      else res_mainloop<24, KC_NST3, 1>(acc0, acc1, sbase, bar3, leader);
      wgmma_wait<0>();
      fence_regs(acc0); fence_regs(acc1);
      TS(4, 4);
#pragma unroll
      for (int j = 0; j < 10; j++) {
        const uint32_t a01 = j < 8 ? pack_bf16(acc0[4 * j], acc0[4 * j + 1]) : pack_bf16(acc1[4 * (j - 8)], acc1[4 * (j - 8) + 1]);
        const uint32_t a23 = j < 8 ? pack_bf16(acc0[4 * j + 2], acc0[4 * j + 3]) : pack_bf16(acc1[4 * (j - 8) + 2], acc1[4 * (j - 8) + 3]);
        *reinterpret_cast<uint32_t*>(out + (size_t)row0 * DM + n0 + j * 8 + c4 * 2) =
            pack_bf16(bf_lo(res[2 * j]) + bf_lo(a01), bf_hi(res[2 * j]) + bf_hi(a01));
        *reinterpret_cast<uint32_t*>(out + (size_t)(row0 + 8) * DM + n0 + j * 8 + c4 * 2) =
            pack_bf16(bf_lo(res[2 * j + 1]) + bf_lo(a23), bf_hi(res[2 * j + 1]) + bf_hi(a23));
      }
      TS(4, 5);
    }
  }
  __syncwarp();
  cluster_sync_relaxed();
  TS(4, 6);
}

constexpr int AT_THREADS = 512;
constexpr int AT_WGS = AT_THREADS / 128;
#define AT_CHUNK_MASK 3
#define AT_STAGGER 0
constexpr int AT_KV_BYTES = IMG_HEAD_ELEMS * 2;
constexpr int AT_SMEM = 2 * AT_KV_BYTES + 256 + 1024;
constexpr int AT_CHUNKS = 8;

__device__ __forceinline__ float exp2_poly(float x) {
  const float u = __saturatef(fmaf(x, 1.0f / 64.0f, 62.0f / 64.0f));
  const float MAGIC = 12582912.0f - 62.0f;
  const float r = fmaf(u, 64.0f, MAGIC);
  const float q = MAGIC - r;
  const float fr = fmaf(u, 64.0f, q);
  float p = fmaf(fr, 0.009570102207362652f, 0.05591785907745361f);
  p = fmaf(p, fr, 0.240247443318367f);
  p = fmaf(p, fr, 0.6931217908859253f);
  p = fmaf(p, fr, 0.9999992847442627f);
  return __uint_as_float(__float_as_uint(p) + (__float_as_uint(r) << 23));
}
#define AT_VARIANT 0
#define AT_POLY_MOD 8
__device__ __forceinline__ bool use_poly(int e) {
  return (e % AT_POLY_MOD) == 1;
}

struct AttnState {
  uint32_t qa0, qa1, qa2, qa3, qa4, qa5;
  float M0, M1;
};

__device__ __forceinline__ bool attn_exp_fast(const float (&s)[32], uint32_t (&p)[16]) {
#pragma unroll
  for (int j = 0; j < 16; j++) {
    const float e0 = use_poly(2 * j) ? exp2_poly(s[2 * j]) : ex2(s[2 * j]);
    const float e1 = use_poly(2 * j + 1) ? exp2_poly(s[2 * j + 1]) : ex2(s[2 * j + 1]);
    p[j] = pack_bf16(e0, e1);
  }
  uint32_t acc_or = 0;
#pragma unroll
  for (int j = 0; j < 16; j++) acc_or |= p[j];
  return __any_sync(0xffffffffu, (acc_or & 0x40004000u) != 0);
}
__device__ __forceinline__ void attn_exp_exact(const float (&s)[32], uint32_t (&p)[16], float (&o)[12], AttnState& st, bool first, int c4) {
  float mx0 = fmaxf(s[0], s[1]), mx1 = fmaxf(s[2], s[3]);
#pragma unroll
  for (int j = 1; j < 8; j++) {
    mx0 = fmaxf(mx0, fmaxf(s[4 * j], s[4 * j + 1]));
    mx1 = fmaxf(mx1, fmaxf(s[4 * j + 2], s[4 * j + 3]));
  }
  mx0 = fmaxf(mx0, __shfl_xor_sync(0xffffffffu, mx0, 1));
  mx1 = fmaxf(mx1, __shfl_xor_sync(0xffffffffu, mx1, 1));
  mx0 = fmaxf(mx0, __shfl_xor_sync(0xffffffffu, mx0, 2));
  mx1 = fmaxf(mx1, __shfl_xor_sync(0xffffffffu, mx1, 2));
  float d0 = mx0 + 7.0f, d1 = mx1 + 7.0f;
  if (!first) { d0 = fmaxf(d0, 0.f); d1 = fmaxf(d1, 0.f); }
  const float T0 = st.M0 + d0, T1 = st.M1 + d1;
  const float h0 = bf16_round(T0), h1 = bf16_round(T1);
  const float i0 = bf16_round(T0 - h0), i1 = bf16_round(T1 - h1);
  const float l0 = bf16_round((T0 - h0) - i0), l1 = bf16_round((T1 - h1) - i1);
  const float N0 = (h0 + i0) + l0, N1 = (h1 + i1) + l1;
  d0 = N0 - st.M0; d1 = N1 - st.M1;
  st.M0 = N0; st.M1 = N1;
  if (c4 == 2) { st.qa4 = pack_bf16(-h0, -i0); st.qa5 = pack_bf16(-h1, -i1); }
  if (c4 == 3) { st.qa4 = pack_bf16(-l0, 0.f); st.qa5 = pack_bf16(-l1, 0.f); }
  if (!first) {
    const float al0 = ex2(-d0), al1 = ex2(-d1);
#pragma unroll
    for (int j = 0; j < 3; j++) {
      o[4 * j] *= al0; o[4 * j + 1] *= al0;
      o[4 * j + 2] *= al1; o[4 * j + 3] *= al1;
    }
  }
#pragma unroll
  for (int j = 0; j < 8; j++) {
    p[2 * j] = pack_bf16(ex2(s[4 * j] - d0), ex2(s[4 * j + 1] - d0));
    p[2 * j + 1] = pack_bf16(ex2(s[4 * j + 2] - d1), ex2(s[4 * j + 3] - d1));
  }
}
__device__ __forceinline__ void attn_step(float (&s)[32], const uint32_t (&pp)[16], uint32_t (&pn)[16], float (&o)[12], AttnState& st,
                                          uint32_t k_addr, uint32_t v_addr_prev, int keep, int c4, int wgdbg = 0, int tdbg = 0) {
  PH(wgdbg, tdbg, 0);
  const uint64_t dk = make_desc(k_addr, 128, 384, 0);
  const uint64_t dv_prev = make_desc(v_addr_prev, 384, 128, 0);
  wgmma_fence();
  wgmma_rs_n64(s, st.qa0, st.qa1, st.qa2, st.qa3, dk, 0);
  wgmma_rs_n64(s, st.qa4, st.qa5, 0u, 0u, dk + 16, 1);
  wgmma_commit();
#pragma unroll
  for (int kk = 0; kk < 4; kk++) wgmma_rs_n24_tb(o, pp[4 * kk], pp[4 * kk + 1], pp[4 * kk + 2], pp[4 * kk + 3], dv_prev + kk * 48, kk == 0 ? keep : 1);
  wgmma_commit();
  wgmma_wait<1>();
  fence_regs(s);
  PH(wgdbg, tdbg, 1);
  const bool redo = attn_exp_fast(s, pn);
  PH(wgdbg, tdbg, 2);
  wgmma_wait<0>();
  fence_regs(o);
  if (redo) attn_exp_exact(s, pn, o, st, false, c4);
}

__global__ void __launch_bounds__(AT_THREADS, 1) attn_kernel(const bf16* __restrict__ wo, const bf16* __restrict__ wgt, const bf16* __restrict__ wup, const bf16* __restrict__ wdn) {
  extern __shared__ uint8_t smem_raw[];
  const uint32_t sbase = (smem_u32(smem_raw) + 1023u) & ~1023u;
  const uint32_t sK = sbase, sV = sbase + AT_KV_BYTES;
  const uint32_t sBar = sV + AT_KV_BYTES;
  const int tid = threadIdx.x, warp = tid >> 5, lane = tid & 31;
  const int head = blockIdx.x >> 2, quarter = blockIdx.x & 3;
  if (blockIdx.x >= 128) {
    pdl_launch();
    const int b = blockIdx.x - 128;
    const bf16* w = (b >> 1) ? wup : wgt;
    const int cgrp = tid % 96, rgrp = tid / 96;
    float acc[8];
#pragma unroll
    for (int i = 0; i < 8; i++) acc[i] = 0.f;
    float* red = reinterpret_cast<float*>(smem_raw);
    if (rgrp < 5) {
      const uint4* src = reinterpret_cast<const uint4*>(w + (size_t)(rgrp * 128) * FF + (b & 1) * 768 + cgrp * 8);
#pragma unroll 8
      for (int r = 0; r < 128; r++) {
        const uint4 v = __ldg(src + (size_t)r * (FF / 8));
        acc[0] += bf_lo(v.x); acc[1] += bf_hi(v.x); acc[2] += bf_lo(v.y); acc[3] += bf_hi(v.y);
        acc[4] += bf_lo(v.z); acc[5] += bf_hi(v.z); acc[6] += bf_lo(v.w); acc[7] += bf_hi(v.w);
      }
#pragma unroll
      for (int i = 0; i < 8; i++) red[rgrp * 768 + cgrp * 8 + i] = acc[i];
    }
    __syncthreads();
    pdl_wait();
    for (int c = tid; c < 768; c += AT_THREADS)
      g_cs[(b >> 1) * FF + (b & 1) * 768 + c] = ((red[c] + red[768 + c]) + (red[1536 + c] + red[2304 + c])) + red[3072 + c];
    if (b == 0 && tid < 16) g_flag[tid] = 0;
    return;
  }
  TS(1, 0);
  if (tid == 0) {
    for (int i = 0; i < AT_CHUNKS; i++) mbar_init(sBar + 8 * i, 1);
    fence_mbar_init();
  }
  pdl_launch();
  if (tid == 32) {
    prefetch_l2(reinterpret_cast<const uint8_t*>(wo) + blockIdx.x * 6400, 6400);
    prefetch_l2(reinterpret_cast<const uint8_t*>(wgt) + blockIdx.x * 15360, 15360);
    prefetch_l2(reinterpret_cast<const uint8_t*>(wup) + blockIdx.x * 15360, 15360);
    prefetch_l2(reinterpret_cast<const uint8_t*>(wdn) + blockIdx.x * 15360, 15360);
  }
  __syncthreads();
  TS(1, 1);
  pdl_wait();
  TS(1, 2);
  if (tid == 0) {
    const uint8_t* kg = reinterpret_cast<const uint8_t*>(g_img + (size_t)(32 + head) * IMG_HEAD_ELEMS);
    const uint8_t* vg = reinterpret_cast<const uint8_t*>(g_img + (size_t)(64 + head) * IMG_HEAD_ELEMS);
    constexpr int CB = AT_KV_BYTES / AT_CHUNKS;
    for (int i = 0; i < AT_CHUNKS; i++) {
      mbar_expect_tx(sBar + 8 * i, 2 * CB);
      bulk_g2s(sK + i * CB, kg + i * CB, CB, sBar + 8 * i);
      bulk_g2s(sV + i * CB, vg + i * CB, CB, sBar + 8 * i);
    }
  }
  const int wg = warp >> 2, wwarp = warp & 3;
  const int g = lane >> 2, c4 = lane & 3;
  const uint64_t dk_base = make_desc(sK, 128, 384, 0);
  const uint64_t dv_base = make_desc(sV, 384, 128, 0);

#pragma unroll 1
  for (int rep = 0; rep < 8 / AT_WGS; rep++) {
    const int row0 = quarter * 512 + (rep * AT_WGS + wg) * 64 + wwarp * 16 + g;
    AttnState st;
    {
      const bf16* q0 = g_img + (size_t)head * IMG_HEAD_ELEMS + (size_t)(row0 >> 3) * 192 + g * 8 + c4 * 2;
      const bf16* q1 = q0 + 192;
      st.qa0 = *reinterpret_cast<const uint32_t*>(q0);
      st.qa1 = *reinterpret_cast<const uint32_t*>(q1);
      st.qa2 = *reinterpret_cast<const uint32_t*>(q0 + 64);
      st.qa3 = *reinterpret_cast<const uint32_t*>(q1 + 64);
      st.qa4 = *reinterpret_cast<const uint32_t*>(q0 + 128);
      st.qa5 = *reinterpret_cast<const uint32_t*>(q1 + 128);
    }
    float o[12];
    float s[32];
    uint32_t pa[16], pb[16];
    st.M0 = st.M1 = 0.f;
    if (rep == 0) mbar_wait(sBar, 0);
    wgmma_fence();
    wgmma_rs_n64(s, st.qa0, st.qa1, st.qa2, st.qa3, dk_base, 0);
    wgmma_rs_n64(s, st.qa4, st.qa5, 0u, 0u, dk_base + 16, 1);
    wgmma_commit();
    wgmma_wait<0>();
    fence_regs(s);
    attn_exp_exact(s, pa, o, st, true, c4);
    attn_step(s, pa, pb, o, st, sK + 3072, sV, 0, c4);
#pragma unroll 1
    for (int tt = 1; tt < 16; tt++) {
      if (rep == 0 && !(tt & 1)) mbar_wait(sBar + 8 * (tt >> 1), 0);
      attn_step(s, pb, pa, o, st, sK + tt * 6144, sV + tt * 6144 - 3072, 1, c4, wg, rep * 32 + tt * 2);
      attn_step(s, pa, pb, o, st, sK + tt * 6144 + 3072, sV + tt * 6144, 1, c4, wg, rep * 32 + tt * 2 + 1);
    }
    wgmma_fence();
#pragma unroll
    for (int kk = 0; kk < 4; kk++) wgmma_rs_n24_tb(o, pb[4 * kk], pb[4 * kk + 1], pb[4 * kk + 2], pb[4 * kk + 3], dv_base + 31 * 192 + kk * 48, 1);
    wgmma_commit();
    wgmma_wait<0>();
    fence_regs(o);
    TS(1, 3 + rep);
    const float l0 = __shfl_sync(0xffffffffu, o[8], (lane & ~3) | 2);
    const float l1 = __shfl_sync(0xffffffffu, o[10], (lane & ~3) | 2);
    const float i0 = 1.0f / l0, i1 = 1.0f / l1;
    bf16* o0 = g_o + (size_t)row0 * DM + head * DH;
    bf16* o1 = o0 + 8 * DM;
#pragma unroll
    for (int j = 0; j < 3; j++) {
      if (j < 2 || c4 < 2) {
        *reinterpret_cast<uint32_t*>(o0 + j * 8 + c4 * 2) = pack_bf16(o[4 * j] * i0, o[4 * j + 1] * i0);
        *reinterpret_cast<uint32_t*>(o1 + j * 8 + c4 * 2) = pack_bf16(o[4 * j + 2] * i1, o[4 * j + 3] * i1);
      }
    }
  }
}

typedef CUresult (*EncodeTiledFn)(CUtensorMap*, CUtensorMapDataType, cuuint32_t, void*, const cuuint64_t*, const cuuint64_t*,
                                  const cuuint32_t*, const cuuint32_t*, CUtensorMapInterleave, CUtensorMapSwizzle,
                                  CUtensorMapL2promotion, CUtensorMapFloatOOBfill);

static void make_map(EncodeTiledFn fn, CUtensorMap* tm, const void* ptr, uint64_t rows, uint64_t cols, uint32_t box_rows,
                     uint32_t box_cols, CUtensorMapSwizzle sw) {
  cuuint64_t dims[2] = {cols, rows};
  cuuint64_t strides[1] = {cols * 2};
  cuuint32_t box[2] = {box_cols, box_rows};
  cuuint32_t es[2] = {1, 1};
  fn(tm, CU_TENSOR_MAP_DATA_TYPE_BFLOAT16, 2, const_cast<void*>(ptr), dims, strides, box, es, CU_TENSOR_MAP_INTERLEAVE_NONE, sw,
     CU_TENSOR_MAP_L2_PROMOTION_L2_256B, CU_TENSOR_MAP_FLOAT_OOB_FILL_NONE);
}

template <typename... KArgs, typename... Args>
static void launch(void (*kern)(KArgs...), int grid, int block, int smem, int cluster, bool pdl, Args... args) {
  cudaLaunchConfig_t cfg = {};
  cfg.gridDim = dim3(grid);
  cfg.blockDim = dim3(block);
  cfg.dynamicSmemBytes = smem;
  cfg.stream = cudaStreamPerThread;
  cudaLaunchAttribute at[2];
  int n = 0;
  if (cluster > 1) {
    at[n].id = cudaLaunchAttributeClusterDimension;
    at[n].val.clusterDim.x = cluster; at[n].val.clusterDim.y = 1; at[n].val.clusterDim.z = 1;
    n++;
  }
  if (pdl) {
    at[n].id = cudaLaunchAttributeProgrammaticStreamSerialization;
    at[n].val.programmaticStreamSerializationAllowed = 1;
    n++;
  }
  cfg.attrs = at;
  cfg.numAttrs = n;
  cudaLaunchKernelEx(&cfg, kern, KArgs(args)...);
}

extern "C" void kernel_launch(void* const* d_in, const int* in_sizes, int n_in, void* d_out, int out_size) {
  const bf16* x = (const bf16*)d_in[0];
  const bf16* wqkv = (const bf16*)d_in[1];
  const bf16* wo = (const bf16*)d_in[2];
  const bf16* wg = (const bf16*)d_in[4];
  const bf16* wu = (const bf16*)d_in[5];
  const bf16* wd = (const bf16*)d_in[6];
  bf16* out = (bf16*)d_out;

  static EncodeTiledFn enc = nullptr;
  static void *p_o = nullptr, *p_h = nullptr, *p_hh = nullptr, *p_xn = nullptr;
  if (!enc) {
    void* fn = nullptr;
    cudaDriverEntryPointQueryResult qr;
    cudaGetDriverEntryPoint("cuTensorMapEncodeTiled", &fn, cudaEnableDefault, &qr);
    enc = (EncodeTiledFn)fn;
    cudaGetSymbolAddress(&p_o, g_o);
    cudaGetSymbolAddress(&p_h, g_h);
    cudaGetSymbolAddress(&p_hh, g_hh);
    cudaGetSymbolAddress(&p_xn, g_xn);
    cudaFuncSetAttribute(qkv_kernel, cudaFuncAttributeMaxDynamicSharedMemorySize, KA_SMEM);
    cudaFuncSetAttribute(mlp_kernel, cudaFuncAttributeMaxDynamicSharedMemorySize, KC_SMEM);
    cudaFuncSetAttribute(attn_kernel, cudaFuncAttributeMaxDynamicSharedMemorySize, AT_SMEM);
  }
  CUtensorMap tm_wqkv, tm_wg, tm_wu, tm_wo64, tm_wo16, tm_wd64, tm_wd16, tm_o, tm_h, tm_hh, tm_hhs, tm_xn;
  make_map(enc, &tm_wqkv, wqkv, DM, 3 * DM, 32, 64, CU_TENSOR_MAP_SWIZZLE_128B);
  make_map(enc, &tm_wg, wg, DM, FF, 32, 64, CU_TENSOR_MAP_SWIZZLE_128B);
  make_map(enc, &tm_wu, wu, DM, FF, 32, 64, CU_TENSOR_MAP_SWIZZLE_128B);
  make_map(enc, &tm_wo64, wo, DM, DM, 32, 64, CU_TENSOR_MAP_SWIZZLE_128B);
  make_map(enc, &tm_wo16, wo, DM, DM, 32, 16, CU_TENSOR_MAP_SWIZZLE_32B);
  make_map(enc, &tm_wd64, wd, FF, DM, 32, 64, CU_TENSOR_MAP_SWIZZLE_128B);
  make_map(enc, &tm_wd16, wd, FF, DM, 32, 16, CU_TENSOR_MAP_SWIZZLE_32B);
  make_map(enc, &tm_o, p_o, SEQ, DM, 128, 64, CU_TENSOR_MAP_SWIZZLE_128B);
  make_map(enc, &tm_h, p_h, SEQ, DM, 128, 32, CU_TENSOR_MAP_SWIZZLE_64B);
  make_map(enc, &tm_hh, p_hh, SEQ, FF, 128, 64, CU_TENSOR_MAP_SWIZZLE_128B);
  make_map(enc, &tm_hhs, p_hh, SEQ, FF, 64, 64, CU_TENSOR_MAP_SWIZZLE_128B);
  make_map(enc, &tm_xn, p_xn, SEQ, DM, 128, 32, CU_TENSOR_MAP_SWIZZLE_64B);

  launch(qkv_kernel, 128, GT, KA_SMEM, 2, false, tm_xn, tm_wqkv, x);
  launch(attn_kernel, 132, AT_THREADS, AT_SMEM, 1, true, wo, wg, wu, wd);
  launch(mlp_kernel, 128, GT, KC_SMEM, 2, true, tm_o, tm_wo64, tm_wo16, tm_h, tm_wg, tm_wu, tm_hhs, tm_hh, tm_wd64, tm_wd16, x, out);
}
```

```cpp
#include <cuda_runtime.h>
#include <cuda_bf16.h>
#include <cuda.h>
#include <stdint.h>

typedef __nv_bfloat16 bf16;

constexpr int SEQ = 2048, DM = 640, NH = 32, DH = 20, FF = 1536;
constexpr float ATT_SCALE_LOG2E = 0.22360679774997896f * 1.4426950408889634f;
constexpr int IMG_HEAD_ELEMS = (SEQ / 8) * 192;

__device__ __align__(1024) bf16 g_img[3 * NH * IMG_HEAD_ELEMS];
__device__ __align__(1024) bf16 g_o[SEQ * DM];
__device__ __align__(1024) bf16 g_h[SEQ * DM];
__device__ __align__(1024) bf16 g_xn[SEQ * DM];
__device__ float2 g_stats[SEQ * 8];
__device__ float g_cs[2 * FF];
__device__ int g_flag[3 * 16];
__device__ __align__(1024) bf16 g_hh[SEQ * FF];

#define TS(k, i)
#define PH(w, t, i)
__device__ __forceinline__ uint32_t smem_u32(const void* p) { return (uint32_t)__cvta_generic_to_shared(p); }
__device__ __forceinline__ void mbar_init(uint32_t bar, uint32_t cnt) {
  asm volatile("mbarrier.init.shared::cta.b64 [%0], %1;" ::"r"(bar), "r"(cnt) : "memory");
}
__device__ __forceinline__ void mbar_expect_tx(uint32_t bar, uint32_t bytes) {
  asm volatile("mbarrier.arrive.expect_tx.shared::cta.b64 _, [%0], %1;" ::"r"(bar), "r"(bytes) : "memory");
}
__device__ __forceinline__ void mbar_arrive(uint32_t bar) {
  asm volatile("mbarrier.arrive.shared::cta.b64 _, [%0];" ::"r"(bar) : "memory");
}
__device__ __forceinline__ void mbar_arrive_cluster(uint32_t bar, uint32_t cta) {
  asm volatile(
      "{\n.reg .b32 r;\nmapa.shared::cluster.u32 r, %0, %1;\n"
      "mbarrier.arrive.shared::cluster.b64 _, [r];\n}\n" ::"r"(bar), "r"(cta)
      : "memory");
}
__device__ __forceinline__ void mbar_wait(uint32_t bar, uint32_t parity) {
  asm volatile(
      "{\n.reg .pred p;\nLAB_WAIT:\n"
      "mbarrier.try_wait.parity.shared::cta.b64 p, [%0], %1;\n"
      "@p bra DONE;\nbra LAB_WAIT;\nDONE:\n}\n" ::"r"(bar), "r"(parity)
      : "memory");
}
__device__ __forceinline__ void mbar_wait_cluster(uint32_t bar, uint32_t parity) {
  asm volatile(
      "{\n.reg .pred p;\nLAB_WAIT:\n"
      "mbarrier.try_wait.parity.acquire.cluster.shared::cta.b64 p, [%0], %1;\n"
      "@p bra DONE;\nbra LAB_WAIT;\nDONE:\n}\n" ::"r"(bar), "r"(parity)
      : "memory");
}
__device__ __forceinline__ void fence_mbar_init() { asm volatile("fence.mbarrier_init.release.cluster;" ::: "memory"); }
__device__ __forceinline__ void fence_proxy_async() { asm volatile("fence.proxy.async.shared::cta;" ::: "memory"); }
__device__ __forceinline__ void cluster_sync_all() {
  asm volatile("barrier.cluster.arrive.release.aligned;\nbarrier.cluster.wait.acquire.aligned;" ::: "memory");
}
__device__ __forceinline__ void cluster_sync_relaxed() {
  asm volatile("barrier.cluster.arrive.relaxed.aligned;\nbarrier.cluster.wait.aligned;" ::: "memory");
}
__device__ __forceinline__ void named_bar_sync(int id, int n) { asm volatile("bar.sync %0, %1;" ::"r"(id), "r"(n) : "memory"); }
__device__ __forceinline__ bool wg_any(bool pred, int id) {
  uint32_t r;
  asm volatile("{\n.reg .pred p, q;\nsetp.ne.u32 p, %1, 0;\nbar.red.or.pred q, %2, 128, p;\nselp.u32 %0, 1, 0, q;\n}\n" : "=r"(r) : "r"((uint32_t)pred), "r"(id) : "memory");
  return r != 0;
}
__device__ __forceinline__ void fence_proxy_async_all() { asm volatile("fence.proxy.async;" ::: "memory"); }
__device__ __forceinline__ void flag_signal(int* f) {
  __threadfence();
  atomicAdd(f, 1);
}
__device__ __forceinline__ void flag_wait(const int* f, int target) {
  int v;
  unsigned spins = 0;
  do {
    asm volatile("ld.acquire.gpu.global.s32 %0, [%1];" : "=r"(v) : "l"(f) : "memory");
    if (++spins > (1u << 24)) __trap();
  } while (v < target);
}
__device__ __forceinline__ void pdl_launch() { asm volatile("griddepcontrol.launch_dependents;" ::: "memory"); }
__device__ __forceinline__ void pdl_wait() { asm volatile("griddepcontrol.wait;" ::: "memory"); }

__device__ __forceinline__ void tma_load_2d(uint32_t dst, const CUtensorMap* tm, int c0, int c1, uint32_t bar) {
  asm volatile(
      "cp.async.bulk.tensor.2d.shared::cluster.global.mbarrier::complete_tx::bytes [%0], [%1, {%3, %4}], [%2];" ::"r"(dst),
      "l"((uint64_t)tm), "r"(bar), "r"(c0), "r"(c1)
      : "memory");
}
__device__ __forceinline__ void tma_load_2d_mc(uint32_t dst, const CUtensorMap* tm, int c0, int c1, uint32_t bar, uint16_t mask) {
  asm volatile(
      "cp.async.bulk.tensor.2d.shared::cluster.global.mbarrier::complete_tx::bytes.multicast::cluster [%0], [%1, {%3, %4}], [%2], %5;" ::"r"(dst),
      "l"((uint64_t)tm), "r"(bar), "r"(c0), "r"(c1), "h"(mask)
      : "memory");
}
__device__ __forceinline__ void bulk_g2s(uint32_t dst, const void* src, uint32_t bytes, uint32_t bar) {
  asm volatile("cp.async.bulk.shared::cluster.global.mbarrier::complete_tx::bytes [%0], [%1], %2, [%3];" ::"r"(dst), "l"(src),
               "r"(bytes), "r"(bar)
               : "memory");
}
__device__ __forceinline__ void bulk_s2g(void* dst, uint32_t src, uint32_t bytes) {
  asm volatile("cp.async.bulk.global.shared::cta.bulk_group [%0], [%1], %2;" ::"l"(dst), "r"(src), "r"(bytes) : "memory");
}
__device__ __forceinline__ void tma_store_2d(const CUtensorMap* tm, uint32_t src, int c0, int c1) {
  asm volatile("cp.async.bulk.tensor.2d.global.shared::cta.bulk_group [%0, {%2, %3}], [%1];" ::"l"((uint64_t)tm), "r"(src), "r"(c0), "r"(c1) : "memory");
}
__device__ __forceinline__ void bulk_commit() { asm volatile("cp.async.bulk.commit_group;" ::: "memory"); }
__device__ __forceinline__ void bulk_wait_read() { asm volatile("cp.async.bulk.wait_group.read 0;" ::: "memory"); }
__device__ __forceinline__ void prefetch_l2(const void* p, uint32_t bytes) {
  asm volatile("cp.async.bulk.prefetch.L2.global [%0], %1;" ::"l"(p), "r"(bytes) : "memory");
}
__device__ __forceinline__ void bulk_wait_all() { asm volatile("cp.async.bulk.wait_group 0;" ::: "memory"); }
__device__ __forceinline__ void st_shared_b32(uint32_t addr, uint32_t v) { asm volatile("st.shared.b32 [%0], %1;" ::"r"(addr), "r"(v) : "memory"); }
__device__ __forceinline__ void st_shared_v2(uint32_t addr, uint32_t a, uint32_t b) { asm volatile("st.shared.v2.b32 [%0], {%1, %2};" ::"r"(addr), "r"(a), "r"(b) : "memory"); }
__device__ __forceinline__ void prefetch_tmap(const CUtensorMap* tm) {
  asm volatile("prefetch.tensormap [%0];" ::"l"((uint64_t)tm) : "memory");
}
__device__ __forceinline__ void wgmma_fence() { asm volatile("wgmma.fence.sync.aligned;" ::: "memory"); }
__device__ __forceinline__ void wgmma_commit() { asm volatile("wgmma.commit_group.sync.aligned;" ::: "memory"); }
template <int N>
__device__ __forceinline__ void wgmma_wait() { asm volatile("wgmma.wait_group.sync.aligned %0;" ::"n"(N) : "memory"); }

template <int N>
__device__ __forceinline__ void fence_regs(float (&r)[N]) {
#pragma unroll
  for (int i = 0; i < N; i++) asm volatile("" : "+f"(r[i])::"memory");
}
template <int N>
__device__ __forceinline__ void fence_regs(uint32_t (&r)[N]) {
#pragma unroll
  for (int i = 0; i < N; i++) asm volatile("" : "+r"(r[i])::"memory");
}
__device__ __forceinline__ uint64_t make_desc(uint32_t addr, uint32_t lbo, uint32_t sbo, uint32_t layout) {
  return (uint64_t)((addr & 0x3FFFF) >> 4) | ((uint64_t)((lbo & 0x3FFFF) >> 4) << 16) | ((uint64_t)((sbo & 0x3FFFF) >> 4) << 32) |
         ((uint64_t)layout << 62);
}
__device__ __forceinline__ uint32_t pack_bf16(float lo, float hi) {
  uint32_t r;
  asm("cvt.rn.bf16x2.f32 %0, %1, %2;" : "=r"(r) : "f"(hi), "f"(lo));
  return r;
}
__device__ __forceinline__ float bf16_round(float x) { return __bfloat162float(__float2bfloat16_rn(x)); }
__device__ __forceinline__ float bf_lo(uint32_t u) { return __uint_as_float(u << 16); }
__device__ __forceinline__ float bf_hi(uint32_t u) { return __uint_as_float(u & 0xffff0000u); }
__device__ __forceinline__ float ex2(float x) {
  float y;
  asm("ex2.approx.ftz.f32 %0, %1;" : "=f"(y) : "f"(x));
  return y;
}

__device__ __forceinline__ void wgmma_ss_n240_tb(float (&d)[120], uint64_t descA, uint64_t descB, int scaleD) {
  asm volatile("{\n.reg .pred p;\nsetp.ne.b32 p, %122, 0;\n"
    "wgmma.mma_async.sync.aligned.m64n240k16.f32.bf16.bf16 {%0, %1, %2, %3, %4, %5, %6, %7, %8, %9, %10, %11, %12, %13, %14, %15, %16, %17, %18, %19, %20, %21, %22, %23, %24, %25, %26, %27, %28, %29, %30, %31, %32, %33, %34, %35, %36, %37, %38, %39, %40, %41, %42, %43, %44, %45, %46, %47, %48, %49, %50, %51, %52, %53, %54, %55, %56, %57, %58, %59, %60, %61, %62, %63, %64, %65, %66, %67, %68, %69, %70, %71, %72, %73, %74, %75, %76, %77, %78, %79, %80, %81, %82, %83, %84, %85, %86, %87, %88, %89, %90, %91, %92, %93, %94, %95, %96, %97, %98, %99, %100, %101, %102, %103, %104, %105, %106, %107, %108, %109, %110, %111, %112, %113, %114, %115, %116, %117, %118, %119}, %120, %121, p, 1, 1, 0, 1;\n}\n"
    : "+f"(d[0]), "+f"(d[1]), "+f"(d[2]), "+f"(d[3]), "+f"(d[4]), "+f"(d[5]), "+f"(d[6]), "+f"(d[7]), "+f"(d[8]), "+f"(d[9]), "+f"(d[10]), "+f"(d[11]), "+f"(d[12]), "+f"(d[13]), "+f"(d[14]), "+f"(d[15]), "+f"(d[16]), "+f"(d[17]), "+f"(d[18]), "+f"(d[19]), "+f"(d[20]), "+f"(d[21]), "+f"(d[22]), "+f"(d[23]), "+f"(d[24]), "+f"(d[25]), "+f"(d[26]), "+f"(d[27]), "+f"(d[28]), "+f"(d[29]), "+f"(d[30]), "+f"(d[31]), "+f"(d[32]), "+f"(d[33]), "+f"(d[34]), "+f"(d[35]), "+f"(d[36]), "+f"(d[37]), "+f"(d[38]), "+f"(d[39]), "+f"(d[40]), "+f"(d[41]), "+f"(d[42]), "+f"(d[43]), "+f"(d[44]), "+f"(d[45]), "+f"(d[46]), "+f"(d[47]), "+f"(d[48]), "+f"(d[49]), "+f"(d[50]), "+f"(d[51]), "+f"(d[52]), "+f"(d[53]), "+f"(d[54]), "+f"(d[55]), "+f"(d[56]), "+f"(d[57]), "+f"(d[58]), "+f"(d[59]), "+f"(d[60]), "+f"(d[61]), "+f"(d[62]), "+f"(d[63]), "+f"(d[64]), "+f"(d[65]), "+f"(d[66]), "+f"(d[67]), "+f"(d[68]), "+f"(d[69]), "+f"(d[70]), "+f"(d[71]), "+f"(d[72]), "+f"(d[73]), "+f"(d[74]), "+f"(d[75]), "+f"(d[76]), "+f"(d[77]), "+f"(d[78]), "+f"(d[79]), "+f"(d[80]), "+f"(d[81]), "+f"(d[82]), "+f"(d[83]), "+f"(d[84]), "+f"(d[85]), "+f"(d[86]), "+f"(d[87]), "+f"(d[88]), "+f"(d[89]), "+f"(d[90]), "+f"(d[91]), "+f"(d[92]), "+f"(d[93]), "+f"(d[94]), "+f"(d[95]), "+f"(d[96]), "+f"(d[97]), "+f"(d[98]), "+f"(d[99]), "+f"(d[100]), "+f"(d[101]), "+f"(d[102]), "+f"(d[103]), "+f"(d[104]), "+f"(d[105]), "+f"(d[106]), "+f"(d[107]), "+f"(d[108]), "+f"(d[109]), "+f"(d[110]), "+f"(d[111]), "+f"(d[112]), "+f"(d[113]), "+f"(d[114]), "+f"(d[115]), "+f"(d[116]), "+f"(d[117]), "+f"(d[118]), "+f"(d[119])
    : "l"(descA), "l"(descB), "r"(scaleD));
}
__device__ __forceinline__ void wgmma_ss_n192_tb(float (&d)[96], uint64_t descA, uint64_t descB, int scaleD) {
  asm volatile("{\n.reg .pred p;\nsetp.ne.b32 p, %98, 0;\n"
    "wgmma.mma_async.sync.aligned.m64n192k16.f32.bf16.bf16 {%0, %1, %2, %3, %4, %5, %6, %7, %8, %9, %10, %11, %12, %13, %14, %15, %16, %17, %18, %19, %20, %21, %22, %23, %24, %25, %26, %27, %28, %29, %30, %31, %32, %33, %34, %35, %36, %37, %38, %39, %40, %41, %42, %43, %44, %45, %46, %47, %48, %49, %50, %51, %52, %53, %54, %55, %56, %57, %58, %59, %60, %61, %62, %63, %64, %65, %66, %67, %68, %69, %70, %71, %72, %73, %74, %75, %76, %77, %78, %79, %80, %81, %82, %83, %84, %85, %86, %87, %88, %89, %90, %91, %92, %93, %94, %95}, %96, %97, p, 1, 1, 0, 1;\n}\n"
    : "+f"(d[0]), "+f"(d[1]), "+f"(d[2]), "+f"(d[3]), "+f"(d[4]), "+f"(d[5]), "+f"(d[6]), "+f"(d[7]), "+f"(d[8]), "+f"(d[9]), "+f"(d[10]), "+f"(d[11]), "+f"(d[12]), "+f"(d[13]), "+f"(d[14]), "+f"(d[15]), "+f"(d[16]), "+f"(d[17]), "+f"(d[18]), "+f"(d[19]), "+f"(d[20]), "+f"(d[21]), "+f"(d[22]), "+f"(d[23]), "+f"(d[24]), "+f"(d[25]), "+f"(d[26]), "+f"(d[27]), "+f"(d[28]), "+f"(d[29]), "+f"(d[30]), "+f"(d[31]), "+f"(d[32]), "+f"(d[33]), "+f"(d[34]), "+f"(d[35]), "+f"(d[36]), "+f"(d[37]), "+f"(d[38]), "+f"(d[39]), "+f"(d[40]), "+f"(d[41]), "+f"(d[42]), "+f"(d[43]), "+f"(d[44]), "+f"(d[45]), "+f"(d[46]), "+f"(d[47]), "+f"(d[48]), "+f"(d[49]), "+f"(d[50]), "+f"(d[51]), "+f"(d[52]), "+f"(d[53]), "+f"(d[54]), "+f"(d[55]), "+f"(d[56]), "+f"(d[57]), "+f"(d[58]), "+f"(d[59]), "+f"(d[60]), "+f"(d[61]), "+f"(d[62]), "+f"(d[63]), "+f"(d[64]), "+f"(d[65]), "+f"(d[66]), "+f"(d[67]), "+f"(d[68]), "+f"(d[69]), "+f"(d[70]), "+f"(d[71]), "+f"(d[72]), "+f"(d[73]), "+f"(d[74]), "+f"(d[75]), "+f"(d[76]), "+f"(d[77]), "+f"(d[78]), "+f"(d[79]), "+f"(d[80]), "+f"(d[81]), "+f"(d[82]), "+f"(d[83]), "+f"(d[84]), "+f"(d[85]), "+f"(d[86]), "+f"(d[87]), "+f"(d[88]), "+f"(d[89]), "+f"(d[90]), "+f"(d[91]), "+f"(d[92]), "+f"(d[93]), "+f"(d[94]), "+f"(d[95])
    : "l"(descA), "l"(descB), "r"(scaleD));
}
__device__ __forceinline__ void wgmma_ss_n64_tb(float (&d)[32], uint64_t descA, uint64_t descB, int scaleD) {
  asm volatile("{\n.reg .pred p;\nsetp.ne.b32 p, %34, 0;\n"
    "wgmma.mma_async.sync.aligned.m64n64k16.f32.bf16.bf16 {%0, %1, %2, %3, %4, %5, %6, %7, %8, %9, %10, %11, %12, %13, %14, %15, %16, %17, %18, %19, %20, %21, %22, %23, %24, %25, %26, %27, %28, %29, %30, %31}, %32, %33, p, 1, 1, 0, 1;\n}\n"
    : "+f"(d[0]), "+f"(d[1]), "+f"(d[2]), "+f"(d[3]), "+f"(d[4]), "+f"(d[5]), "+f"(d[6]), "+f"(d[7]), "+f"(d[8]), "+f"(d[9]), "+f"(d[10]), "+f"(d[11]), "+f"(d[12]), "+f"(d[13]), "+f"(d[14]), "+f"(d[15]), "+f"(d[16]), "+f"(d[17]), "+f"(d[18]), "+f"(d[19]), "+f"(d[20]), "+f"(d[21]), "+f"(d[22]), "+f"(d[23]), "+f"(d[24]), "+f"(d[25]), "+f"(d[26]), "+f"(d[27]), "+f"(d[28]), "+f"(d[29]), "+f"(d[30]), "+f"(d[31])
    : "l"(descA), "l"(descB), "r"(scaleD));
}
__device__ __forceinline__ void wgmma_ss_n16_tb(float (&d)[8], uint64_t descA, uint64_t descB, int scaleD) {
  asm volatile("{\n.reg .pred p;\nsetp.ne.b32 p, %10, 0;\n"
    "wgmma.mma_async.sync.aligned.m64n16k16.f32.bf16.bf16 {%0, %1, %2, %3, %4, %5, %6, %7}, %8, %9, p, 1, 1, 0, 1;\n}\n"
    : "+f"(d[0]), "+f"(d[1]), "+f"(d[2]), "+f"(d[3]), "+f"(d[4]), "+f"(d[5]), "+f"(d[6]), "+f"(d[7])
    : "l"(descA), "l"(descB), "r"(scaleD));
}
__device__ __forceinline__ void wgmma_rs_n128(float (&d)[64], uint32_t a0, uint32_t a1, uint32_t a2, uint32_t a3, uint64_t descB, int scaleD) {
  asm volatile("{\n.reg .pred p;\nsetp.ne.b32 p, %69, 0;\n"
    "wgmma.mma_async.sync.aligned.m64n128k16.f32.bf16.bf16 {%0, %1, %2, %3, %4, %5, %6, %7, %8, %9, %10, %11, %12, %13, %14, %15, %16, %17, %18, %19, %20, %21, %22, %23, %24, %25, %26, %27, %28, %29, %30, %31, %32, %33, %34, %35, %36, %37, %38, %39, %40, %41, %42, %43, %44, %45, %46, %47, %48, %49, %50, %51, %52, %53, %54, %55, %56, %57, %58, %59, %60, %61, %62, %63}, {%64, %65, %66, %67}, %68, p, 1, 1, 0;\n}\n"
    : "+f"(d[0]), "+f"(d[1]), "+f"(d[2]), "+f"(d[3]), "+f"(d[4]), "+f"(d[5]), "+f"(d[6]), "+f"(d[7]), "+f"(d[8]), "+f"(d[9]), "+f"(d[10]), "+f"(d[11]), "+f"(d[12]), "+f"(d[13]), "+f"(d[14]), "+f"(d[15]), "+f"(d[16]), "+f"(d[17]), "+f"(d[18]), "+f"(d[19]), "+f"(d[20]), "+f"(d[21]), "+f"(d[22]), "+f"(d[23]), "+f"(d[24]), "+f"(d[25]), "+f"(d[26]), "+f"(d[27]), "+f"(d[28]), "+f"(d[29]), "+f"(d[30]), "+f"(d[31]), "+f"(d[32]), "+f"(d[33]), "+f"(d[34]), "+f"(d[35]), "+f"(d[36]), "+f"(d[37]), "+f"(d[38]), "+f"(d[39]), "+f"(d[40]), "+f"(d[41]), "+f"(d[42]), "+f"(d[43]), "+f"(d[44]), "+f"(d[45]), "+f"(d[46]), "+f"(d[47]), "+f"(d[48]), "+f"(d[49]), "+f"(d[50]), "+f"(d[51]), "+f"(d[52]), "+f"(d[53]), "+f"(d[54]), "+f"(d[55]), "+f"(d[56]), "+f"(d[57]), "+f"(d[58]), "+f"(d[59]), "+f"(d[60]), "+f"(d[61]), "+f"(d[62]), "+f"(d[63])
    : "r"(a0), "r"(a1), "r"(a2), "r"(a3), "l"(descB), "r"(scaleD));
}
__device__ __forceinline__ void wgmma_rs_n64(float (&d)[32], uint32_t a0, uint32_t a1, uint32_t a2, uint32_t a3, uint64_t descB, int scaleD) {
  asm volatile("{\n.reg .pred p;\nsetp.ne.b32 p, %37, 0;\n"
    "wgmma.mma_async.sync.aligned.m64n64k16.f32.bf16.bf16 {%0, %1, %2, %3, %4, %5, %6, %7, %8, %9, %10, %11, %12, %13, %14, %15, %16, %17, %18, %19, %20, %21, %22, %23, %24, %25, %26, %27, %28, %29, %30, %31}, {%32, %33, %34, %35}, %36, p, 1, 1, 0;\n}\n"
    : "+f"(d[0]), "+f"(d[1]), "+f"(d[2]), "+f"(d[3]), "+f"(d[4]), "+f"(d[5]), "+f"(d[6]), "+f"(d[7]), "+f"(d[8]), "+f"(d[9]), "+f"(d[10]), "+f"(d[11]), "+f"(d[12]), "+f"(d[13]), "+f"(d[14]), "+f"(d[15]), "+f"(d[16]), "+f"(d[17]), "+f"(d[18]), "+f"(d[19]), "+f"(d[20]), "+f"(d[21]), "+f"(d[22]), "+f"(d[23]), "+f"(d[24]), "+f"(d[25]), "+f"(d[26]), "+f"(d[27]), "+f"(d[28]), "+f"(d[29]), "+f"(d[30]), "+f"(d[31])
    : "r"(a0), "r"(a1), "r"(a2), "r"(a3), "l"(descB), "r"(scaleD));
}
__device__ __forceinline__ void wgmma_rs_n24_tb(float (&d)[12], uint32_t a0, uint32_t a1, uint32_t a2, uint32_t a3, uint64_t descB, int scaleD) {
  asm volatile("{\n.reg .pred p;\nsetp.ne.b32 p, %17, 0;\n"
    "wgmma.mma_async.sync.aligned.m64n24k16.f32.bf16.bf16 {%0, %1, %2, %3, %4, %5, %6, %7, %8, %9, %10, %11}, {%12, %13, %14, %15}, %16, p, 1, 1, 1;\n}\n"
    : "+f"(d[0]), "+f"(d[1]), "+f"(d[2]), "+f"(d[3]), "+f"(d[4]), "+f"(d[5]), "+f"(d[6]), "+f"(d[7]), "+f"(d[8]), "+f"(d[9]), "+f"(d[10]), "+f"(d[11])
    : "r"(a0), "r"(a1), "r"(a2), "r"(a3), "l"(descB), "r"(scaleD));
}

constexpr int GT = 384;

__device__ __forceinline__ void release_stage(uint32_t bar, bool leader) {
  if (leader) {
    mbar_arrive_cluster(bar, 0);
    mbar_arrive_cluster(bar, 1);
  }
}

__device__ __forceinline__ void ln_row(const bf16* __restrict__ xin, bf16* __restrict__ xout, int l16) {
  const uint4* src = reinterpret_cast<const uint4*>(xin);
  uint4 v[5];
#pragma unroll
  for (int j = 0; j < 5; j++) v[j] = __ldg(src + j * 16 + l16);
  float s0 = 0.f, s1 = 0.f, s2 = 0.f, s3 = 0.f;
#pragma unroll
  for (int j = 0; j < 5; j++) {
    s0 += bf_lo(v[j].x) + bf_hi(v[j].x);
    s1 += bf_lo(v[j].y) + bf_hi(v[j].y);
    s2 += bf_lo(v[j].z) + bf_hi(v[j].z);
    s3 += bf_lo(v[j].w) + bf_hi(v[j].w);
  }
  float mean = (s0 + s1) + (s2 + s3);
#pragma unroll
  for (int o = 1; o < 16; o <<= 1) mean += __shfl_xor_sync(0xffffffffu, mean, o);
  mean *= (1.0f / DM);
  s0 = s1 = s2 = s3 = 0.f;
#pragma unroll
  for (int j = 0; j < 5; j++) {
    float d;
    d = bf_lo(v[j].x) - mean; s0 = fmaf(d, d, s0);
    d = bf_hi(v[j].x) - mean; s1 = fmaf(d, d, s1);
    d = bf_lo(v[j].y) - mean; s2 = fmaf(d, d, s2);
    d = bf_hi(v[j].y) - mean; s3 = fmaf(d, d, s3);
    d = bf_lo(v[j].z) - mean; s0 = fmaf(d, d, s0);
    d = bf_hi(v[j].z) - mean; s1 = fmaf(d, d, s1);
    d = bf_lo(v[j].w) - mean; s2 = fmaf(d, d, s2);
    d = bf_hi(v[j].w) - mean; s3 = fmaf(d, d, s3);
  }
  float sq = (s0 + s1) + (s2 + s3);
#pragma unroll
  for (int o = 1; o < 16; o <<= 1) sq += __shfl_xor_sync(0xffffffffu, sq, o);
  const float var_b = bf16_round(sq * (1.0f / DM));
  const float den = bf16_round(sqrtf(bf16_round(var_b + 1e-5f)));
  const float iv = __frcp_rn(den);
  const float mb = bf16_round(mean);
  uint4* dst = reinterpret_cast<uint4*>(xout);
#pragma unroll
  for (int j = 0; j < 5; j++) {
    uint4 w;
    uint32_t t;
    t = pack_bf16(bf_lo(v[j].x) - mb, bf_hi(v[j].x) - mb); w.x = pack_bf16(bf_lo(t) * iv, bf_hi(t) * iv);
    t = pack_bf16(bf_lo(v[j].y) - mb, bf_hi(v[j].y) - mb); w.y = pack_bf16(bf_lo(t) * iv, bf_hi(t) * iv);
    t = pack_bf16(bf_lo(v[j].z) - mb, bf_hi(v[j].z) - mb); w.z = pack_bf16(bf_lo(t) * iv, bf_hi(t) * iv);
    t = pack_bf16(bf_lo(v[j].w) - mb, bf_hi(v[j].w) - mb); w.w = pack_bf16(bf_lo(t) * iv, bf_hi(t) * iv);
    dst[j * 16 + l16] = w;
  }
}

constexpr int LG_STAGES = 5;
constexpr int QKV_STAGE = 8192 + 4 * 4096;
constexpr int GLU_STAGE = 8192 + 6 * 4096;

template <int WG>
__device__ __forceinline__ void qkv_mainloop(float (&acc)[120], uint32_t sbase, uint32_t sBar, bool leader) {
  constexpr int STAGE_BYTES = QKV_STAGE, NST = LG_STAGES;
  const uint64_t da_base = make_desc(sbase + WG * 4096, 16, 512, 2);
  const uint64_t db_base = make_desc(sbase + 8192, 4096, 1024, 1);
#pragma unroll 1
  for (int r = 0; r < 20 / NST; r++) {
#pragma unroll
    for (int s = 0; s < NST; s++) {
      mbar_wait(sBar + 8 * s, r & 1);
      wgmma_fence();
#pragma unroll
      for (int ks = 0; ks < 2; ks++)
        wgmma_ss_n240_tb(acc, da_base + (uint64_t)((s * STAGE_BYTES + ks * 32) >> 4), db_base + (uint64_t)((s * STAGE_BYTES + ks * 2048) >> 4), 1);
      wgmma_commit();
      wgmma_wait<1>();
      release_stage(sBar + 8 * (NST + (s + NST - 1) % NST), leader && (s > 0 || r > 0));
    }
  }
}
template <int WG>
__device__ __forceinline__ void glu_mainloop(float (&accg)[96], float (&accu)[96], uint32_t sbase, uint32_t sBar, bool leader) {
  constexpr int STAGE_BYTES = GLU_STAGE, NST = LG_STAGES;
  const uint64_t da_base = make_desc(sbase + WG * 4096, 16, 512, 2);
  const uint64_t db_base = make_desc(sbase + 8192, 4096, 1024, 1);
#pragma unroll 1
  for (int r = 0; r < 20 / NST; r++) {
#pragma unroll
    for (int s = 0; s < NST; s++) {
      mbar_wait(sBar + 8 * s, r & 1);
      wgmma_fence();
#pragma unroll
      for (int ks = 0; ks < 2; ks++) {
        const uint64_t da = da_base + (uint64_t)((s * STAGE_BYTES + ks * 32) >> 4);
        wgmma_ss_n192_tb(accg, da, db_base + (uint64_t)((s * STAGE_BYTES + ks * 2048) >> 4), 1);
        wgmma_ss_n192_tb(accu, da, db_base + (uint64_t)((s * STAGE_BYTES + 3 * 4096 + ks * 2048) >> 4), 1);
      }
      wgmma_commit();
      wgmma_wait<1>();
      release_stage(sBar + 8 * (NST + (s + NST - 1) % NST), leader && (s > 0 || r > 0));
    }
  }
}
constexpr int RG_STAGE_BYTES = 16384 + 8192 + 2048;
template <int NKB, int NST, int WG>
__device__ __forceinline__ void res_mainloop(float (&acc0)[32], float (&acc1)[8], uint32_t sbase, uint32_t sBar, bool leader) {
  const uint64_t da_base = make_desc(sbase + WG * 8192, 16, 1024, 1);
  const uint64_t db0_base = make_desc(sbase + 16384, 8192, 1024, 1);
  const uint64_t db1_base = make_desc(sbase + 16384 + 8192, 2048, 256, 3);
#pragma unroll 1
  for (int r = 0; r < NKB / NST; r++) {
#pragma unroll
    for (int s = 0; s < NST; s++) {
      const uint64_t so = (uint64_t)(s * (RG_STAGE_BYTES >> 4));
      mbar_wait(sBar + 8 * s, r & 1);
      wgmma_fence();
#pragma unroll
      for (int ks = 0; ks < 4; ks++) {
        wgmma_ss_n64_tb(acc0, da_base + so + ks * 2, db0_base + so + ks * 128, 1);
        wgmma_ss_n16_tb(acc1, da_base + so + ks * 2, db1_base + so + ks * 32, 1);
      }
      wgmma_commit();
      wgmma_wait<1>();
      release_stage(sBar + 8 * (NST + (s + NST - 1) % NST), leader && (s > 0 || r > 0));
    }
  }
}

constexpr int KA_SMEM = LG_STAGES * QKV_STAGE + 128 + 1024;

__global__ void __launch_bounds__(GT, 1)
qkv_kernel(const __grid_constant__ CUtensorMap tmA, const __grid_constant__ CUtensorMap tmB, const bf16* __restrict__ x) {
  constexpr int STAGE_BYTES = QKV_STAGE, NST = LG_STAGES, NKB = 20;
  extern __shared__ uint8_t smem_raw[];
  const uint32_t sbase = (smem_u32(smem_raw) + 1023u) & ~1023u;
  const uint32_t sBar = sbase + NST * STAGE_BYTES;
  const int tid = threadIdx.x, warp = tid >> 5, lane = tid & 31;
  const int rank = blockIdx.x & 1;
  const int pair = blockIdx.x >> 1;
  const int n_blk = pair & 7;
  const int m_blk = (pair >> 3) * 2 + rank;
  TS(0, 0);
  if (tid == 256) {
    prefetch_tmap(&tmA);
    prefetch_tmap(&tmB);
  }
  if (tid == 0) {
    for (int s = 0; s < NST; s++) {
      mbar_init(sBar + 8 * s, 1);
      mbar_init(sBar + 8 * (NST + s), 4);
    }
    fence_mbar_init();
    if (blockIdx.x < 32) g_flag[16 + blockIdx.x] = 0;
  }
  pdl_launch();
  cluster_sync_all();

  if (warp >= 8) {
    asm volatile("setmaxnreg.dec.sync.aligned.u32 40;");
    if (tid == 256) {
      auto issue_b = [&](int kb) {
        const int s = kb % NST;
        const uint32_t full = sBar + 8 * s;
        mbar_expect_tx(full, STAGE_BYTES);
        const uint32_t dst = sbase + s * STAGE_BYTES + 8192;
#pragma unroll
        for (int j = 0; j < 2; j++) {
          const int sl = rank * 2 + j;
          tma_load_2d_mc(dst + sl * 4096, &tmB, n_blk * 240 + sl * 64, kb * 32, full, (uint16_t)3);
        }
      };
      for (int kb = 0; kb < NST; kb++) issue_b(kb);
      flag_wait(&g_flag[m_blk], 8);
      fence_proxy_async_all();
      for (int kb = 0; kb < NKB; kb++) {
        const int s = kb % NST;
        if (kb >= NST) {
          mbar_wait(sBar + 8 * (NST + s), ((kb / NST) & 1) ^ 1);
          issue_b(kb);
        }
        tma_load_2d(sbase + s * STAGE_BYTES, &tmA, kb * 32, m_blk * 128, sBar + 8 * s);
      }
    }
  } else {
    asm volatile("setmaxnreg.inc.sync.aligned.u32 232;");
    const int wg = __shfl_sync(0xffffffffu, warp >> 2, 0);
    const int wwarp = warp & 3;
    {
      const int row = m_blk * 128 + n_blk * 16 + warp * 2 + (lane >> 4);
      ln_row(x + (size_t)row * DM, g_xn + (size_t)row * DM, lane & 15);
      named_bar_sync(3, 256);
      if (tid == 0) flag_signal(&g_flag[m_blk]);
    }
    TS(0, 1);
    mbar_wait(sBar, 0);
    TS(0, 3);
    float acc[120];
#pragma unroll
    for (int i = 0; i < 120; i++) acc[i] = 0.f;
    if (wg == 0) qkv_mainloop<0>(acc, sbase, sBar, (tid & 127) == 0);
    else qkv_mainloop<1>(acc, sbase, sBar, (tid & 127) == 0);
    wgmma_wait<0>();
    fence_regs(acc);
    TS(0, 4);
    named_bar_sync(3, 256);
    const int g = lane >> 2, c4 = lane & 3;
    const uint32_t stg = sbase + wg * (12 * 3072) + (wwarp * 2) * 384 + g * 16;
    const int hbase = n_blk * 12;
#pragma unroll
    for (int j = 0; j < 30; j++) {
      const int cb = (j * 8) % 20;
      const int hb = (j * 8) / 20;
      int d = cb + c4 * 2;
      int hl = hb;
      if (cb == 16 && c4 >= 2) { d -= 20; hl += 1; }
      const uint32_t a0 = stg + hl * 3072 + (d >> 3) * 128 + (d & 7) * 2;
      const int hg = hbase + hl;
      const float sc = hg < 32 ? ATT_SCALE_LOG2E : 1.0f;
      st_shared_b32(a0, pack_bf16(acc[4 * j] * sc, acc[4 * j + 1] * sc));
      st_shared_b32(a0 + 384, pack_bf16(acc[4 * j + 2] * sc, acc[4 * j + 3] * sc));
      if (d == 18) {
        const uint32_t pad0 = hg < 32 ? 0u : (hg < 64 ? 0x3f803f80u : 0x00003f80u);
        const uint32_t pad1 = (hg >= 32 && hg < 64) ? 0x00003f80u : 0u;
        st_shared_v2(a0 + 4, pad0, pad1);
        st_shared_v2(a0 + 388, pad0, pad1);
      }
    }
    fence_proxy_async();
    named_bar_sync(1 + wg, 128);
    if ((tid & 127) < 12) {
      const int hl = tid & 127;
      bf16* dst = g_img + (size_t)(hbase + hl) * IMG_HEAD_ELEMS + (size_t)(m_blk * 16 + wg * 8) * 192;
      bulk_s2g(dst, sbase + wg * (12 * 3072) + hl * 3072, 3072);
      bulk_commit();
      bulk_wait_read();
    }
  }
  __syncwarp();
  TS(0, 5);
  cluster_sync_relaxed();
  TS(0, 6);
}

constexpr int KC_NST1 = 5, KC_NST3 = 6;
constexpr int KC_STAGING = 160 * 1024;
constexpr int KC_BAR = KC_STAGING + 48 * 1024;
constexpr int KC_CS = KC_BAR + 512;
constexpr int KC_SMEM = KC_CS + 1536 + 1024;

__global__ void __launch_bounds__(GT, 1)
mlp_kernel(const __grid_constant__ CUtensorMap tmO, const __grid_constant__ CUtensorMap tmWo64, const __grid_constant__ CUtensorMap tmWo16,
           const __grid_constant__ CUtensorMap tmH, const __grid_constant__ CUtensorMap tmWg, const __grid_constant__ CUtensorMap tmWu,
           const __grid_constant__ CUtensorMap tmHHs, const __grid_constant__ CUtensorMap tmHH, const __grid_constant__ CUtensorMap tmWd64,
           const __grid_constant__ CUtensorMap tmWd16, const __grid_constant__ CUtensorMap tmHs, const __grid_constant__ CUtensorMap tmOut,
           const bf16* __restrict__ x) {
  extern __shared__ uint8_t smem_raw[];
  const uint32_t sbase = (smem_u32(smem_raw) + 1023u) & ~1023u;
  const uint32_t bar1 = sbase + KC_BAR;
  const uint32_t bar2 = bar1 + 128;
  const uint32_t bar3 = bar2 + 128;
  const uint32_t barD = bar3 + 128;
  const int tid = threadIdx.x, warp = tid >> 5, lane = tid & 31;
  const int rank = blockIdx.x & 1;
  const int pair = blockIdx.x >> 1;
  const int j_blk = pair & 7;
  const int m_blk = (pair >> 3) * 2 + rank;
  const int n0 = j_blk * 80;
  TS(2, 0);
  if (tid == 256) {
    prefetch_tmap(&tmO); prefetch_tmap(&tmWo64); prefetch_tmap(&tmWo16); prefetch_tmap(&tmH); prefetch_tmap(&tmWg);
    prefetch_tmap(&tmWu); prefetch_tmap(&tmHHs); prefetch_tmap(&tmHH); prefetch_tmap(&tmWd64); prefetch_tmap(&tmWd16);
    prefetch_tmap(&tmHs); prefetch_tmap(&tmOut);
  }
  if (tid == 0) {
    for (int s = 0; s < 5; s++) {
      mbar_init(bar1 + 8 * s, 1); mbar_init(bar1 + 8 * (5 + s), 4);
      mbar_init(bar2 + 8 * s, 1); mbar_init(bar2 + 8 * (5 + s), 4);
    }
    for (int s = 0; s < 6; s++) { mbar_init(bar3 + 8 * s, 1); mbar_init(bar3 + 8 * (6 + s), 4); }
    mbar_init(barD, 4); mbar_init(barD + 8, 4);
    fence_mbar_init();
  }
  cluster_sync_all();

  if (warp >= 8) {
    asm volatile("setmaxnreg.dec.sync.aligned.u32 40;");
    if (tid == 256) {
      auto issue_b80 = [&](const CUtensorMap* t64, const CUtensorMap* t16, uint32_t bars, int nst, int kb) {
        const int s = kb % nst;
        const uint32_t full = bars + 8 * s;
        const uint32_t st = sbase + s * RG_STAGE_BYTES;
        mbar_expect_tx(full, RG_STAGE_BYTES);
        tma_load_2d_mc(st + 16384 + rank * 4096, t64, n0, kb * 64 + rank * 32, full, (uint16_t)3);
        tma_load_2d_mc(st + 16384 + 8192 + rank * 1024, t16, n0 + 64, kb * 64 + rank * 32, full, (uint16_t)3);
      };
      for (int kb = 0; kb < KC_NST1; kb++) issue_b80(&tmWo64, &tmWo16, bar1, KC_NST1, kb);
      pdl_wait();
      for (int kb = 0; kb < 10; kb++) {
        const int s = kb % KC_NST1;
        if (kb >= KC_NST1) {
          mbar_wait(bar1 + 8 * (KC_NST1 + s), ((kb / KC_NST1) & 1) ^ 1);
          issue_b80(&tmWo64, &tmWo16, bar1, KC_NST1, kb);
        }
        tma_load_2d(sbase + s * RG_STAGE_BYTES, &tmO, kb * 64, m_blk * 128, bar1 + 8 * s);
      }
      auto issue_bglu = [&](int kb) {
        const int s = kb % LG_STAGES;
        const uint32_t full = bar2 + 8 * s;
        mbar_expect_tx(full, GLU_STAGE);
        const uint32_t dst = sbase + s * GLU_STAGE + 8192;
#pragma unroll
        for (int j = 0; j < 3; j++)
          tma_load_2d_mc(dst + (rank * 3 + j) * 4096, rank == 0 ? &tmWg : &tmWu, j_blk * 192 + j * 64, kb * 32, full, (uint16_t)3);
      };
      mbar_wait(barD, 0);
      for (int kb = 0; kb < LG_STAGES; kb++) issue_bglu(kb);
      flag_wait(&g_flag[16 + m_blk], 16);
      fence_proxy_async_all();
      for (int kb = 0; kb < 20; kb++) {
        const int s = kb % LG_STAGES;
        if (kb >= LG_STAGES) {
          mbar_wait(bar2 + 8 * (LG_STAGES + s), ((kb / LG_STAGES) & 1) ^ 1);
          issue_bglu(kb);
        }
        tma_load_2d(sbase + s * GLU_STAGE, &tmH, kb * 32, m_blk * 128, bar2 + 8 * s);
      }
      mbar_wait(barD + 8, 0);
      for (int kb = 0; kb < KC_NST3; kb++) issue_b80(&tmWd64, &tmWd16, bar3, KC_NST3, kb);
      flag_wait(&g_flag[32 + m_blk], 16);
      fence_proxy_async_all();
      for (int kb = 0; kb < 24; kb++) {
        const int s = kb % KC_NST3;
        if (kb >= KC_NST3) {
          mbar_wait(bar3 + 8 * (KC_NST3 + s), ((kb / KC_NST3) & 1) ^ 1);
          issue_b80(&tmWd64, &tmWd16, bar3, KC_NST3, kb);
        }
        tma_load_2d(sbase + s * RG_STAGE_BYTES, &tmHH, kb * 64, m_blk * 128, bar3 + 8 * s);
      }
    }
  } else {
    asm volatile("setmaxnreg.inc.sync.aligned.u32 232;");
    const int wg = __shfl_sync(0xffffffffu, warp >> 2, 0);
    const int wwarp = warp & 3;
    const int g = lane >> 2, c4 = lane & 3;
    const int row0 = m_blk * 128 + wg * 64 + wwarp * 16 + g;
    const bool leader = (tid & 127) == 0;
    const uint32_t stg80_base = sbase + KC_STAGING + wg * 24576;
    const uint32_t stg80 = stg80_base + (wwarp * 16 + g) * 160 + c4 * 4;
    {
      uint32_t res[20];
#pragma unroll
      for (int j = 0; j < 10; j++) {
        res[2 * j] = __ldg(reinterpret_cast<const uint32_t*>(x + (size_t)row0 * DM + n0 + j * 8 + c4 * 2));
        res[2 * j + 1] = __ldg(reinterpret_cast<const uint32_t*>(x + (size_t)(row0 + 8) * DM + n0 + j * 8 + c4 * 2));
      }
      float acc0[32], acc1[8];
#pragma unroll
      for (int i = 0; i < 32; i++) acc0[i] = 0.f;
#pragma unroll
      for (int i = 0; i < 8; i++) acc1[i] = 0.f;
      TS(2, 1);
      if (wg == 0) res_mainloop<10, KC_NST1, 0>(acc0, acc1, sbase, bar1, leader);
      else res_mainloop<10, KC_NST1, 1>(acc0, acc1, sbase, bar1, leader);
      wgmma_wait<0>();
      fence_regs(acc0); fence_regs(acc1);
      release_stage(barD, leader);
      TS(2, 4);
      float sum0 = 0.f, sum1 = 0.f;
#pragma unroll
      for (int j = 0; j < 10; j++) {
        const uint32_t a01 = j < 8 ? pack_bf16(acc0[4 * j], acc0[4 * j + 1]) : pack_bf16(acc1[4 * (j - 8)], acc1[4 * (j - 8) + 1]);
        const uint32_t a23 = j < 8 ? pack_bf16(acc0[4 * j + 2], acc0[4 * j + 3]) : pack_bf16(acc1[4 * (j - 8) + 2], acc1[4 * (j - 8) + 3]);
        res[2 * j] = pack_bf16(bf_lo(res[2 * j]) + bf_lo(a01), bf_hi(res[2 * j]) + bf_hi(a01));
        res[2 * j + 1] = pack_bf16(bf_lo(res[2 * j + 1]) + bf_lo(a23), bf_hi(res[2 * j + 1]) + bf_hi(a23));
        st_shared_b32(stg80 + j * 16, res[2 * j]);
        st_shared_b32(stg80 + 8 * 160 + j * 16, res[2 * j + 1]);
        sum0 += bf_lo(res[2 * j]) + bf_hi(res[2 * j]);
        sum1 += bf_lo(res[2 * j + 1]) + bf_hi(res[2 * j + 1]);
      }
      sum0 += __shfl_xor_sync(0xffffffffu, sum0, 1); sum1 += __shfl_xor_sync(0xffffffffu, sum1, 1);
      sum0 += __shfl_xor_sync(0xffffffffu, sum0, 2); sum1 += __shfl_xor_sync(0xffffffffu, sum1, 2);
      const float mu0 = sum0 * (1.0f / 80.0f), mu1 = sum1 * (1.0f / 80.0f);
      float q0 = 0.f, q1 = 0.f;
#pragma unroll
      for (int j = 0; j < 10; j++) {
        float d;
        d = bf_lo(res[2 * j]) - mu0; q0 = fmaf(d, d, q0);
        d = bf_hi(res[2 * j]) - mu0; q0 = fmaf(d, d, q0);
        d = bf_lo(res[2 * j + 1]) - mu1; q1 = fmaf(d, d, q1);
        d = bf_hi(res[2 * j + 1]) - mu1; q1 = fmaf(d, d, q1);
      }
      q0 += __shfl_xor_sync(0xffffffffu, q0, 1); q1 += __shfl_xor_sync(0xffffffffu, q1, 1);
      q0 += __shfl_xor_sync(0xffffffffu, q0, 2); q1 += __shfl_xor_sync(0xffffffffu, q1, 2);
      if (c4 == 0) {
        g_stats[row0 * 8 + j_blk] = make_float2(mu0, q0);
        g_stats[(row0 + 8) * 8 + j_blk] = make_float2(mu1, q1);
      }
      fence_proxy_async();
      named_bar_sync(1 + wg, 128);
      if (leader) {
        tma_store_2d(&tmHs, stg80_base, n0, m_blk * 128 + wg * 64);
        bulk_commit();
        bulk_wait_all();
        fence_proxy_async_all();
        flag_signal(&g_flag[16 + m_blk]);
      }
      TS(2, 5);
    }
    {
      pdl_wait();
      {
        float* cs_s = reinterpret_cast<float*>(smem_raw + (sbase - smem_u32(smem_raw)) + KC_CS);
        for (int i = tid; i < 384; i += 256) cs_s[i] = g_cs[(i >= 192 ? FF - 192 : 0) + j_blk * 192 + i];
        named_bar_sync(3, 256);
      }
      flag_wait(&g_flag[16 + m_blk], 16);
      float mb[2], iv[2];
#pragma unroll
      for (int h = 0; h < 2; h++) {
        const float4* sp = reinterpret_cast<const float4*>(g_stats + (row0 + 8 * h) * 8);
        const float4 p0 = sp[0], p1 = sp[1], p2 = sp[2], p3 = sp[3];
        const float mean = (((p0.x + p0.z) + (p1.x + p1.z)) + ((p2.x + p2.z) + (p3.x + p3.z))) * 0.125f;
        float m2 = ((p0.y + p0.w) + (p1.y + p1.w)) + ((p2.y + p2.w) + (p3.y + p3.w));
        float dd = 0.f, d;
        d = p0.x - mean; dd = fmaf(d, d, dd); d = p0.z - mean; dd = fmaf(d, d, dd);
        d = p1.x - mean; dd = fmaf(d, d, dd); d = p1.z - mean; dd = fmaf(d, d, dd);
        d = p2.x - mean; dd = fmaf(d, d, dd); d = p2.z - mean; dd = fmaf(d, d, dd);
        d = p3.x - mean; dd = fmaf(d, d, dd); d = p3.z - mean; dd = fmaf(d, d, dd);
        m2 = fmaf(dd, 80.0f, m2);
        const float var_b = bf16_round(m2 * (1.0f / DM));
        const float den = bf16_round(sqrtf(bf16_round(var_b + 1e-5f)));
        iv[h] = __frcp_rn(den);
        mb[h] = bf16_round(mean);
      }
      float accg[96], accu[96];
#pragma unroll
      for (int i = 0; i < 96; i++) { accg[i] = 0.f; accu[i] = 0.f; }
      TS(3, 3);
      if (wg == 0) glu_mainloop<0>(accg, accu, sbase, bar2, leader);
      else glu_mainloop<1>(accg, accu, sbase, bar2, leader);
      wgmma_wait<0>();
      fence_regs(accg); fence_regs(accu);
      release_stage(barD + 8, leader);
      TS(3, 4);
      const uint32_t stg = sbase + KC_STAGING + wg * 24576 + (wwarp * 16 + g) * 128 + c4 * 4;
      const float* csg = reinterpret_cast<const float*>(smem_raw + (sbase - smem_u32(smem_raw)) + KC_CS) + c4 * 2;
#pragma unroll
      for (int j = 0; j < 24; j++) {
        const float2 cg = *reinterpret_cast<const float2*>(csg + j * 8);
        const float2 cu = *reinterpret_cast<const float2*>(csg + 192 + j * 8);
        uint32_t pk[2];
#pragma unroll
        for (int h = 0; h < 2; h++) {
          const uint32_t gp = pack_bf16(fmaf(-mb[h], cg.x, accg[4 * j + 2 * h]) * iv[h], fmaf(-mb[h], cg.y, accg[4 * j + 2 * h + 1]) * iv[h]);
          const uint32_t up = pack_bf16(fmaf(-mb[h], cu.x, accu[4 * j + 2 * h]) * iv[h], fmaf(-mb[h], cu.y, accu[4 * j + 2 * h + 1]) * iv[h]);
          const float g0 = bf_lo(gp), g1 = bf_hi(gp);
          const float r0 = (g0 * (g0 > 0.f ? 1.f : 0.f)) * bf_lo(up);
          const float r1 = (g1 * (g1 > 0.f ? 1.f : 0.f)) * bf_hi(up);
          pk[h] = pack_bf16(r0, r1);
        }
        const uint32_t a0 = stg + (j >> 3) * 8192 + (((j & 7) ^ g) << 4);
        st_shared_b32(a0, pk[0]);
        st_shared_b32(a0 + 1024, pk[1]);
      }
      fence_proxy_async();
      named_bar_sync(1 + wg, 128);
      if (leader) {
#pragma unroll
        for (int sl = 0; sl < 3; sl++)
          tma_store_2d(&tmHHs, sbase + KC_STAGING + wg * 24576 + sl * 8192, j_blk * 192 + sl * 64, m_blk * 128 + wg * 64);
        bulk_commit();
        bulk_wait_all();
        fence_proxy_async_all();
        flag_signal(&g_flag[32 + m_blk]);
      }
      TS(3, 5);
    }
    {
      uint32_t res[20];
#pragma unroll
      for (int j = 0; j < 10; j++) {
        res[2 * j] = *reinterpret_cast<const uint32_t*>(g_h + (size_t)row0 * DM + n0 + j * 8 + c4 * 2);
        res[2 * j + 1] = *reinterpret_cast<const uint32_t*>(g_h + (size_t)(row0 + 8) * DM + n0 + j * 8 + c4 * 2);
      }
      float acc0[32], acc1[8];
#pragma unroll
      for (int i = 0; i < 32; i++) acc0[i] = 0.f;
#pragma unroll
      for (int i = 0; i < 8; i++) acc1[i] = 0.f;
      mbar_wait(bar3, 0);
      TS(4, 3);
      if (wg == 0) res_mainloop<24, KC_NST3, 0>(acc0, acc1, sbase, bar3, leader);
      else res_mainloop<24, KC_NST3, 1>(acc0, acc1, sbase, bar3, leader);
      wgmma_wait<0>();
      fence_regs(acc0); fence_regs(acc1);
      TS(4, 4);
#pragma unroll
      for (int j = 0; j < 10; j++) {
        const uint32_t a01 = j < 8 ? pack_bf16(acc0[4 * j], acc0[4 * j + 1]) : pack_bf16(acc1[4 * (j - 8)], acc1[4 * (j - 8) + 1]);
        const uint32_t a23 = j < 8 ? pack_bf16(acc0[4 * j + 2], acc0[4 * j + 3]) : pack_bf16(acc1[4 * (j - 8) + 2], acc1[4 * (j - 8) + 3]);
        st_shared_b32(stg80 + j * 16, pack_bf16(bf_lo(res[2 * j]) + bf_lo(a01), bf_hi(res[2 * j]) + bf_hi(a01)));
        st_shared_b32(stg80 + 8 * 160 + j * 16, pack_bf16(bf_lo(res[2 * j + 1]) + bf_lo(a23), bf_hi(res[2 * j + 1]) + bf_hi(a23)));
      }
      fence_proxy_async();
      named_bar_sync(1 + wg, 128);
      if (leader) {
        tma_store_2d(&tmOut, stg80_base, n0, m_blk * 128 + wg * 64);
        bulk_commit();
        bulk_wait_read();
      }
      TS(4, 5);
    }
  }
  __syncwarp();
  cluster_sync_relaxed();
  TS(4, 6);
}

constexpr int AT_THREADS = 512;
constexpr int AT_WGS = AT_THREADS / 128;
#define AT_CHUNK_MASK 3
#define AT_STAGGER 0
constexpr int AT_KV_BYTES = IMG_HEAD_ELEMS * 2;
constexpr int AT_SMEM = 2 * AT_KV_BYTES + 256 + 1024;
constexpr int AT_CHUNKS = 8;

__device__ __forceinline__ float exp2_poly(float x) {
  const float u = __saturatef(fmaf(x, 1.0f / 64.0f, 62.0f / 64.0f));
  const float MAGIC = 12582912.0f - 62.0f;
  const float r = fmaf(u, 64.0f, MAGIC);
  const float q = MAGIC - r;
  const float fr = fmaf(u, 64.0f, q);
  float p = fmaf(fr, 0.009570102207362652f, 0.05591785907745361f);
  p = fmaf(p, fr, 0.240247443318367f);
  p = fmaf(p, fr, 0.6931217908859253f);
  p = fmaf(p, fr, 0.9999992847442627f);
  return __uint_as_float(__float_as_uint(p) + (__float_as_uint(r) << 23));
}
#define AT_VARIANT 0
#define AT_POLY_MOD 8
__device__ __forceinline__ bool use_poly(int e) {
  return (e % AT_POLY_MOD) == 1;
}

struct AttnState {
  uint32_t qa0, qa1, qa2, qa3, qa4, qa5;
  float M0, M1;
};

__device__ __forceinline__ bool attn_exp_fast(const float (&s)[32], uint32_t (&p)[16]) {
#pragma unroll
  for (int j = 0; j < 16; j++) {
    const float e0 = use_poly(2 * j) ? exp2_poly(s[2 * j]) : ex2(s[2 * j]);
    const float e1 = use_poly(2 * j + 1) ? exp2_poly(s[2 * j + 1]) : ex2(s[2 * j + 1]);
    p[j] = pack_bf16(e0, e1);
  }
  uint32_t acc_or = 0;
#pragma unroll
  for (int j = 0; j < 16; j++) acc_or |= p[j];
  return __any_sync(0xffffffffu, (acc_or & 0x40004000u) != 0);
}
__device__ __forceinline__ void attn_exp_exact(const float (&s)[32], uint32_t (&p)[16], float (&o)[12], AttnState& st, bool first, int c4) {
  float mx0 = fmaxf(s[0], s[1]), mx1 = fmaxf(s[2], s[3]);
#pragma unroll
  for (int j = 1; j < 8; j++) {
    mx0 = fmaxf(mx0, fmaxf(s[4 * j], s[4 * j + 1]));
    mx1 = fmaxf(mx1, fmaxf(s[4 * j + 2], s[4 * j + 3]));
  }
  mx0 = fmaxf(mx0, __shfl_xor_sync(0xffffffffu, mx0, 1));
  mx1 = fmaxf(mx1, __shfl_xor_sync(0xffffffffu, mx1, 1));
  mx0 = fmaxf(mx0, __shfl_xor_sync(0xffffffffu, mx0, 2));
  mx1 = fmaxf(mx1, __shfl_xor_sync(0xffffffffu, mx1, 2));
  float d0 = mx0 + 7.0f, d1 = mx1 + 7.0f;
  if (!first) { d0 = fmaxf(d0, 0.f); d1 = fmaxf(d1, 0.f); }
  const float T0 = st.M0 + d0, T1 = st.M1 + d1;
  const float h0 = bf16_round(T0), h1 = bf16_round(T1);
  const float i0 = bf16_round(T0 - h0), i1 = bf16_round(T1 - h1);
  const float l0 = bf16_round((T0 - h0) - i0), l1 = bf16_round((T1 - h1) - i1);
  const float N0 = (h0 + i0) + l0, N1 = (h1 + i1) + l1;
  d0 = N0 - st.M0; d1 = N1 - st.M1;
  st.M0 = N0; st.M1 = N1;
  if (c4 == 2) { st.qa4 = pack_bf16(-h0, -i0); st.qa5 = pack_bf16(-h1, -i1); }
  if (c4 == 3) { st.qa4 = pack_bf16(-l0, 0.f); st.qa5 = pack_bf16(-l1, 0.f); }
  if (!first) {
    const float al0 = ex2(-d0), al1 = ex2(-d1);
#pragma unroll
    for (int j = 0; j < 3; j++) {
      o[4 * j] *= al0; o[4 * j + 1] *= al0;
      o[4 * j + 2] *= al1; o[4 * j + 3] *= al1;
    }
  }
#pragma unroll
  for (int j = 0; j < 8; j++) {
    p[2 * j] = pack_bf16(ex2(s[4 * j] - d0), ex2(s[4 * j + 1] - d0));
    p[2 * j + 1] = pack_bf16(ex2(s[4 * j + 2] - d1), ex2(s[4 * j + 3] - d1));
  }
}
__device__ __forceinline__ void attn_step(float (&s)[32], const uint32_t (&pp)[16], uint32_t (&pn)[16], float (&o)[12], AttnState& st,
                                          uint32_t k_addr, uint32_t v_addr_prev, int keep, int c4, int wgdbg = 0, int tdbg = 0) {
  PH(wgdbg, tdbg, 0);
  const uint64_t dk = make_desc(k_addr, 128, 384, 0);
  const uint64_t dv_prev = make_desc(v_addr_prev, 384, 128, 0);
  wgmma_fence();
  wgmma_rs_n64(s, st.qa0, st.qa1, st.qa2, st.qa3, dk, 0);
  wgmma_rs_n64(s, st.qa4, st.qa5, 0u, 0u, dk + 16, 1);
  wgmma_commit();
#pragma unroll
  for (int kk = 0; kk < 4; kk++) wgmma_rs_n24_tb(o, pp[4 * kk], pp[4 * kk + 1], pp[4 * kk + 2], pp[4 * kk + 3], dv_prev + kk * 48, kk == 0 ? keep : 1);
  wgmma_commit();
  wgmma_wait<1>();
  fence_regs(s);
  PH(wgdbg, tdbg, 1);
  const bool redo = attn_exp_fast(s, pn);
  PH(wgdbg, tdbg, 2);
  wgmma_wait<0>();
  fence_regs(o);
  if (redo) attn_exp_exact(s, pn, o, st, false, c4);
}

__global__ void __launch_bounds__(AT_THREADS, 1) attn_kernel(const bf16* __restrict__ wo, const bf16* __restrict__ wgt, const bf16* __restrict__ wup, const bf16* __restrict__ wdn) {
  extern __shared__ uint8_t smem_raw[];
  const uint32_t sbase = (smem_u32(smem_raw) + 1023u) & ~1023u;
  const uint32_t sK = sbase, sV = sbase + AT_KV_BYTES;
  const uint32_t sBar = sV + AT_KV_BYTES;
  const int tid = threadIdx.x, warp = tid >> 5, lane = tid & 31;
  const int head = blockIdx.x >> 2, quarter = blockIdx.x & 3;
  if (blockIdx.x >= 128) {
    pdl_launch();
    const int b = blockIdx.x - 128;
    const bf16* w = (b >> 1) ? wup : wgt;
    const int cgrp = tid % 96, rgrp = tid / 96;
    float acc[8];
#pragma unroll
    for (int i = 0; i < 8; i++) acc[i] = 0.f;
    float* red = reinterpret_cast<float*>(smem_raw);
    if (rgrp < 5) {
      const uint4* src = reinterpret_cast<const uint4*>(w + (size_t)(rgrp * 128) * FF + (b & 1) * 768 + cgrp * 8);
#pragma unroll 8
      for (int r = 0; r < 128; r++) {
        const uint4 v = __ldg(src + (size_t)r * (FF / 8));
        acc[0] += bf_lo(v.x); acc[1] += bf_hi(v.x); acc[2] += bf_lo(v.y); acc[3] += bf_hi(v.y);
        acc[4] += bf_lo(v.z); acc[5] += bf_hi(v.z); acc[6] += bf_lo(v.w); acc[7] += bf_hi(v.w);
      }
#pragma unroll
      for (int i = 0; i < 8; i++) red[rgrp * 768 + cgrp * 8 + i] = acc[i];
    }
    __syncthreads();
    pdl_wait();
    for (int c = tid; c < 768; c += AT_THREADS)
      g_cs[(b >> 1) * FF + (b & 1) * 768 + c] = ((red[c] + red[768 + c]) + (red[1536 + c] + red[2304 + c])) + red[3072 + c];
    if (b == 0 && tid < 16) g_flag[tid] = 0;
    return;
  }
  TS(1, 0);
  if (tid == 0) {
    for (int i = 0; i < AT_CHUNKS; i++) mbar_init(sBar + 8 * i, 1);
    fence_mbar_init();
  }
  pdl_launch();
  if (tid == 32) {
    prefetch_l2(reinterpret_cast<const uint8_t*>(wo) + blockIdx.x * 6400, 6400);
    prefetch_l2(reinterpret_cast<const uint8_t*>(wgt) + blockIdx.x * 15360, 15360);
    prefetch_l2(reinterpret_cast<const uint8_t*>(wup) + blockIdx.x * 15360, 15360);
    prefetch_l2(reinterpret_cast<const uint8_t*>(wdn) + blockIdx.x * 15360, 15360);
  }
  __syncthreads();
  TS(1, 1);
  pdl_wait();
  TS(1, 2);
  if (tid == 0) {
    const uint8_t* kg = reinterpret_cast<const uint8_t*>(g_img + (size_t)(32 + head) * IMG_HEAD_ELEMS);
    const uint8_t* vg = reinterpret_cast<const uint8_t*>(g_img + (size_t)(64 + head) * IMG_HEAD_ELEMS);
    constexpr int CB = AT_KV_BYTES / AT_CHUNKS;
    for (int i = 0; i < AT_CHUNKS; i++) {
      mbar_expect_tx(sBar + 8 * i, 2 * CB);
      bulk_g2s(sK + i * CB, kg + i * CB, CB, sBar + 8 * i);
      bulk_g2s(sV + i * CB, vg + i * CB, CB, sBar + 8 * i);
    }
  }
  const int wg = warp >> 2, wwarp = warp & 3;
  const int g = lane >> 2, c4 = lane & 3;
  const uint64_t dk_base = make_desc(sK, 128, 384, 0);
  const uint64_t dv_base = make_desc(sV, 384, 128, 0);

#pragma unroll 1
  for (int rep = 0; rep < 8 / AT_WGS; rep++) {
    const int row0 = quarter * 512 + (rep * AT_WGS + wg) * 64 + wwarp * 16 + g;
    AttnState st;
    {
      const bf16* q0 = g_img + (size_t)head * IMG_HEAD_ELEMS + (size_t)(row0 >> 3) * 192 + g * 8 + c4 * 2;
      const bf16* q1 = q0 + 192;
      st.qa0 = *reinterpret_cast<const uint32_t*>(q0);
      st.qa1 = *reinterpret_cast<const uint32_t*>(q1);
      st.qa2 = *reinterpret_cast<const uint32_t*>(q0 + 64);
      st.qa3 = *reinterpret_cast<const uint32_t*>(q1 + 64);
      st.qa4 = *reinterpret_cast<const uint32_t*>(q0 + 128);
      st.qa5 = *reinterpret_cast<const uint32_t*>(q1 + 128);
    }
    float o[12];
    float s[32];
    uint32_t pa[16], pb[16];
    st.M0 = st.M1 = 0.f;
    if (rep == 0) mbar_wait(sBar, 0);
    wgmma_fence();
    wgmma_rs_n64(s, st.qa0, st.qa1, st.qa2, st.qa3, dk_base, 0);
    wgmma_rs_n64(s, st.qa4, st.qa5, 0u, 0u, dk_base + 16, 1);
    wgmma_commit();
    wgmma_wait<0>();
    fence_regs(s);
    attn_exp_exact(s, pa, o, st, true, c4);
    attn_step(s, pa, pb, o, st, sK + 3072, sV, 0, c4);
#pragma unroll 1
    for (int tt = 1; tt < 16; tt++) {
      if (rep == 0 && !(tt & 1)) mbar_wait(sBar + 8 * (tt >> 1), 0);
      attn_step(s, pb, pa, o, st, sK + tt * 6144, sV + tt * 6144 - 3072, 1, c4, wg, rep * 32 + tt * 2);
      attn_step(s, pa, pb, o, st, sK + tt * 6144 + 3072, sV + tt * 6144, 1, c4, wg, rep * 32 + tt * 2 + 1);
    }
    wgmma_fence();
#pragma unroll
    for (int kk = 0; kk < 4; kk++) wgmma_rs_n24_tb(o, pb[4 * kk], pb[4 * kk + 1], pb[4 * kk + 2], pb[4 * kk + 3], dv_base + 31 * 192 + kk * 48, 1);
    wgmma_commit();
    wgmma_wait<0>();
    fence_regs(o);
    TS(1, 3 + rep);
    const float l0 = __shfl_sync(0xffffffffu, o[8], (lane & ~3) | 2);
    const float l1 = __shfl_sync(0xffffffffu, o[10], (lane & ~3) | 2);
    const float i0 = 1.0f / l0, i1 = 1.0f / l1;
    bf16* o0 = g_o + (size_t)row0 * DM + head * DH;
    bf16* o1 = o0 + 8 * DM;
#pragma unroll
    for (int j = 0; j < 3; j++) {
      if (j < 2 || c4 < 2) {
        *reinterpret_cast<uint32_t*>(o0 + j * 8 + c4 * 2) = pack_bf16(o[4 * j] * i0, o[4 * j + 1] * i0);
        *reinterpret_cast<uint32_t*>(o1 + j * 8 + c4 * 2) = pack_bf16(o[4 * j + 2] * i1, o[4 * j + 3] * i1);
      }
    }
  }
}

typedef CUresult (*EncodeTiledFn)(CUtensorMap*, CUtensorMapDataType, cuuint32_t, void*, const cuuint64_t*, const cuuint64_t*,
                                  const cuuint32_t*, const cuuint32_t*, CUtensorMapInterleave, CUtensorMapSwizzle,
                                  CUtensorMapL2promotion, CUtensorMapFloatOOBfill);

static void make_map(EncodeTiledFn fn, CUtensorMap* tm, const void* ptr, uint64_t rows, uint64_t cols, uint32_t box_rows,
                     uint32_t box_cols, CUtensorMapSwizzle sw) {
  cuuint64_t dims[2] = {cols, rows};
  cuuint64_t strides[1] = {cols * 2};
  cuuint32_t box[2] = {box_cols, box_rows};
  cuuint32_t es[2] = {1, 1};
  fn(tm, CU_TENSOR_MAP_DATA_TYPE_BFLOAT16, 2, const_cast<void*>(ptr), dims, strides, box, es, CU_TENSOR_MAP_INTERLEAVE_NONE, sw,
     CU_TENSOR_MAP_L2_PROMOTION_L2_256B, CU_TENSOR_MAP_FLOAT_OOB_FILL_NONE);
}

template <typename... KArgs, typename... Args>
static void launch(void (*kern)(KArgs...), int grid, int block, int smem, int cluster, bool pdl, Args... args) {
  cudaLaunchConfig_t cfg = {};
  cfg.gridDim = dim3(grid);
  cfg.blockDim = dim3(block);
  cfg.dynamicSmemBytes = smem;
  cfg.stream = cudaStreamPerThread;
  cudaLaunchAttribute at[2];
  int n = 0;
  if (cluster > 1) {
    at[n].id = cudaLaunchAttributeClusterDimension;
    at[n].val.clusterDim.x = cluster; at[n].val.clusterDim.y = 1; at[n].val.clusterDim.z = 1;
    n++;
  }
  if (pdl) {
    at[n].id = cudaLaunchAttributeProgrammaticStreamSerialization;
    at[n].val.programmaticStreamSerializationAllowed = 1;
    n++;
  }
  cfg.attrs = at;
  cfg.numAttrs = n;
  cudaLaunchKernelEx(&cfg, kern, KArgs(args)...);
}

extern "C" void kernel_launch(void* const* d_in, const int* in_sizes, int n_in, void* d_out, int out_size) {
  const bf16* x = (const bf16*)d_in[0];
  const bf16* wqkv = (const bf16*)d_in[1];
  const bf16* wo = (const bf16*)d_in[2];
  const bf16* wg = (const bf16*)d_in[4];
  const bf16* wu = (const bf16*)d_in[5];
  const bf16* wd = (const bf16*)d_in[6];
  bf16* out = (bf16*)d_out;

  static EncodeTiledFn enc = nullptr;
  static void *p_o = nullptr, *p_h = nullptr, *p_hh = nullptr, *p_xn = nullptr;
  if (!enc) {
    void* fn = nullptr;
    cudaDriverEntryPointQueryResult qr;
    cudaGetDriverEntryPoint("cuTensorMapEncodeTiled", &fn, cudaEnableDefault, &qr);
    enc = (EncodeTiledFn)fn;
    cudaGetSymbolAddress(&p_o, g_o);
    cudaGetSymbolAddress(&p_h, g_h);
    cudaGetSymbolAddress(&p_hh, g_hh);
    cudaGetSymbolAddress(&p_xn, g_xn);
    cudaFuncSetAttribute(qkv_kernel, cudaFuncAttributeMaxDynamicSharedMemorySize, KA_SMEM);
    cudaFuncSetAttribute(mlp_kernel, cudaFuncAttributeMaxDynamicSharedMemorySize, KC_SMEM);
    cudaFuncSetAttribute(attn_kernel, cudaFuncAttributeMaxDynamicSharedMemorySize, AT_SMEM);
  }
  CUtensorMap tm_wqkv, tm_wg, tm_wu, tm_wo64, tm_wo16, tm_wd64, tm_wd16, tm_o, tm_h, tm_hh, tm_hhs, tm_xn, tm_hs, tm_out;
  make_map(enc, &tm_wqkv, wqkv, DM, 3 * DM, 32, 64, CU_TENSOR_MAP_SWIZZLE_128B);
  make_map(enc, &tm_wg, wg, DM, FF, 32, 64, CU_TENSOR_MAP_SWIZZLE_128B);
  make_map(enc, &tm_wu, wu, DM, FF, 32, 64, CU_TENSOR_MAP_SWIZZLE_128B);
  make_map(enc, &tm_wo64, wo, DM, DM, 32, 64, CU_TENSOR_MAP_SWIZZLE_128B);
  make_map(enc, &tm_wo16, wo, DM, DM, 32, 16, CU_TENSOR_MAP_SWIZZLE_32B);
  make_map(enc, &tm_wd64, wd, FF, DM, 32, 64, CU_TENSOR_MAP_SWIZZLE_128B);
  make_map(enc, &tm_wd16, wd, FF, DM, 32, 16, CU_TENSOR_MAP_SWIZZLE_32B);
  make_map(enc, &tm_o, p_o, SEQ, DM, 128, 64, CU_TENSOR_MAP_SWIZZLE_128B);
  make_map(enc, &tm_h, p_h, SEQ, DM, 128, 32, CU_TENSOR_MAP_SWIZZLE_64B);
  make_map(enc, &tm_hh, p_hh, SEQ, FF, 128, 64, CU_TENSOR_MAP_SWIZZLE_128B);
  make_map(enc, &tm_hhs, p_hh, SEQ, FF, 64, 64, CU_TENSOR_MAP_SWIZZLE_128B);
  make_map(enc, &tm_xn, p_xn, SEQ, DM, 128, 32, CU_TENSOR_MAP_SWIZZLE_64B);
  make_map(enc, &tm_hs, p_h, SEQ, DM, 64, 80, CU_TENSOR_MAP_SWIZZLE_NONE);
  make_map(enc, &tm_out, out, SEQ, DM, 64, 80, CU_TENSOR_MAP_SWIZZLE_NONE);

  launch(qkv_kernel, 128, GT, KA_SMEM, 2, false, tm_xn, tm_wqkv, x);
  launch(attn_kernel, 132, AT_THREADS, AT_SMEM, 1, true, wo, wg, wu, wd);
  launch(mlp_kernel, 128, GT, KC_SMEM, 2, true, tm_o, tm_wo64, tm_wo16, tm_h, tm_wg, tm_wu, tm_hhs, tm_hh, tm_wd64, tm_wd16, tm_hs, tm_out, x);
}
```

```cpp
#include <cuda_runtime.h>
#include <cuda_bf16.h>
#include <cuda.h>
#include <stdint.h>

typedef __nv_bfloat16 bf16;

constexpr int SEQ = 2048, DM = 640, NH = 32, DH = 20, FF = 1536;
constexpr float ATT_SCALE_LOG2E = 0.22360679774997896f * 1.4426950408889634f;
constexpr int IMG_HEAD_ELEMS = (SEQ / 8) * 192;

__device__ __align__(1024) bf16 g_img[3 * NH * IMG_HEAD_ELEMS];
__device__ __align__(1024) bf16 g_o[SEQ * DM];
__device__ __align__(1024) bf16 g_h[SEQ * DM];
__device__ __align__(1024) bf16 g_xn[SEQ * DM];
__device__ float2 g_stats[SEQ * 8];
__device__ float g_cs[2 * FF];
__device__ int g_flag[3 * 16];
__device__ __align__(1024) bf16 g_hh[SEQ * FF];

#define TS(k, i)
#define PH(w, t, i)
__device__ __forceinline__ uint32_t smem_u32(const void* p) { return (uint32_t)__cvta_generic_to_shared(p); }
__device__ __forceinline__ void mbar_init(uint32_t bar, uint32_t cnt) {
  asm volatile("mbarrier.init.shared::cta.b64 [%0], %1;" ::"r"(bar), "r"(cnt) : "memory");
}
__device__ __forceinline__ void mbar_expect_tx(uint32_t bar, uint32_t bytes) {
  asm volatile("mbarrier.arrive.expect_tx.shared::cta.b64 _, [%0], %1;" ::"r"(bar), "r"(bytes) : "memory");
}
__device__ __forceinline__ void mbar_arrive(uint32_t bar) {
  asm volatile("mbarrier.arrive.shared::cta.b64 _, [%0];" ::"r"(bar) : "memory");
}
__device__ __forceinline__ void mbar_arrive_cluster(uint32_t bar, uint32_t cta) {
  asm volatile(
      "{\n.reg .b32 r;\nmapa.shared::cluster.u32 r, %0, %1;\n"
      "mbarrier.arrive.shared::cluster.b64 _, [r];\n}\n" ::"r"(bar), "r"(cta)
      : "memory");
}
__device__ __forceinline__ void mbar_wait(uint32_t bar, uint32_t parity) {
  asm volatile(
      "{\n.reg .pred p;\nLAB_WAIT:\n"
      "mbarrier.try_wait.parity.shared::cta.b64 p, [%0], %1;\n"
      "@p bra DONE;\nbra LAB_WAIT;\nDONE:\n}\n" ::"r"(bar), "r"(parity)
      : "memory");
}
__device__ __forceinline__ void mbar_wait_cluster(uint32_t bar, uint32_t parity) {
  asm volatile(
      "{\n.reg .pred p;\nLAB_WAIT:\n"
      "mbarrier.try_wait.parity.acquire.cluster.shared::cta.b64 p, [%0], %1;\n"
      "@p bra DONE;\nbra LAB_WAIT;\nDONE:\n}\n" ::"r"(bar), "r"(parity)
      : "memory");
}
__device__ __forceinline__ void fence_mbar_init() { asm volatile("fence.mbarrier_init.release.cluster;" ::: "memory"); }
__device__ __forceinline__ void fence_proxy_async() { asm volatile("fence.proxy.async.shared::cta;" ::: "memory"); }
__device__ __forceinline__ void cluster_sync_all() {
  asm volatile("barrier.cluster.arrive.release.aligned;\nbarrier.cluster.wait.acquire.aligned;" ::: "memory");
}
__device__ __forceinline__ void cluster_sync_relaxed() {
  asm volatile("barrier.cluster.arrive.relaxed.aligned;\nbarrier.cluster.wait.aligned;" ::: "memory");
}
__device__ __forceinline__ void named_bar_sync(int id, int n) { asm volatile("bar.sync %0, %1;" ::"r"(id), "r"(n) : "memory"); }
__device__ __forceinline__ bool wg_any(bool pred, int id) {
  uint32_t r;
  asm volatile("{\n.reg .pred p, q;\nsetp.ne.u32 p, %1, 0;\nbar.red.or.pred q, %2, 128, p;\nselp.u32 %0, 1, 0, q;\n}\n" : "=r"(r) : "r"((uint32_t)pred), "r"(id) : "memory");
  return r != 0;
}
__device__ __forceinline__ void fence_proxy_async_all() { asm volatile("fence.proxy.async;" ::: "memory"); }
__device__ __forceinline__ void flag_signal(int* f) {
  __threadfence();
  atomicAdd(f, 1);
}
__device__ __forceinline__ void flag_wait(const int* f, int target) {
  int v;
  unsigned spins = 0;
  do {
    asm volatile("ld.acquire.gpu.global.s32 %0, [%1];" : "=r"(v) : "l"(f) : "memory");
    if (++spins > (1u << 24)) __trap();
  } while (v < target);
}
__device__ __forceinline__ void pdl_launch() { asm volatile("griddepcontrol.launch_dependents;" ::: "memory"); }
__device__ __forceinline__ void pdl_wait() { asm volatile("griddepcontrol.wait;" ::: "memory"); }

__device__ __forceinline__ void tma_load_2d(uint32_t dst, const CUtensorMap* tm, int c0, int c1, uint32_t bar) {
  asm volatile(
      "cp.async.bulk.tensor.2d.shared::cluster.global.mbarrier::complete_tx::bytes [%0], [%1, {%3, %4}], [%2];" ::"r"(dst),
      "l"((uint64_t)tm), "r"(bar), "r"(c0), "r"(c1)
      : "memory");
}
__device__ __forceinline__ void tma_load_2d_mc(uint32_t dst, const CUtensorMap* tm, int c0, int c1, uint32_t bar, uint16_t mask) {
  asm volatile(
      "cp.async.bulk.tensor.2d.shared::cluster.global.mbarrier::complete_tx::bytes.multicast::cluster [%0], [%1, {%3, %4}], [%2], %5;" ::"r"(dst),
      "l"((uint64_t)tm), "r"(bar), "r"(c0), "r"(c1), "h"(mask)
      : "memory");
}
__device__ __forceinline__ void bulk_g2s(uint32_t dst, const void* src, uint32_t bytes, uint32_t bar) {
  asm volatile("cp.async.bulk.shared::cluster.global.mbarrier::complete_tx::bytes [%0], [%1], %2, [%3];" ::"r"(dst), "l"(src),
               "r"(bytes), "r"(bar)
               : "memory");
}
__device__ __forceinline__ void bulk_s2g(void* dst, uint32_t src, uint32_t bytes) {
  asm volatile("cp.async.bulk.global.shared::cta.bulk_group [%0], [%1], %2;" ::"l"(dst), "r"(src), "r"(bytes) : "memory");
}
__device__ __forceinline__ void tma_store_2d(const CUtensorMap* tm, uint32_t src, int c0, int c1) {
  asm volatile("cp.async.bulk.tensor.2d.global.shared::cta.bulk_group [%0, {%2, %3}], [%1];" ::"l"((uint64_t)tm), "r"(src), "r"(c0), "r"(c1) : "memory");
}
__device__ __forceinline__ void bulk_commit() { asm volatile("cp.async.bulk.commit_group;" ::: "memory"); }
__device__ __forceinline__ void bulk_wait_read() { asm volatile("cp.async.bulk.wait_group.read 0;" ::: "memory"); }
__device__ __forceinline__ void prefetch_l2(const void* p, uint32_t bytes) {
  asm volatile("cp.async.bulk.prefetch.L2.global [%0], %1;" ::"l"(p), "r"(bytes) : "memory");
}
__device__ __forceinline__ void bulk_wait_all() { asm volatile("cp.async.bulk.wait_group 0;" ::: "memory"); }
__device__ __forceinline__ void st_shared_b32(uint32_t addr, uint32_t v) { asm volatile("st.shared.b32 [%0], %1;" ::"r"(addr), "r"(v) : "memory"); }
__device__ __forceinline__ void st_shared_v2(uint32_t addr, uint32_t a, uint32_t b) { asm volatile("st.shared.v2.b32 [%0], {%1, %2};" ::"r"(addr), "r"(a), "r"(b) : "memory"); }
__device__ __forceinline__ void prefetch_tmap(const CUtensorMap* tm) {
  asm volatile("prefetch.tensormap [%0];" ::"l"((uint64_t)tm) : "memory");
}
__device__ __forceinline__ void wgmma_fence() { asm volatile("wgmma.fence.sync.aligned;" ::: "memory"); }
__device__ __forceinline__ void wgmma_commit() { asm volatile("wgmma.commit_group.sync.aligned;" ::: "memory"); }
template <int N>
__device__ __forceinline__ void wgmma_wait() { asm volatile("wgmma.wait_group.sync.aligned %0;" ::"n"(N) : "memory"); }

template <int N>
__device__ __forceinline__ void fence_regs(float (&r)[N]) {
#pragma unroll
  for (int i = 0; i < N; i++) asm volatile("" : "+f"(r[i])::"memory");
}
template <int N>
__device__ __forceinline__ void fence_regs(uint32_t (&r)[N]) {
#pragma unroll
  for (int i = 0; i < N; i++) asm volatile("" : "+r"(r[i])::"memory");
}
__device__ __forceinline__ uint64_t make_desc(uint32_t addr, uint32_t lbo, uint32_t sbo, uint32_t layout) {
  return (uint64_t)((addr & 0x3FFFF) >> 4) | ((uint64_t)((lbo & 0x3FFFF) >> 4) << 16) | ((uint64_t)((sbo & 0x3FFFF) >> 4) << 32) |
         ((uint64_t)layout << 62);
}
__device__ __forceinline__ uint32_t pack_bf16(float lo, float hi) {
  uint32_t r;
  asm("cvt.rn.bf16x2.f32 %0, %1, %2;" : "=r"(r) : "f"(hi), "f"(lo));
  return r;
}
__device__ __forceinline__ float bf16_round(float x) { return __bfloat162float(__float2bfloat16_rn(x)); }
__device__ __forceinline__ float bf_lo(uint32_t u) { return __uint_as_float(u << 16); }
__device__ __forceinline__ float bf_hi(uint32_t u) { return __uint_as_float(u & 0xffff0000u); }
__device__ __forceinline__ float ex2(float x) {
  float y;
  asm("ex2.approx.ftz.f32 %0, %1;" : "=f"(y) : "f"(x));
  return y;
}

__device__ __forceinline__ void wgmma_ss_n240_tb(float (&d)[120], uint64_t descA, uint64_t descB, int scaleD) {
  asm volatile("{\n.reg .pred p;\nsetp.ne.b32 p, %122, 0;\n"
    "wgmma.mma_async.sync.aligned.m64n240k16.f32.bf16.bf16 {%0, %1, %2, %3, %4, %5, %6, %7, %8, %9, %10, %11, %12, %13, %14, %15, %16, %17, %18, %19, %20, %21, %22, %23, %24, %25, %26, %27, %28, %29, %30, %31, %32, %33, %34, %35, %36, %37, %38, %39, %40, %41, %42, %43, %44, %45, %46, %47, %48, %49, %50, %51, %52, %53, %54, %55, %56, %57, %58, %59, %60, %61, %62, %63, %64, %65, %66, %67, %68, %69, %70, %71, %72, %73, %74, %75, %76, %77, %78, %79, %80, %81, %82, %83, %84, %85, %86, %87, %88, %89, %90, %91, %92, %93, %94, %95, %96, %97, %98, %99, %100, %101, %102, %103, %104, %105, %106, %107, %108, %109, %110, %111, %112, %113, %114, %115, %116, %117, %118, %119}, %120, %121, p, 1, 1, 0, 1;\n}\n"
    : "+f"(d[0]), "+f"(d[1]), "+f"(d[2]), "+f"(d[3]), "+f"(d[4]), "+f"(d[5]), "+f"(d[6]), "+f"(d[7]), "+f"(d[8]), "+f"(d[9]), "+f"(d[10]), "+f"(d[11]), "+f"(d[12]), "+f"(d[13]), "+f"(d[14]), "+f"(d[15]), "+f"(d[16]), "+f"(d[17]), "+f"(d[18]), "+f"(d[19]), "+f"(d[20]), "+f"(d[21]), "+f"(d[22]), "+f"(d[23]), "+f"(d[24]), "+f"(d[25]), "+f"(d[26]), "+f"(d[27]), "+f"(d[28]), "+f"(d[29]), "+f"(d[30]), "+f"(d[31]), "+f"(d[32]), "+f"(d[33]), "+f"(d[34]), "+f"(d[35]), "+f"(d[36]), "+f"(d[37]), "+f"(d[38]), "+f"(d[39]), "+f"(d[40]), "+f"(d[41]), "+f"(d[42]), "+f"(d[43]), "+f"(d[44]), "+f"(d[45]), "+f"(d[46]), "+f"(d[47]), "+f"(d[48]), "+f"(d[49]), "+f"(d[50]), "+f"(d[51]), "+f"(d[52]), "+f"(d[53]), "+f"(d[54]), "+f"(d[55]), "+f"(d[56]), "+f"(d[57]), "+f"(d[58]), "+f"(d[59]), "+f"(d[60]), "+f"(d[61]), "+f"(d[62]), "+f"(d[63]), "+f"(d[64]), "+f"(d[65]), "+f"(d[66]), "+f"(d[67]), "+f"(d[68]), "+f"(d[69]), "+f"(d[70]), "+f"(d[71]), "+f"(d[72]), "+f"(d[73]), "+f"(d[74]), "+f"(d[75]), "+f"(d[76]), "+f"(d[77]), "+f"(d[78]), "+f"(d[79]), "+f"(d[80]), "+f"(d[81]), "+f"(d[82]), "+f"(d[83]), "+f"(d[84]), "+f"(d[85]), "+f"(d[86]), "+f"(d[87]), "+f"(d[88]), "+f"(d[89]), "+f"(d[90]), "+f"(d[91]), "+f"(d[92]), "+f"(d[93]), "+f"(d[94]), "+f"(d[95]), "+f"(d[96]), "+f"(d[97]), "+f"(d[98]), "+f"(d[99]), "+f"(d[100]), "+f"(d[101]), "+f"(d[102]), "+f"(d[103]), "+f"(d[104]), "+f"(d[105]), "+f"(d[106]), "+f"(d[107]), "+f"(d[108]), "+f"(d[109]), "+f"(d[110]), "+f"(d[111]), "+f"(d[112]), "+f"(d[113]), "+f"(d[114]), "+f"(d[115]), "+f"(d[116]), "+f"(d[117]), "+f"(d[118]), "+f"(d[119])
    : "l"(descA), "l"(descB), "r"(scaleD));
}
__device__ __forceinline__ void wgmma_ss_n192_tb(float (&d)[96], uint64_t descA, uint64_t descB, int scaleD) {
  asm volatile("{\n.reg .pred p;\nsetp.ne.b32 p, %98, 0;\n"
    "wgmma.mma_async.sync.aligned.m64n192k16.f32.bf16.bf16 {%0, %1, %2, %3, %4, %5, %6, %7, %8, %9, %10, %11, %12, %13, %14, %15, %16, %17, %18, %19, %20, %21, %22, %23, %24, %25, %26, %27, %28, %29, %30, %31, %32, %33, %34, %35, %36, %37, %38, %39, %40, %41, %42, %43, %44, %45, %46, %47, %48, %49, %50, %51, %52, %53, %54, %55, %56, %57, %58, %59, %60, %61, %62, %63, %64, %65, %66, %67, %68, %69, %70, %71, %72, %73, %74, %75, %76, %77, %78, %79, %80, %81, %82, %83, %84, %85, %86, %87, %88, %89, %90, %91, %92, %93, %94, %95}, %96, %97, p, 1, 1, 0, 1;\n}\n"
    : "+f"(d[0]), "+f"(d[1]), "+f"(d[2]), "+f"(d[3]), "+f"(d[4]), "+f"(d[5]), "+f"(d[6]), "+f"(d[7]), "+f"(d[8]), "+f"(d[9]), "+f"(d[10]), "+f"(d[11]), "+f"(d[12]), "+f"(d[13]), "+f"(d[14]), "+f"(d[15]), "+f"(d[16]), "+f"(d[17]), "+f"(d[18]), "+f"(d[19]), "+f"(d[20]), "+f"(d[21]), "+f"(d[22]), "+f"(d[23]), "+f"(d[24]), "+f"(d[25]), "+f"(d[26]), "+f"(d[27]), "+f"(d[28]), "+f"(d[29]), "+f"(d[30]), "+f"(d[31]), "+f"(d[32]), "+f"(d[33]), "+f"(d[34]), "+f"(d[35]), "+f"(d[36]), "+f"(d[37]), "+f"(d[38]), "+f"(d[39]), "+f"(d[40]), "+f"(d[41]), "+f"(d[42]), "+f"(d[43]), "+f"(d[44]), "+f"(d[45]), "+f"(d[46]), "+f"(d[47]), "+f"(d[48]), "+f"(d[49]), "+f"(d[50]), "+f"(d[51]), "+f"(d[52]), "+f"(d[53]), "+f"(d[54]), "+f"(d[55]), "+f"(d[56]), "+f"(d[57]), "+f"(d[58]), "+f"(d[59]), "+f"(d[60]), "+f"(d[61]), "+f"(d[62]), "+f"(d[63]), "+f"(d[64]), "+f"(d[65]), "+f"(d[66]), "+f"(d[67]), "+f"(d[68]), "+f"(d[69]), "+f"(d[70]), "+f"(d[71]), "+f"(d[72]), "+f"(d[73]), "+f"(d[74]), "+f"(d[75]), "+f"(d[76]), "+f"(d[77]), "+f"(d[78]), "+f"(d[79]), "+f"(d[80]), "+f"(d[81]), "+f"(d[82]), "+f"(d[83]), "+f"(d[84]), "+f"(d[85]), "+f"(d[86]), "+f"(d[87]), "+f"(d[88]), "+f"(d[89]), "+f"(d[90]), "+f"(d[91]), "+f"(d[92]), "+f"(d[93]), "+f"(d[94]), "+f"(d[95])
    : "l"(descA), "l"(descB), "r"(scaleD));
}
__device__ __forceinline__ void wgmma_ss_n64_tb(float (&d)[32], uint64_t descA, uint64_t descB, int scaleD) {
  asm volatile("{\n.reg .pred p;\nsetp.ne.b32 p, %34, 0;\n"
    "wgmma.mma_async.sync.aligned.m64n64k16.f32.bf16.bf16 {%0, %1, %2, %3, %4, %5, %6, %7, %8, %9, %10, %11, %12, %13, %14, %15, %16, %17, %18, %19, %20, %21, %22, %23, %24, %25, %26, %27, %28, %29, %30, %31}, %32, %33, p, 1, 1, 0, 1;\n}\n"
    : "+f"(d[0]), "+f"(d[1]), "+f"(d[2]), "+f"(d[3]), "+f"(d[4]), "+f"(d[5]), "+f"(d[6]), "+f"(d[7]), "+f"(d[8]), "+f"(d[9]), "+f"(d[10]), "+f"(d[11]), "+f"(d[12]), "+f"(d[13]), "+f"(d[14]), "+f"(d[15]), "+f"(d[16]), "+f"(d[17]), "+f"(d[18]), "+f"(d[19]), "+f"(d[20]), "+f"(d[21]), "+f"(d[22]), "+f"(d[23]), "+f"(d[24]), "+f"(d[25]), "+f"(d[26]), "+f"(d[27]), "+f"(d[28]), "+f"(d[29]), "+f"(d[30]), "+f"(d[31])
    : "l"(descA), "l"(descB), "r"(scaleD));
}
__device__ __forceinline__ void wgmma_ss_n16_tb(float (&d)[8], uint64_t descA, uint64_t descB, int scaleD) {
  asm volatile("{\n.reg .pred p;\nsetp.ne.b32 p, %10, 0;\n"
    "wgmma.mma_async.sync.aligned.m64n16k16.f32.bf16.bf16 {%0, %1, %2, %3, %4, %5, %6, %7}, %8, %9, p, 1, 1, 0, 1;\n}\n"
    : "+f"(d[0]), "+f"(d[1]), "+f"(d[2]), "+f"(d[3]), "+f"(d[4]), "+f"(d[5]), "+f"(d[6]), "+f"(d[7])
    : "l"(descA), "l"(descB), "r"(scaleD));
}
__device__ __forceinline__ void wgmma_rs_n128(float (&d)[64], uint32_t a0, uint32_t a1, uint32_t a2, uint32_t a3, uint64_t descB, int scaleD) {
  asm volatile("{\n.reg .pred p;\nsetp.ne.b32 p, %69, 0;\n"
    "wgmma.mma_async.sync.aligned.m64n128k16.f32.bf16.bf16 {%0, %1, %2, %3, %4, %5, %6, %7, %8, %9, %10, %11, %12, %13, %14, %15, %16, %17, %18, %19, %20, %21, %22, %23, %24, %25, %26, %27, %28, %29, %30, %31, %32, %33, %34, %35, %36, %37, %38, %39, %40, %41, %42, %43, %44, %45, %46, %47, %48, %49, %50, %51, %52, %53, %54, %55, %56, %57, %58, %59, %60, %61, %62, %63}, {%64, %65, %66, %67}, %68, p, 1, 1, 0;\n}\n"
    : "+f"(d[0]), "+f"(d[1]), "+f"(d[2]), "+f"(d[3]), "+f"(d[4]), "+f"(d[5]), "+f"(d[6]), "+f"(d[7]), "+f"(d[8]), "+f"(d[9]), "+f"(d[10]), "+f"(d[11]), "+f"(d[12]), "+f"(d[13]), "+f"(d[14]), "+f"(d[15]), "+f"(d[16]), "+f"(d[17]), "+f"(d[18]), "+f"(d[19]), "+f"(d[20]), "+f"(d[21]), "+f"(d[22]), "+f"(d[23]), "+f"(d[24]), "+f"(d[25]), "+f"(d[26]), "+f"(d[27]), "+f"(d[28]), "+f"(d[29]), "+f"(d[30]), "+f"(d[31]), "+f"(d[32]), "+f"(d[33]), "+f"(d[34]), "+f"(d[35]), "+f"(d[36]), "+f"(d[37]), "+f"(d[38]), "+f"(d[39]), "+f"(d[40]), "+f"(d[41]), "+f"(d[42]), "+f"(d[43]), "+f"(d[44]), "+f"(d[45]), "+f"(d[46]), "+f"(d[47]), "+f"(d[48]), "+f"(d[49]), "+f"(d[50]), "+f"(d[51]), "+f"(d[52]), "+f"(d[53]), "+f"(d[54]), "+f"(d[55]), "+f"(d[56]), "+f"(d[57]), "+f"(d[58]), "+f"(d[59]), "+f"(d[60]), "+f"(d[61]), "+f"(d[62]), "+f"(d[63])
    : "r"(a0), "r"(a1), "r"(a2), "r"(a3), "l"(descB), "r"(scaleD));
}
__device__ __forceinline__ void wgmma_rs_n64(float (&d)[32], uint32_t a0, uint32_t a1, uint32_t a2, uint32_t a3, uint64_t descB, int scaleD) {
  asm volatile("{\n.reg .pred p;\nsetp.ne.b32 p, %37, 0;\n"
    "wgmma.mma_async.sync.aligned.m64n64k16.f32.bf16.bf16 {%0, %1, %2, %3, %4, %5, %6, %7, %8, %9, %10, %11, %12, %13, %14, %15, %16, %17, %18, %19, %20, %21, %22, %23, %24, %25, %26, %27, %28, %29, %30, %31}, {%32, %33, %34, %35}, %36, p, 1, 1, 0;\n}\n"
    : "+f"(d[0]), "+f"(d[1]), "+f"(d[2]), "+f"(d[3]), "+f"(d[4]), "+f"(d[5]), "+f"(d[6]), "+f"(d[7]), "+f"(d[8]), "+f"(d[9]), "+f"(d[10]), "+f"(d[11]), "+f"(d[12]), "+f"(d[13]), "+f"(d[14]), "+f"(d[15]), "+f"(d[16]), "+f"(d[17]), "+f"(d[18]), "+f"(d[19]), "+f"(d[20]), "+f"(d[21]), "+f"(d[22]), "+f"(d[23]), "+f"(d[24]), "+f"(d[25]), "+f"(d[26]), "+f"(d[27]), "+f"(d[28]), "+f"(d[29]), "+f"(d[30]), "+f"(d[31])
    : "r"(a0), "r"(a1), "r"(a2), "r"(a3), "l"(descB), "r"(scaleD));
}
__device__ __forceinline__ void wgmma_rs_n24_tb(float (&d)[12], uint32_t a0, uint32_t a1, uint32_t a2, uint32_t a3, uint64_t descB, int scaleD) {
  asm volatile("{\n.reg .pred p;\nsetp.ne.b32 p, %17, 0;\n"
    "wgmma.mma_async.sync.aligned.m64n24k16.f32.bf16.bf16 {%0, %1, %2, %3, %4, %5, %6, %7, %8, %9, %10, %11}, {%12, %13, %14, %15}, %16, p, 1, 1, 1;\n}\n"
    : "+f"(d[0]), "+f"(d[1]), "+f"(d[2]), "+f"(d[3]), "+f"(d[4]), "+f"(d[5]), "+f"(d[6]), "+f"(d[7]), "+f"(d[8]), "+f"(d[9]), "+f"(d[10]), "+f"(d[11])
    : "r"(a0), "r"(a1), "r"(a2), "r"(a3), "l"(descB), "r"(scaleD));
}

constexpr int GT = 384;

__device__ __forceinline__ void release_stage(uint32_t bar, bool leader) {
  if (leader) {
    mbar_arrive_cluster(bar, 0);
    mbar_arrive_cluster(bar, 1);
  }
}

__device__ __forceinline__ void ln_row(const bf16* __restrict__ xin, bf16* __restrict__ xout, int l16) {
  const uint4* src = reinterpret_cast<const uint4*>(xin);
  uint4 v[5];
#pragma unroll
  for (int j = 0; j < 5; j++) v[j] = __ldg(src + j * 16 + l16);
  float s0 = 0.f, s1 = 0.f, s2 = 0.f, s3 = 0.f;
#pragma unroll
  for (int j = 0; j < 5; j++) {
    s0 += bf_lo(v[j].x) + bf_hi(v[j].x);
    s1 += bf_lo(v[j].y) + bf_hi(v[j].y);
    s2 += bf_lo(v[j].z) + bf_hi(v[j].z);
    s3 += bf_lo(v[j].w) + bf_hi(v[j].w);
  }
  float mean = (s0 + s1) + (s2 + s3);
#pragma unroll
  for (int o = 1; o < 16; o <<= 1) mean += __shfl_xor_sync(0xffffffffu, mean, o);
  mean *= (1.0f / DM);
  s0 = s1 = s2 = s3 = 0.f;
#pragma unroll
  for (int j = 0; j < 5; j++) {
    float d;
    d = bf_lo(v[j].x) - mean; s0 = fmaf(d, d, s0);
    d = bf_hi(v[j].x) - mean; s1 = fmaf(d, d, s1);
    d = bf_lo(v[j].y) - mean; s2 = fmaf(d, d, s2);
    d = bf_hi(v[j].y) - mean; s3 = fmaf(d, d, s3);
    d = bf_lo(v[j].z) - mean; s0 = fmaf(d, d, s0);
    d = bf_hi(v[j].z) - mean; s1 = fmaf(d, d, s1);
    d = bf_lo(v[j].w) - mean; s2 = fmaf(d, d, s2);
    d = bf_hi(v[j].w) - mean; s3 = fmaf(d, d, s3);
  }
  float sq = (s0 + s1) + (s2 + s3);
#pragma unroll
  for (int o = 1; o < 16; o <<= 1) sq += __shfl_xor_sync(0xffffffffu, sq, o);
  const float var_b = bf16_round(sq * (1.0f / DM));
  const float den = bf16_round(sqrtf(bf16_round(var_b + 1e-5f)));
  const float iv = __frcp_rn(den);
  const float mb = bf16_round(mean);
  uint4* dst = reinterpret_cast<uint4*>(xout);
#pragma unroll
  for (int j = 0; j < 5; j++) {
    uint4 w;
    uint32_t t;
    t = pack_bf16(bf_lo(v[j].x) - mb, bf_hi(v[j].x) - mb); w.x = pack_bf16(bf_lo(t) * iv, bf_hi(t) * iv);
    t = pack_bf16(bf_lo(v[j].y) - mb, bf_hi(v[j].y) - mb); w.y = pack_bf16(bf_lo(t) * iv, bf_hi(t) * iv);
    t = pack_bf16(bf_lo(v[j].z) - mb, bf_hi(v[j].z) - mb); w.z = pack_bf16(bf_lo(t) * iv, bf_hi(t) * iv);
    t = pack_bf16(bf_lo(v[j].w) - mb, bf_hi(v[j].w) - mb); w.w = pack_bf16(bf_lo(t) * iv, bf_hi(t) * iv);
    dst[j * 16 + l16] = w;
  }
}

constexpr int LG_STAGES = 5;
constexpr int QKV_STAGE = 8192 + 4 * 4096;
constexpr int GLU_STAGE = 8192 + 6 * 4096;

template <int WG>
__device__ __forceinline__ void qkv_mainloop(float (&acc)[120], uint32_t sbase, uint32_t sBar, bool leader) {
  constexpr int STAGE_BYTES = QKV_STAGE, NST = LG_STAGES;
  const uint64_t da_base = make_desc(sbase + WG * 4096, 16, 512, 2);
  const uint64_t db_base = make_desc(sbase + 8192, 4096, 1024, 1);
#pragma unroll 1
  for (int r = 0; r < 20 / NST; r++) {
#pragma unroll
    for (int s = 0; s < NST; s++) {
      mbar_wait(sBar + 8 * s, r & 1);
      wgmma_fence();
#pragma unroll
      for (int ks = 0; ks < 2; ks++)
        wgmma_ss_n240_tb(acc, da_base + (uint64_t)((s * STAGE_BYTES + ks * 32) >> 4), db_base + (uint64_t)((s * STAGE_BYTES + ks * 2048) >> 4), 1);
      wgmma_commit();
      wgmma_wait<1>();
      release_stage(sBar + 8 * (NST + (s + NST - 1) % NST), leader && (s > 0 || r > 0));
    }
  }
}
template <int WG>
__device__ __forceinline__ void glu_mainloop(float (&accg)[96], float (&accu)[96], uint32_t sbase, uint32_t sBar, bool leader) {
  constexpr int STAGE_BYTES = GLU_STAGE, NST = LG_STAGES;
  const uint64_t da_base = make_desc(sbase + WG * 4096, 16, 512, 2);
  const uint64_t db_base = make_desc(sbase + 8192, 4096, 1024, 1);
#pragma unroll 1
  for (int r = 0; r < 20 / NST; r++) {
#pragma unroll
    for (int s = 0; s < NST; s++) {
      mbar_wait(sBar + 8 * s, r & 1);
      wgmma_fence();
#pragma unroll
      for (int ks = 0; ks < 2; ks++) {
        const uint64_t da = da_base + (uint64_t)((s * STAGE_BYTES + ks * 32) >> 4);
        wgmma_ss_n192_tb(accg, da, db_base + (uint64_t)((s * STAGE_BYTES + ks * 2048) >> 4), 1);
        wgmma_ss_n192_tb(accu, da, db_base + (uint64_t)((s * STAGE_BYTES + 3 * 4096 + ks * 2048) >> 4), 1);
      }
      wgmma_commit();
      wgmma_wait<1>();
      release_stage(sBar + 8 * (NST + (s + NST - 1) % NST), leader && (s > 0 || r > 0));
    }
  }
}
constexpr int RG_STAGE_BYTES = 16384 + 8192 + 2048;
template <int NKB, int NST, int WG>
__device__ __forceinline__ void res_mainloop(float (&acc0)[32], float (&acc1)[8], uint32_t sbase, uint32_t sBar, bool leader) {
  const uint64_t da_base = make_desc(sbase + WG * 8192, 16, 1024, 1);
  const uint64_t db0_base = make_desc(sbase + 16384, 8192, 1024, 1);
  const uint64_t db1_base = make_desc(sbase + 16384 + 8192, 2048, 256, 3);
#pragma unroll 1
  for (int r = 0; r < NKB / NST; r++) {
#pragma unroll
    for (int s = 0; s < NST; s++) {
      const uint64_t so = (uint64_t)(s * (RG_STAGE_BYTES >> 4));
      mbar_wait(sBar + 8 * s, r & 1);
      wgmma_fence();
#pragma unroll
      for (int ks = 0; ks < 4; ks++) {
        wgmma_ss_n64_tb(acc0, da_base + so + ks * 2, db0_base + so + ks * 128, 1);
        wgmma_ss_n16_tb(acc1, da_base + so + ks * 2, db1_base + so + ks * 32, 1);
      }
      wgmma_commit();
      wgmma_wait<1>();
      release_stage(sBar + 8 * (NST + (s + NST - 1) % NST), leader && (s > 0 || r > 0));
    }
  }
}

constexpr int KA_SMEM = LG_STAGES * QKV_STAGE + 128 + 1024;

__global__ void __launch_bounds__(GT, 1)
qkv_kernel(const __grid_constant__ CUtensorMap tmA, const __grid_constant__ CUtensorMap tmB, const bf16* __restrict__ x) {
  constexpr int STAGE_BYTES = QKV_STAGE, NST = LG_STAGES, NKB = 20;
  extern __shared__ uint8_t smem_raw[];
  const uint32_t sbase = (smem_u32(smem_raw) + 1023u) & ~1023u;
  const uint32_t sBar = sbase + NST * STAGE_BYTES;
  const int tid = threadIdx.x, warp = tid >> 5, lane = tid & 31;
  const int rank = blockIdx.x & 1;
  const int pair = blockIdx.x >> 1;
  const int n_blk = pair & 7;
  const int m_blk = (pair >> 3) * 2 + rank;
  TS(0, 0);
  if (tid == 256) {
    prefetch_tmap(&tmA);
    prefetch_tmap(&tmB);
  }
  if (tid == 0) {
    for (int s = 0; s < NST; s++) {
      mbar_init(sBar + 8 * s, 1);
      mbar_init(sBar + 8 * (NST + s), 4);
    }
    fence_mbar_init();
    if (blockIdx.x < 32) g_flag[16 + blockIdx.x] = 0;
  }
  pdl_launch();
  cluster_sync_all();

  if (warp >= 8) {
    asm volatile("setmaxnreg.dec.sync.aligned.u32 40;");
    if (tid == 256) {
      auto issue_b = [&](int kb) {
        const int s = kb % NST;
        const uint32_t full = sBar + 8 * s;
        mbar_expect_tx(full, STAGE_BYTES);
        const uint32_t dst = sbase + s * STAGE_BYTES + 8192;
#pragma unroll
        for (int j = 0; j < 2; j++) {
          const int sl = rank * 2 + j;
          tma_load_2d_mc(dst + sl * 4096, &tmB, n_blk * 240 + sl * 64, kb * 32, full, (uint16_t)3);
        }
      };
      for (int kb = 0; kb < NST; kb++) issue_b(kb);
      flag_wait(&g_flag[m_blk], 8);
      fence_proxy_async_all();
      for (int kb = 0; kb < NKB; kb++) {
        const int s = kb % NST;
        if (kb >= NST) {
          mbar_wait(sBar + 8 * (NST + s), ((kb / NST) & 1) ^ 1);
          issue_b(kb);
        }
        tma_load_2d(sbase + s * STAGE_BYTES, &tmA, kb * 32, m_blk * 128, sBar + 8 * s);
      }
    }
  } else {
    asm volatile("setmaxnreg.inc.sync.aligned.u32 232;");
    const int wg = __shfl_sync(0xffffffffu, warp >> 2, 0);
    const int wwarp = warp & 3;
    {
      const int row = m_blk * 128 + n_blk * 16 + warp * 2 + (lane >> 4);
      ln_row(x + (size_t)row * DM, g_xn + (size_t)row * DM, lane & 15);
      named_bar_sync(3, 256);
      if (tid == 0) flag_signal(&g_flag[m_blk]);
    }
    TS(0, 1);
    mbar_wait(sBar, 0);
    TS(0, 3);
    float acc[120];
#pragma unroll
    for (int i = 0; i < 120; i++) acc[i] = 0.f;
    if (wg == 0) qkv_mainloop<0>(acc, sbase, sBar, (tid & 127) == 0);
    else qkv_mainloop<1>(acc, sbase, sBar, (tid & 127) == 0);
    wgmma_wait<0>();
    fence_regs(acc);
    TS(0, 4);
    named_bar_sync(3, 256);
    const int g = lane >> 2, c4 = lane & 3;
    const uint32_t stg = sbase + wg * (12 * 3072) + (wwarp * 2) * 384 + g * 16;
    const int hbase = n_blk * 12;
#pragma unroll
    for (int j = 0; j < 30; j++) {
      const int cb = (j * 8) % 20;
      const int hb = (j * 8) / 20;
      int d = cb + c4 * 2;
      int hl = hb;
      if (cb == 16 && c4 >= 2) { d -= 20; hl += 1; }
      const uint32_t a0 = stg + hl * 3072 + (d >> 3) * 128 + (d & 7) * 2;
      const int hg = hbase + hl;
      const float sc = hg < 32 ? ATT_SCALE_LOG2E : 1.0f;
      st_shared_b32(a0, pack_bf16(acc[4 * j] * sc, acc[4 * j + 1] * sc));
      st_shared_b32(a0 + 384, pack_bf16(acc[4 * j + 2] * sc, acc[4 * j + 3] * sc));
      if (d == 18) {
        const uint32_t pad0 = hg < 32 ? 0u : (hg < 64 ? 0x3f803f80u : 0x00003f80u);
        const uint32_t pad1 = (hg >= 32 && hg < 64) ? 0x00003f80u : 0u;
        st_shared_v2(a0 + 4, pad0, pad1);
        st_shared_v2(a0 + 388, pad0, pad1);
      }
      if (j % 10 == 9) {
        fence_proxy_async();
        named_bar_sync(1 + wg, 128);
        if ((tid & 127) < 4) {
          const int hs = (j / 10) * 4 + (tid & 127);
          bf16* dst = g_img + (size_t)(hbase + hs) * IMG_HEAD_ELEMS + (size_t)(m_blk * 16 + wg * 8) * 192;
          bulk_s2g(dst, sbase + wg * (12 * 3072) + hs * 3072, 3072);
          bulk_commit();
        }
      }
    }
    if ((tid & 127) < 4) bulk_wait_read();
  }
  __syncwarp();
  TS(0, 5);
  cluster_sync_relaxed();
  TS(0, 6);
}

constexpr int KC_NST1 = 5, KC_NST3 = 6;
constexpr int KC_STAGING = 160 * 1024;
constexpr int KC_BAR = KC_STAGING + 48 * 1024;
constexpr int KC_CS = KC_BAR + 512;
constexpr int KC_SMEM = KC_CS + 1536 + 1024;

__global__ void __launch_bounds__(GT, 1)
mlp_kernel(const __grid_constant__ CUtensorMap tmO, const __grid_constant__ CUtensorMap tmWo64, const __grid_constant__ CUtensorMap tmWo16,
           const __grid_constant__ CUtensorMap tmH, const __grid_constant__ CUtensorMap tmWg, const __grid_constant__ CUtensorMap tmWu,
           const __grid_constant__ CUtensorMap tmHHs, const __grid_constant__ CUtensorMap tmHH, const __grid_constant__ CUtensorMap tmWd64,
           const __grid_constant__ CUtensorMap tmWd16, const __grid_constant__ CUtensorMap tmHs, const __grid_constant__ CUtensorMap tmOut,
           const bf16* __restrict__ x) {
  extern __shared__ uint8_t smem_raw[];
  const uint32_t sbase = (smem_u32(smem_raw) + 1023u) & ~1023u;
  const uint32_t bar1 = sbase + KC_BAR;
  const uint32_t bar2 = bar1 + 128;
  const uint32_t bar3 = bar2 + 128;
  const uint32_t barD = bar3 + 128;
  const int tid = threadIdx.x, warp = tid >> 5, lane = tid & 31;
  const int rank = blockIdx.x & 1;
  const int pair = blockIdx.x >> 1;
  const int j_blk = pair & 7;
  const int m_blk = (pair >> 3) * 2 + rank;
  const int n0 = j_blk * 80;
  TS(2, 0);
  if (tid == 256) {
    prefetch_tmap(&tmO); prefetch_tmap(&tmWo64); prefetch_tmap(&tmWo16); prefetch_tmap(&tmH); prefetch_tmap(&tmWg);
    prefetch_tmap(&tmWu); prefetch_tmap(&tmHHs); prefetch_tmap(&tmHH); prefetch_tmap(&tmWd64); prefetch_tmap(&tmWd16);
    prefetch_tmap(&tmHs); prefetch_tmap(&tmOut);
  }
  if (tid == 0) {
    for (int s = 0; s < 5; s++) {
      mbar_init(bar1 + 8 * s, 1); mbar_init(bar1 + 8 * (5 + s), 4);
      mbar_init(bar2 + 8 * s, 1); mbar_init(bar2 + 8 * (5 + s), 4);
    }
    for (int s = 0; s < 6; s++) { mbar_init(bar3 + 8 * s, 1); mbar_init(bar3 + 8 * (6 + s), 4); }
    mbar_init(barD, 4); mbar_init(barD + 8, 4);
    fence_mbar_init();
  }
  cluster_sync_all();

  if (warp >= 8) {
    asm volatile("setmaxnreg.dec.sync.aligned.u32 40;");
    if (tid == 256) {
      auto issue_b80 = [&](const CUtensorMap* t64, const CUtensorMap* t16, uint32_t bars, int nst, int kb) {
        const int s = kb % nst;
        const uint32_t full = bars + 8 * s;
        const uint32_t st = sbase + s * RG_STAGE_BYTES;
        mbar_expect_tx(full, RG_STAGE_BYTES);
        tma_load_2d_mc(st + 16384 + rank * 4096, t64, n0, kb * 64 + rank * 32, full, (uint16_t)3);
        tma_load_2d_mc(st + 16384 + 8192 + rank * 1024, t16, n0 + 64, kb * 64 + rank * 32, full, (uint16_t)3);
      };
      for (int kb = 0; kb < KC_NST1; kb++) issue_b80(&tmWo64, &tmWo16, bar1, KC_NST1, kb);
      pdl_wait();
      for (int kb = 0; kb < 10; kb++) {
        const int s = kb % KC_NST1;
        if (kb >= KC_NST1) {
          mbar_wait(bar1 + 8 * (KC_NST1 + s), ((kb / KC_NST1) & 1) ^ 1);
          issue_b80(&tmWo64, &tmWo16, bar1, KC_NST1, kb);
        }
        tma_load_2d(sbase + s * RG_STAGE_BYTES, &tmO, kb * 64, m_blk * 128, bar1 + 8 * s);
      }
      auto issue_bglu = [&](int kb) {
        const int s = kb % LG_STAGES;
        const uint32_t full = bar2 + 8 * s;
        mbar_expect_tx(full, GLU_STAGE);
        const uint32_t dst = sbase + s * GLU_STAGE + 8192;
#pragma unroll
        for (int j = 0; j < 3; j++)
          tma_load_2d_mc(dst + (rank * 3 + j) * 4096, rank == 0 ? &tmWg : &tmWu, j_blk * 192 + j * 64, kb * 32, full, (uint16_t)3);
      };
      mbar_wait(barD, 0);
      for (int kb = 0; kb < LG_STAGES; kb++) issue_bglu(kb);
      flag_wait(&g_flag[16 + m_blk], 16);
      fence_proxy_async_all();
      for (int kb = 0; kb < 20; kb++) {
        const int s = kb % LG_STAGES;
        if (kb >= LG_STAGES) {
          mbar_wait(bar2 + 8 * (LG_STAGES + s), ((kb / LG_STAGES) & 1) ^ 1);
          issue_bglu(kb);
        }
        tma_load_2d(sbase + s * GLU_STAGE, &tmH, kb * 32, m_blk * 128, bar2 + 8 * s);
      }
      mbar_wait(barD + 8, 0);
      for (int kb = 0; kb < KC_NST3; kb++) issue_b80(&tmWd64, &tmWd16, bar3, KC_NST3, kb);
      flag_wait(&g_flag[32 + m_blk], 16);
      fence_proxy_async_all();
      for (int kb = 0; kb < 24; kb++) {
        const int s = kb % KC_NST3;
        if (kb >= KC_NST3) {
          mbar_wait(bar3 + 8 * (KC_NST3 + s), ((kb / KC_NST3) & 1) ^ 1);
          issue_b80(&tmWd64, &tmWd16, bar3, KC_NST3, kb);
        }
        tma_load_2d(sbase + s * RG_STAGE_BYTES, &tmHH, kb * 64, m_blk * 128, bar3 + 8 * s);
      }
    }
  } else {
    asm volatile("setmaxnreg.inc.sync.aligned.u32 232;");
    const int wg = __shfl_sync(0xffffffffu, warp >> 2, 0);
    const int wwarp = warp & 3;
    const int g = lane >> 2, c4 = lane & 3;
    const int row0 = m_blk * 128 + wg * 64 + wwarp * 16 + g;
    const bool leader = (tid & 127) == 0;
    const uint32_t stg80_base = sbase + KC_STAGING + wg * 24576;
    const uint32_t stg80 = stg80_base + (wwarp * 16 + g) * 160 + c4 * 4;
    {
      uint32_t res[20];
#pragma unroll
      for (int j = 0; j < 10; j++) {
        res[2 * j] = __ldg(reinterpret_cast<const uint32_t*>(x + (size_t)row0 * DM + n0 + j * 8 + c4 * 2));
        res[2 * j + 1] = __ldg(reinterpret_cast<const uint32_t*>(x + (size_t)(row0 + 8) * DM + n0 + j * 8 + c4 * 2));
      }
      float acc0[32], acc1[8];
#pragma unroll
      for (int i = 0; i < 32; i++) acc0[i] = 0.f;
#pragma unroll
      for (int i = 0; i < 8; i++) acc1[i] = 0.f;
      TS(2, 1);
      if (wg == 0) res_mainloop<10, KC_NST1, 0>(acc0, acc1, sbase, bar1, leader);
      else res_mainloop<10, KC_NST1, 1>(acc0, acc1, sbase, bar1, leader);
      wgmma_wait<0>();
      fence_regs(acc0); fence_regs(acc1);
      release_stage(barD, leader);
      TS(2, 4);
      float sum0 = 0.f, sum1 = 0.f;
#pragma unroll
      for (int j = 0; j < 10; j++) {
        const uint32_t a01 = j < 8 ? pack_bf16(acc0[4 * j], acc0[4 * j + 1]) : pack_bf16(acc1[4 * (j - 8)], acc1[4 * (j - 8) + 1]);
        const uint32_t a23 = j < 8 ? pack_bf16(acc0[4 * j + 2], acc0[4 * j + 3]) : pack_bf16(acc1[4 * (j - 8) + 2], acc1[4 * (j - 8) + 3]);
        res[2 * j] = pack_bf16(bf_lo(res[2 * j]) + bf_lo(a01), bf_hi(res[2 * j]) + bf_hi(a01));
        res[2 * j + 1] = pack_bf16(bf_lo(res[2 * j + 1]) + bf_lo(a23), bf_hi(res[2 * j + 1]) + bf_hi(a23));
        st_shared_b32(stg80 + j * 16, res[2 * j]);
        st_shared_b32(stg80 + 8 * 160 + j * 16, res[2 * j + 1]);
        sum0 += bf_lo(res[2 * j]) + bf_hi(res[2 * j]);
        sum1 += bf_lo(res[2 * j + 1]) + bf_hi(res[2 * j + 1]);
      }
      sum0 += __shfl_xor_sync(0xffffffffu, sum0, 1); sum1 += __shfl_xor_sync(0xffffffffu, sum1, 1);
      sum0 += __shfl_xor_sync(0xffffffffu, sum0, 2); sum1 += __shfl_xor_sync(0xffffffffu, sum1, 2);
      const float mu0 = sum0 * (1.0f / 80.0f), mu1 = sum1 * (1.0f / 80.0f);
      float q0 = 0.f, q1 = 0.f;
#pragma unroll
      for (int j = 0; j < 10; j++) {
        float d;
        d = bf_lo(res[2 * j]) - mu0; q0 = fmaf(d, d, q0);
        d = bf_hi(res[2 * j]) - mu0; q0 = fmaf(d, d, q0);
        d = bf_lo(res[2 * j + 1]) - mu1; q1 = fmaf(d, d, q1);
        d = bf_hi(res[2 * j + 1]) - mu1; q1 = fmaf(d, d, q1);
      }
      q0 += __shfl_xor_sync(0xffffffffu, q0, 1); q1 += __shfl_xor_sync(0xffffffffu, q1, 1);
      q0 += __shfl_xor_sync(0xffffffffu, q0, 2); q1 += __shfl_xor_sync(0xffffffffu, q1, 2);
      if (c4 == 0) {
        g_stats[row0 * 8 + j_blk] = make_float2(mu0, q0);
        g_stats[(row0 + 8) * 8 + j_blk] = make_float2(mu1, q1);
      }
      fence_proxy_async();
      named_bar_sync(1 + wg, 128);
      if (leader) {
        tma_store_2d(&tmHs, stg80_base, n0, m_blk * 128 + wg * 64);
        bulk_commit();
        bulk_wait_all();
        fence_proxy_async_all();
        flag_signal(&g_flag[16 + m_blk]);
      }
      TS(2, 5);
    }
    {
      pdl_wait();
      {
        float* cs_s = reinterpret_cast<float*>(smem_raw + (sbase - smem_u32(smem_raw)) + KC_CS);
        for (int i = tid; i < 384; i += 256) cs_s[i] = g_cs[(i >= 192 ? FF - 192 : 0) + j_blk * 192 + i];
        named_bar_sync(3, 256);
      }
      flag_wait(&g_flag[16 + m_blk], 16);
      float mb[2], iv[2];
#pragma unroll
      for (int h = 0; h < 2; h++) {
        const float4* sp = reinterpret_cast<const float4*>(g_stats + (row0 + 8 * h) * 8);
        const float4 p0 = sp[0], p1 = sp[1], p2 = sp[2], p3 = sp[3];
        const float mean = (((p0.x + p0.z) + (p1.x + p1.z)) + ((p2.x + p2.z) + (p3.x + p3.z))) * 0.125f;
        float m2 = ((p0.y + p0.w) + (p1.y + p1.w)) + ((p2.y + p2.w) + (p3.y + p3.w));
        float dd = 0.f, d;
        d = p0.x - mean; dd = fmaf(d, d, dd); d = p0.z - mean; dd = fmaf(d, d, dd);
        d = p1.x - mean; dd = fmaf(d, d, dd); d = p1.z - mean; dd = fmaf(d, d, dd);
        d = p2.x - mean; dd = fmaf(d, d, dd); d = p2.z - mean; dd = fmaf(d, d, dd);
        d = p3.x - mean; dd = fmaf(d, d, dd); d = p3.z - mean; dd = fmaf(d, d, dd);
        m2 = fmaf(dd, 80.0f, m2);
        const float var_b = bf16_round(m2 * (1.0f / DM));
        const float den = bf16_round(sqrtf(bf16_round(var_b + 1e-5f)));
        iv[h] = __frcp_rn(den);
        mb[h] = bf16_round(mean);
      }
      float accg[96], accu[96];
#pragma unroll
      for (int i = 0; i < 96; i++) { accg[i] = 0.f; accu[i] = 0.f; }
      TS(3, 3);
      if (wg == 0) glu_mainloop<0>(accg, accu, sbase, bar2, leader);
      else glu_mainloop<1>(accg, accu, sbase, bar2, leader);
      wgmma_wait<0>();
      fence_regs(accg); fence_regs(accu);
      release_stage(barD + 8, leader);
      TS(3, 4);
      const uint32_t stg = sbase + KC_STAGING + wg * 24576 + (wwarp * 16 + g) * 128 + c4 * 4;
      const float* csg = reinterpret_cast<const float*>(smem_raw + (sbase - smem_u32(smem_raw)) + KC_CS) + c4 * 2;
      const float nm0 = -mb[0] * iv[0], nm1 = -mb[1] * iv[1];
#pragma unroll
      for (int sl = 0; sl < 3; sl++) {
#pragma unroll
        for (int jj = 0; jj < 8; jj++) {
          const int j = sl * 8 + jj;
          const float2 cg = *reinterpret_cast<const float2*>(csg + j * 8);
          const float2 cu = *reinterpret_cast<const float2*>(csg + 192 + j * 8);
          const float r0 = fmaxf(fmaf(accg[4 * j], iv[0], nm0 * cg.x), 0.f) * fmaf(accu[4 * j], iv[0], nm0 * cu.x);
          const float r1 = fmaxf(fmaf(accg[4 * j + 1], iv[0], nm0 * cg.y), 0.f) * fmaf(accu[4 * j + 1], iv[0], nm0 * cu.y);
          const float r2 = fmaxf(fmaf(accg[4 * j + 2], iv[1], nm1 * cg.x), 0.f) * fmaf(accu[4 * j + 2], iv[1], nm1 * cu.x);
          const float r3 = fmaxf(fmaf(accg[4 * j + 3], iv[1], nm1 * cg.y), 0.f) * fmaf(accu[4 * j + 3], iv[1], nm1 * cu.y);
          const uint32_t a0 = stg + sl * 8192 + ((jj ^ g) << 4);
          st_shared_b32(a0, pack_bf16(r0, r1));
          st_shared_b32(a0 + 1024, pack_bf16(r2, r3));
        }
        fence_proxy_async();
        named_bar_sync(1 + wg, 128);
        if (leader) {
          tma_store_2d(&tmHHs, sbase + KC_STAGING + wg * 24576 + sl * 8192, j_blk * 192 + sl * 64, m_blk * 128 + wg * 64);
          bulk_commit();
        }
      }
      TS(3, 7);
      if (leader) {
        bulk_wait_all();
        TS(3, 8);
        fence_proxy_async_all();
        flag_signal(&g_flag[32 + m_blk]);
      }
      TS(3, 9);
    }
    {
      uint32_t res[20];
#pragma unroll
      for (int j = 0; j < 10; j++) {
        res[2 * j] = *reinterpret_cast<const uint32_t*>(g_h + (size_t)row0 * DM + n0 + j * 8 + c4 * 2);
        res[2 * j + 1] = *reinterpret_cast<const uint32_t*>(g_h + (size_t)(row0 + 8) * DM + n0 + j * 8 + c4 * 2);
      }
      float acc0[32], acc1[8];
#pragma unroll
      for (int i = 0; i < 32; i++) acc0[i] = 0.f;
#pragma unroll
      for (int i = 0; i < 8; i++) acc1[i] = 0.f;
      mbar_wait(bar3, 0);
      TS(4, 3);
      if (wg == 0) res_mainloop<24, KC_NST3, 0>(acc0, acc1, sbase, bar3, leader);
      else res_mainloop<24, KC_NST3, 1>(acc0, acc1, sbase, bar3, leader);
      wgmma_wait<0>();
      fence_regs(acc0); fence_regs(acc1);
      TS(4, 4);
#pragma unroll
      for (int j = 0; j < 10; j++) {
        const uint32_t a01 = j < 8 ? pack_bf16(acc0[4 * j], acc0[4 * j + 1]) : pack_bf16(acc1[4 * (j - 8)], acc1[4 * (j - 8) + 1]);
        const uint32_t a23 = j < 8 ? pack_bf16(acc0[4 * j + 2], acc0[4 * j + 3]) : pack_bf16(acc1[4 * (j - 8) + 2], acc1[4 * (j - 8) + 3]);
        st_shared_b32(stg80 + j * 16, pack_bf16(bf_lo(res[2 * j]) + bf_lo(a01), bf_hi(res[2 * j]) + bf_hi(a01)));
        st_shared_b32(stg80 + 8 * 160 + j * 16, pack_bf16(bf_lo(res[2 * j + 1]) + bf_lo(a23), bf_hi(res[2 * j + 1]) + bf_hi(a23)));
      }
      fence_proxy_async();
      named_bar_sync(1 + wg, 128);
      if (leader) {
        tma_store_2d(&tmOut, stg80_base, n0, m_blk * 128 + wg * 64);
        bulk_commit();
        bulk_wait_read();
      }
      TS(4, 5);
    }
  }
  __syncwarp();
  cluster_sync_relaxed();
  TS(4, 6);
}

constexpr int AT_THREADS = 512;
constexpr int AT_WGS = AT_THREADS / 128;
#define AT_CHUNK_MASK 3
#define AT_STAGGER 0
constexpr int AT_KV_BYTES = IMG_HEAD_ELEMS * 2;
constexpr int AT_SMEM = 2 * AT_KV_BYTES + 256 + 1024;
constexpr int AT_CHUNKS = 8;

__device__ __forceinline__ float exp2_poly(float x) {
  const float u = __saturatef(fmaf(x, 1.0f / 64.0f, 62.0f / 64.0f));
  const float MAGIC = 12582912.0f - 62.0f;
  const float r = fmaf(u, 64.0f, MAGIC);
  const float q = MAGIC - r;
  const float fr = fmaf(u, 64.0f, q);
  float p = fmaf(fr, 0.009570102207362652f, 0.05591785907745361f);
  p = fmaf(p, fr, 0.240247443318367f);
  p = fmaf(p, fr, 0.6931217908859253f);
  p = fmaf(p, fr, 0.9999992847442627f);
  return __uint_as_float(__float_as_uint(p) + (__float_as_uint(r) << 23));
}
#define AT_VARIANT 0
#define AT_POLY_MOD 8
__device__ __forceinline__ bool use_poly(int e) {
  return (e % AT_POLY_MOD) == 1;
}

struct AttnState {
  uint32_t qa0, qa1, qa2, qa3, qa4, qa5;
  float M0, M1;
};

__device__ __forceinline__ bool attn_exp_fast(const float (&s)[32], uint32_t (&p)[16]) {
#pragma unroll
  for (int j = 0; j < 16; j++) {
    const float e0 = use_poly(2 * j) ? exp2_poly(s[2 * j]) : ex2(s[2 * j]);
    const float e1 = use_poly(2 * j + 1) ? exp2_poly(s[2 * j + 1]) : ex2(s[2 * j + 1]);
    p[j] = pack_bf16(e0, e1);
  }
  uint32_t acc_or = 0;
#pragma unroll
  for (int j = 0; j < 16; j++) acc_or |= p[j];
  return __any_sync(0xffffffffu, (acc_or & 0x40004000u) != 0);
}
__device__ __forceinline__ void attn_exp_exact(const float (&s)[32], uint32_t (&p)[16], float (&o)[12], AttnState& st, bool first, int c4) {
  float mx0 = fmaxf(s[0], s[1]), mx1 = fmaxf(s[2], s[3]);
#pragma unroll
  for (int j = 1; j < 8; j++) {
    mx0 = fmaxf(mx0, fmaxf(s[4 * j], s[4 * j + 1]));
    mx1 = fmaxf(mx1, fmaxf(s[4 * j + 2], s[4 * j + 3]));
  }
  mx0 = fmaxf(mx0, __shfl_xor_sync(0xffffffffu, mx0, 1));
  mx1 = fmaxf(mx1, __shfl_xor_sync(0xffffffffu, mx1, 1));
  mx0 = fmaxf(mx0, __shfl_xor_sync(0xffffffffu, mx0, 2));
  mx1 = fmaxf(mx1, __shfl_xor_sync(0xffffffffu, mx1, 2));
  float d0 = mx0 + 7.0f, d1 = mx1 + 7.0f;
  if (!first) { d0 = fmaxf(d0, 0.f); d1 = fmaxf(d1, 0.f); }
  const float T0 = st.M0 + d0, T1 = st.M1 + d1;
  const float h0 = bf16_round(T0), h1 = bf16_round(T1);
  const float i0 = bf16_round(T0 - h0), i1 = bf16_round(T1 - h1);
  const float l0 = bf16_round((T0 - h0) - i0), l1 = bf16_round((T1 - h1) - i1);
  const float N0 = (h0 + i0) + l0, N1 = (h1 + i1) + l1;
  d0 = N0 - st.M0; d1 = N1 - st.M1;
  st.M0 = N0; st.M1 = N1;
  if (c4 == 2) { st.qa4 = pack_bf16(-h0, -i0); st.qa5 = pack_bf16(-h1, -i1); }
  if (c4 == 3) { st.qa4 = pack_bf16(-l0, 0.f); st.qa5 = pack_bf16(-l1, 0.f); }
  if (!first) {
    const float al0 = ex2(-d0), al1 = ex2(-d1);
#pragma unroll
    for (int j = 0; j < 3; j++) {
      o[4 * j] *= al0; o[4 * j + 1] *= al0;
      o[4 * j + 2] *= al1; o[4 * j + 3] *= al1;
    }
  }
#pragma unroll
  for (int j = 0; j < 8; j++) {
    p[2 * j] = pack_bf16(ex2(s[4 * j] - d0), ex2(s[4 * j + 1] - d0));
    p[2 * j + 1] = pack_bf16(ex2(s[4 * j + 2] - d1), ex2(s[4 * j + 3] - d1));
  }
}
__device__ __forceinline__ void attn_step(float (&s)[32], const uint32_t (&pp)[16], uint32_t (&pn)[16], float (&o)[12], AttnState& st,
                                          uint32_t k_addr, uint32_t v_addr_prev, int keep, int c4, int wgdbg = 0, int tdbg = 0) {
  PH(wgdbg, tdbg, 0);
  const uint64_t dk = make_desc(k_addr, 128, 384, 0);
  const uint64_t dv_prev = make_desc(v_addr_prev, 384, 128, 0);
  wgmma_fence();
  wgmma_rs_n64(s, st.qa0, st.qa1, st.qa2, st.qa3, dk, 0);
  wgmma_rs_n64(s, st.qa4, st.qa5, 0u, 0u, dk + 16, 1);
  wgmma_commit();
#pragma unroll
  for (int kk = 0; kk < 4; kk++) wgmma_rs_n24_tb(o, pp[4 * kk], pp[4 * kk + 1], pp[4 * kk + 2], pp[4 * kk + 3], dv_prev + kk * 48, kk == 0 ? keep : 1);
  wgmma_commit();
  wgmma_wait<1>();
  fence_regs(s);
  PH(wgdbg, tdbg, 1);
  const bool redo = attn_exp_fast(s, pn);
  PH(wgdbg, tdbg, 2);
  wgmma_wait<0>();
  fence_regs(o);
  if (redo) attn_exp_exact(s, pn, o, st, false, c4);
}

__global__ void __launch_bounds__(AT_THREADS, 1) attn_kernel(const bf16* __restrict__ wo, const bf16* __restrict__ wgt, const bf16* __restrict__ wup, const bf16* __restrict__ wdn) {
  extern __shared__ uint8_t smem_raw[];
  const uint32_t sbase = (smem_u32(smem_raw) + 1023u) & ~1023u;
  const uint32_t sK = sbase, sV = sbase + AT_KV_BYTES;
  const uint32_t sBar = sV + AT_KV_BYTES;
  const int tid = threadIdx.x, warp = tid >> 5, lane = tid & 31;
  const int head = blockIdx.x >> 2, quarter = blockIdx.x & 3;
  if (blockIdx.x >= 128) {
    pdl_launch();
    const int b = blockIdx.x - 128;
    const bf16* w = (b >> 1) ? wup : wgt;
    const int cgrp = tid % 96, rgrp = tid / 96;
    float acc[8];
#pragma unroll
    for (int i = 0; i < 8; i++) acc[i] = 0.f;
    float* red = reinterpret_cast<float*>(smem_raw);
    if (rgrp < 5) {
      const uint4* src = reinterpret_cast<const uint4*>(w + (size_t)(rgrp * 128) * FF + (b & 1) * 768 + cgrp * 8);
#pragma unroll 8
      for (int r = 0; r < 128; r++) {
        const uint4 v = __ldg(src + (size_t)r * (FF / 8));
        acc[0] += bf_lo(v.x); acc[1] += bf_hi(v.x); acc[2] += bf_lo(v.y); acc[3] += bf_hi(v.y);
        acc[4] += bf_lo(v.z); acc[5] += bf_hi(v.z); acc[6] += bf_lo(v.w); acc[7] += bf_hi(v.w);
      }
#pragma unroll
      for (int i = 0; i < 8; i++) red[rgrp * 768 + cgrp * 8 + i] = acc[i];
    }
    __syncthreads();
    pdl_wait();
    for (int c = tid; c < 768; c += AT_THREADS)
      g_cs[(b >> 1) * FF + (b & 1) * 768 + c] = ((red[c] + red[768 + c]) + (red[1536 + c] + red[2304 + c])) + red[3072 + c];
    if (b == 0 && tid < 16) g_flag[tid] = 0;
    return;
  }
  TS(1, 0);
  if (tid == 0) {
    for (int i = 0; i < AT_CHUNKS; i++) mbar_init(sBar + 8 * i, 1);
    fence_mbar_init();
  }
  pdl_launch();
  if (tid == 32) {
    prefetch_l2(reinterpret_cast<const uint8_t*>(wo) + blockIdx.x * 6400, 6400);
    prefetch_l2(reinterpret_cast<const uint8_t*>(wgt) + blockIdx.x * 15360, 15360);
    prefetch_l2(reinterpret_cast<const uint8_t*>(wup) + blockIdx.x * 15360, 15360);
    prefetch_l2(reinterpret_cast<const uint8_t*>(wdn) + blockIdx.x * 15360, 15360);
  }
  __syncthreads();
  TS(1, 1);
  pdl_wait();
  TS(1, 2);
  if (tid == 0) {
    const uint8_t* kg = reinterpret_cast<const uint8_t*>(g_img + (size_t)(32 + head) * IMG_HEAD_ELEMS);
    const uint8_t* vg = reinterpret_cast<const uint8_t*>(g_img + (size_t)(64 + head) * IMG_HEAD_ELEMS);
    constexpr int CB = AT_KV_BYTES / AT_CHUNKS;
    for (int i = 0; i < AT_CHUNKS; i++) {
      mbar_expect_tx(sBar + 8 * i, 2 * CB);
      bulk_g2s(sK + i * CB, kg + i * CB, CB, sBar + 8 * i);
      bulk_g2s(sV + i * CB, vg + i * CB, CB, sBar + 8 * i);
    }
  }
  const int wg = warp >> 2, wwarp = warp & 3;
  const int g = lane >> 2, c4 = lane & 3;
  const uint64_t dk_base = make_desc(sK, 128, 384, 0);
  const uint64_t dv_base = make_desc(sV, 384, 128, 0);

#pragma unroll 1
  for (int rep = 0; rep < 8 / AT_WGS; rep++) {
    const int row0 = quarter * 512 + (rep * AT_WGS + wg) * 64 + wwarp * 16 + g;
    AttnState st;
    {
      const bf16* q0 = g_img + (size_t)head * IMG_HEAD_ELEMS + (size_t)(row0 >> 3) * 192 + g * 8 + c4 * 2;
      const bf16* q1 = q0 + 192;
      st.qa0 = *reinterpret_cast<const uint32_t*>(q0);
      st.qa1 = *reinterpret_cast<const uint32_t*>(q1);
      st.qa2 = *reinterpret_cast<const uint32_t*>(q0 + 64);
      st.qa3 = *reinterpret_cast<const uint32_t*>(q1 + 64);
      st.qa4 = *reinterpret_cast<const uint32_t*>(q0 + 128);
      st.qa5 = *reinterpret_cast<const uint32_t*>(q1 + 128);
    }
    float o[12];
    float s[32];
    uint32_t pa[16], pb[16];
    st.M0 = st.M1 = 0.f;
    if (rep == 0) mbar_wait(sBar, 0);
    wgmma_fence();
    wgmma_rs_n64(s, st.qa0, st.qa1, st.qa2, st.qa3, dk_base, 0);
    wgmma_rs_n64(s, st.qa4, st.qa5, 0u, 0u, dk_base + 16, 1);
    wgmma_commit();
    wgmma_wait<0>();
    fence_regs(s);
    attn_exp_exact(s, pa, o, st, true, c4);
    attn_step(s, pa, pb, o, st, sK + 3072, sV, 0, c4);
#pragma unroll 1
    for (int tt = 1; tt < 16; tt++) {
      if (rep == 0 && !(tt & 1)) mbar_wait(sBar + 8 * (tt >> 1), 0);
      attn_step(s, pb, pa, o, st, sK + tt * 6144, sV + tt * 6144 - 3072, 1, c4, wg, rep * 32 + tt * 2);
      attn_step(s, pa, pb, o, st, sK + tt * 6144 + 3072, sV + tt * 6144, 1, c4, wg, rep * 32 + tt * 2 + 1);
    }
    wgmma_fence();
#pragma unroll
    for (int kk = 0; kk < 4; kk++) wgmma_rs_n24_tb(o, pb[4 * kk], pb[4 * kk + 1], pb[4 * kk + 2], pb[4 * kk + 3], dv_base + 31 * 192 + kk * 48, 1);
    wgmma_commit();
    wgmma_wait<0>();
    fence_regs(o);
    TS(1, 3 + rep);
    const float l0 = __shfl_sync(0xffffffffu, o[8], (lane & ~3) | 2);
    const float l1 = __shfl_sync(0xffffffffu, o[10], (lane & ~3) | 2);
    const float i0 = 1.0f / l0, i1 = 1.0f / l1;
    bf16* o0 = g_o + (size_t)row0 * DM + head * DH;
    bf16* o1 = o0 + 8 * DM;
#pragma unroll
    for (int j = 0; j < 3; j++) {
      if (j < 2 || c4 < 2) {
        *reinterpret_cast<uint32_t*>(o0 + j * 8 + c4 * 2) = pack_bf16(o[4 * j] * i0, o[4 * j + 1] * i0);
        *reinterpret_cast<uint32_t*>(o1 + j * 8 + c4 * 2) = pack_bf16(o[4 * j + 2] * i1, o[4 * j + 3] * i1);
      }
    }
  }
}

typedef CUresult (*EncodeTiledFn)(CUtensorMap*, CUtensorMapDataType, cuuint32_t, void*, const cuuint64_t*, const cuuint64_t*,
                                  const cuuint32_t*, const cuuint32_t*, CUtensorMapInterleave, CUtensorMapSwizzle,
                                  CUtensorMapL2promotion, CUtensorMapFloatOOBfill);

static void make_map(EncodeTiledFn fn, CUtensorMap* tm, const void* ptr, uint64_t rows, uint64_t cols, uint32_t box_rows,
                     uint32_t box_cols, CUtensorMapSwizzle sw) {
  cuuint64_t dims[2] = {cols, rows};
  cuuint64_t strides[1] = {cols * 2};
  cuuint32_t box[2] = {box_cols, box_rows};
  cuuint32_t es[2] = {1, 1};
  fn(tm, CU_TENSOR_MAP_DATA_TYPE_BFLOAT16, 2, const_cast<void*>(ptr), dims, strides, box, es, CU_TENSOR_MAP_INTERLEAVE_NONE, sw,
     CU_TENSOR_MAP_L2_PROMOTION_L2_256B, CU_TENSOR_MAP_FLOAT_OOB_FILL_NONE);
}

template <typename... KArgs, typename... Args>
static void launch(void (*kern)(KArgs...), int grid, int block, int smem, int cluster, bool pdl, Args... args) {
  cudaLaunchConfig_t cfg = {};
  cfg.gridDim = dim3(grid);
  cfg.blockDim = dim3(block);
  cfg.dynamicSmemBytes = smem;
  cfg.stream = cudaStreamPerThread;
  cudaLaunchAttribute at[2];
  int n = 0;
  if (cluster > 1) {
    at[n].id = cudaLaunchAttributeClusterDimension;
    at[n].val.clusterDim.x = cluster; at[n].val.clusterDim.y = 1; at[n].val.clusterDim.z = 1;
    n++;
  }
  if (pdl) {
    at[n].id = cudaLaunchAttributeProgrammaticStreamSerialization;
    at[n].val.programmaticStreamSerializationAllowed = 1;
    n++;
  }
  cfg.attrs = at;
  cfg.numAttrs = n;
  cudaLaunchKernelEx(&cfg, kern, KArgs(args)...);
}

extern "C" void kernel_launch(void* const* d_in, const int* in_sizes, int n_in, void* d_out, int out_size) {
  const bf16* x = (const bf16*)d_in[0];
  const bf16* wqkv = (const bf16*)d_in[1];
  const bf16* wo = (const bf16*)d_in[2];
  const bf16* wg = (const bf16*)d_in[4];
  const bf16* wu = (const bf16*)d_in[5];
  const bf16* wd = (const bf16*)d_in[6];
  bf16* out = (bf16*)d_out;

  static EncodeTiledFn enc = nullptr;
  static void *p_o = nullptr, *p_h = nullptr, *p_hh = nullptr, *p_xn = nullptr;
  if (!enc) {
    void* fn = nullptr;
    cudaDriverEntryPointQueryResult qr;
    cudaGetDriverEntryPoint("cuTensorMapEncodeTiled", &fn, cudaEnableDefault, &qr);
    enc = (EncodeTiledFn)fn;
    cudaGetSymbolAddress(&p_o, g_o);
    cudaGetSymbolAddress(&p_h, g_h);
    cudaGetSymbolAddress(&p_hh, g_hh);
    cudaGetSymbolAddress(&p_xn, g_xn);
    cudaFuncSetAttribute(qkv_kernel, cudaFuncAttributeMaxDynamicSharedMemorySize, KA_SMEM);
    cudaFuncSetAttribute(mlp_kernel, cudaFuncAttributeMaxDynamicSharedMemorySize, KC_SMEM);
    cudaFuncSetAttribute(attn_kernel, cudaFuncAttributeMaxDynamicSharedMemorySize, AT_SMEM);
  }
  CUtensorMap tm_wqkv, tm_wg, tm_wu, tm_wo64, tm_wo16, tm_wd64, tm_wd16, tm_o, tm_h, tm_hh, tm_hhs, tm_xn, tm_hs, tm_out;
  make_map(enc, &tm_wqkv, wqkv, DM, 3 * DM, 32, 64, CU_TENSOR_MAP_SWIZZLE_128B);
  make_map(enc, &tm_wg, wg, DM, FF, 32, 64, CU_TENSOR_MAP_SWIZZLE_128B);
  make_map(enc, &tm_wu, wu, DM, FF, 32, 64, CU_TENSOR_MAP_SWIZZLE_128B);
  make_map(enc, &tm_wo64, wo, DM, DM, 32, 64, CU_TENSOR_MAP_SWIZZLE_128B);
  make_map(enc, &tm_wo16, wo, DM, DM, 32, 16, CU_TENSOR_MAP_SWIZZLE_32B);
  make_map(enc, &tm_wd64, wd, FF, DM, 32, 64, CU_TENSOR_MAP_SWIZZLE_128B);
  make_map(enc, &tm_wd16, wd, FF, DM, 32, 16, CU_TENSOR_MAP_SWIZZLE_32B);
  make_map(enc, &tm_o, p_o, SEQ, DM, 128, 64, CU_TENSOR_MAP_SWIZZLE_128B);
  make_map(enc, &tm_h, p_h, SEQ, DM, 128, 32, CU_TENSOR_MAP_SWIZZLE_64B);
  make_map(enc, &tm_hh, p_hh, SEQ, FF, 128, 64, CU_TENSOR_MAP_SWIZZLE_128B);
  make_map(enc, &tm_hhs, p_hh, SEQ, FF, 64, 64, CU_TENSOR_MAP_SWIZZLE_128B);
  make_map(enc, &tm_xn, p_xn, SEQ, DM, 128, 32, CU_TENSOR_MAP_SWIZZLE_64B);
  make_map(enc, &tm_hs, p_h, SEQ, DM, 64, 80, CU_TENSOR_MAP_SWIZZLE_NONE);
  make_map(enc, &tm_out, out, SEQ, DM, 64, 80, CU_TENSOR_MAP_SWIZZLE_NONE);

  launch(qkv_kernel, 128, GT, KA_SMEM, 2, false, tm_xn, tm_wqkv, x);
  launch(attn_kernel, 132, AT_THREADS, AT_SMEM, 1, true, wo, wg, wu, wd);
  launch(mlp_kernel, 128, GT, KC_SMEM, 2, true, tm_o, tm_wo64, tm_wo16, tm_h, tm_wg, tm_wu, tm_hhs, tm_hh, tm_wd64, tm_wd16, tm_hs, tm_out, x);
}
```

```cpp
#include <cuda_runtime.h>
#include <cuda_bf16.h>
#include <cuda.h>
#include <stdint.h>

typedef __nv_bfloat16 bf16;
#define FLAGV 0

constexpr int SEQ = 2048, DM = 640, NH = 32, DH = 20, FF = 1536;
constexpr float ATT_SCALE_LOG2E = 0.22360679774997896f * 1.4426950408889634f;
constexpr int IMG_HEAD_ELEMS = (SEQ / 8) * 192;

__device__ __align__(1024) bf16 g_img[3 * NH * IMG_HEAD_ELEMS];
__device__ __align__(1024) bf16 g_o[SEQ * DM];
__device__ __align__(1024) bf16 g_h[SEQ * DM];
__device__ float2 g_stats[SEQ * 8];
__device__ float g_cs[2 * FF];
__device__ int g_flag[4 * 16];
__device__ float2 g_rs[SEQ];
__device__ float g_csp[16 * 3 * DM];
__device__ __align__(1024) bf16 g_hh[SEQ * FF];

#define TS(k, i)
#define PH(w, t, i)
__device__ __forceinline__ uint32_t smem_u32(const void* p) { return (uint32_t)__cvta_generic_to_shared(p); }
__device__ __forceinline__ void mbar_init(uint32_t bar, uint32_t cnt) {
  asm volatile("mbarrier.init.shared::cta.b64 [%0], %1;" ::"r"(bar), "r"(cnt) : "memory");
}
__device__ __forceinline__ void mbar_expect_tx(uint32_t bar, uint32_t bytes) {
  asm volatile("mbarrier.arrive.expect_tx.shared::cta.b64 _, [%0], %1;" ::"r"(bar), "r"(bytes) : "memory");
}
__device__ __forceinline__ void mbar_arrive(uint32_t bar) {
  asm volatile("mbarrier.arrive.shared::cta.b64 _, [%0];" ::"r"(bar) : "memory");
}
__device__ __forceinline__ void mbar_arrive_cluster(uint32_t bar, uint32_t cta) {
  asm volatile(
      "{\n.reg .b32 r;\nmapa.shared::cluster.u32 r, %0, %1;\n"
      "mbarrier.arrive.shared::cluster.b64 _, [r];\n}\n" ::"r"(bar), "r"(cta)
      : "memory");
}
__device__ __forceinline__ void mbar_wait(uint32_t bar, uint32_t parity) {
  asm volatile(
      "{\n.reg .pred p;\nLAB_WAIT:\n"
      "mbarrier.try_wait.parity.shared::cta.b64 p, [%0], %1;\n"
      "@p bra DONE;\nbra LAB_WAIT;\nDONE:\n}\n" ::"r"(bar), "r"(parity)
      : "memory");
}
__device__ __forceinline__ void mbar_wait_cluster(uint32_t bar, uint32_t parity) {
  asm volatile(
      "{\n.reg .pred p;\nLAB_WAIT:\n"
      "mbarrier.try_wait.parity.acquire.cluster.shared::cta.b64 p, [%0], %1;\n"
      "@p bra DONE;\nbra LAB_WAIT;\nDONE:\n}\n" ::"r"(bar), "r"(parity)
      : "memory");
}
__device__ __forceinline__ void fence_mbar_init() { asm volatile("fence.mbarrier_init.release.cluster;" ::: "memory"); }
__device__ __forceinline__ void fence_proxy_async() { asm volatile("fence.proxy.async.shared::cta;" ::: "memory"); }
__device__ __forceinline__ void cluster_sync_all() {
  asm volatile("barrier.cluster.arrive.release.aligned;\nbarrier.cluster.wait.acquire.aligned;" ::: "memory");
}
__device__ __forceinline__ void cluster_sync_relaxed() {
  asm volatile("barrier.cluster.arrive.relaxed.aligned;\nbarrier.cluster.wait.aligned;" ::: "memory");
}
__device__ __forceinline__ void named_bar_sync(int id, int n) { asm volatile("bar.sync %0, %1;" ::"r"(id), "r"(n) : "memory"); }
__device__ __forceinline__ bool wg_any(bool pred, int id) {
  uint32_t r;
  asm volatile("{\n.reg .pred p, q;\nsetp.ne.u32 p, %1, 0;\nbar.red.or.pred q, %2, 128, p;\nselp.u32 %0, 1, 0, q;\n}\n" : "=r"(r) : "r"((uint32_t)pred), "r"(id) : "memory");
  return r != 0;
}
__device__ __forceinline__ void fence_proxy_async_all() { asm volatile("fence.proxy.async;" ::: "memory"); }
__device__ __forceinline__ void flag_signal(int* f) {
  __threadfence();
  atomicAdd(f, 1);
}
__device__ __forceinline__ void flag_wait(const int* f, int target) {
  int v;
  unsigned spins = 0;
  do {
    asm volatile("ld.acquire.gpu.global.s32 %0, [%1];" : "=r"(v) : "l"(f) : "memory");
    if (++spins > (1u << 24)) __trap();
  } while (v < target);
}
__device__ __forceinline__ void pdl_launch() { asm volatile("griddepcontrol.launch_dependents;" ::: "memory"); }
__device__ __forceinline__ void pdl_wait() { asm volatile("griddepcontrol.wait;" ::: "memory"); }

__device__ __forceinline__ void tma_load_2d(uint32_t dst, const CUtensorMap* tm, int c0, int c1, uint32_t bar) {
  asm volatile(
      "cp.async.bulk.tensor.2d.shared::cluster.global.mbarrier::complete_tx::bytes [%0], [%1, {%3, %4}], [%2];" ::"r"(dst),
      "l"((uint64_t)tm), "r"(bar), "r"(c0), "r"(c1)
      : "memory");
}
__device__ __forceinline__ void tma_load_2d_mc(uint32_t dst, const CUtensorMap* tm, int c0, int c1, uint32_t bar, uint16_t mask) {
  asm volatile(
      "cp.async.bulk.tensor.2d.shared::cluster.global.mbarrier::complete_tx::bytes.multicast::cluster [%0], [%1, {%3, %4}], [%2], %5;" ::"r"(dst),
      "l"((uint64_t)tm), "r"(bar), "r"(c0), "r"(c1), "h"(mask)
      : "memory");
}
__device__ __forceinline__ void bulk_g2s(uint32_t dst, const void* src, uint32_t bytes, uint32_t bar) {
  asm volatile("cp.async.bulk.shared::cluster.global.mbarrier::complete_tx::bytes [%0], [%1], %2, [%3];" ::"r"(dst), "l"(src),
               "r"(bytes), "r"(bar)
               : "memory");
}
__device__ __forceinline__ void bulk_s2g(void* dst, uint32_t src, uint32_t bytes) {
  asm volatile("cp.async.bulk.global.shared::cta.bulk_group [%0], [%1], %2;" ::"l"(dst), "r"(src), "r"(bytes) : "memory");
}
__device__ __forceinline__ void tma_store_2d(const CUtensorMap* tm, uint32_t src, int c0, int c1) {
  asm volatile("cp.async.bulk.tensor.2d.global.shared::cta.bulk_group [%0, {%2, %3}], [%1];" ::"l"((uint64_t)tm), "r"(src), "r"(c0), "r"(c1) : "memory");
}
__device__ __forceinline__ void bulk_commit() { asm volatile("cp.async.bulk.commit_group;" ::: "memory"); }
__device__ __forceinline__ void bulk_wait_read() { asm volatile("cp.async.bulk.wait_group.read 0;" ::: "memory"); }
__device__ __forceinline__ void prefetch_l2(const void* p, uint32_t bytes) {
  asm volatile("cp.async.bulk.prefetch.L2.global [%0], %1;" ::"l"(p), "r"(bytes) : "memory");
}
__device__ __forceinline__ void bulk_wait_all() { asm volatile("cp.async.bulk.wait_group 0;" ::: "memory"); }
__device__ __forceinline__ void st_shared_b32(uint32_t addr, uint32_t v) { asm volatile("st.shared.b32 [%0], %1;" ::"r"(addr), "r"(v) : "memory"); }
__device__ __forceinline__ void st_shared_v2(uint32_t addr, uint32_t a, uint32_t b) { asm volatile("st.shared.v2.b32 [%0], {%1, %2};" ::"r"(addr), "r"(a), "r"(b) : "memory"); }
__device__ __forceinline__ void prefetch_tmap(const CUtensorMap* tm) {
  asm volatile("prefetch.tensormap [%0];" ::"l"((uint64_t)tm) : "memory");
}
__device__ __forceinline__ void wgmma_fence() { asm volatile("wgmma.fence.sync.aligned;" ::: "memory"); }
__device__ __forceinline__ void wgmma_commit() { asm volatile("wgmma.commit_group.sync.aligned;" ::: "memory"); }
template <int N>
__device__ __forceinline__ void wgmma_wait() { asm volatile("wgmma.wait_group.sync.aligned %0;" ::"n"(N) : "memory"); }

template <int N>
__device__ __forceinline__ void fence_regs(float (&r)[N]) {
#pragma unroll
  for (int i = 0; i < N; i++) asm volatile("" : "+f"(r[i])::"memory");
}
template <int N>
__device__ __forceinline__ void fence_regs(uint32_t (&r)[N]) {
#pragma unroll
  for (int i = 0; i < N; i++) asm volatile("" : "+r"(r[i])::"memory");
}
__device__ __forceinline__ uint64_t make_desc(uint32_t addr, uint32_t lbo, uint32_t sbo, uint32_t layout) {
  return (uint64_t)((addr & 0x3FFFF) >> 4) | ((uint64_t)((lbo & 0x3FFFF) >> 4) << 16) | ((uint64_t)((sbo & 0x3FFFF) >> 4) << 32) |
         ((uint64_t)layout << 62);
}
__device__ __forceinline__ uint32_t pack_bf16(float lo, float hi) {
  uint32_t r;
  asm("cvt.rn.bf16x2.f32 %0, %1, %2;" : "=r"(r) : "f"(hi), "f"(lo));
  return r;
}
__device__ __forceinline__ float bf16_round(float x) { return __bfloat162float(__float2bfloat16_rn(x)); }
__device__ __forceinline__ float bf_lo(uint32_t u) { return __uint_as_float(u << 16); }
__device__ __forceinline__ float bf_hi(uint32_t u) { return __uint_as_float(u & 0xffff0000u); }
__device__ __forceinline__ float ex2(float x) {
  float y;
  asm("ex2.approx.ftz.f32 %0, %1;" : "=f"(y) : "f"(x));
  return y;
}

__device__ __forceinline__ void wgmma_ss_n240_tb(float (&d)[120], uint64_t descA, uint64_t descB, int scaleD) {
  asm volatile("{\n.reg .pred p;\nsetp.ne.b32 p, %122, 0;\n"
    "wgmma.mma_async.sync.aligned.m64n240k16.f32.bf16.bf16 {%0, %1, %2, %3, %4, %5, %6, %7, %8, %9, %10, %11, %12, %13, %14, %15, %16, %17, %18, %19, %20, %21, %22, %23, %24, %25, %26, %27, %28, %29, %30, %31, %32, %33, %34, %35, %36, %37, %38, %39, %40, %41, %42, %43, %44, %45, %46, %47, %48, %49, %50, %51, %52, %53, %54, %55, %56, %57, %58, %59, %60, %61, %62, %63, %64, %65, %66, %67, %68, %69, %70, %71, %72, %73, %74, %75, %76, %77, %78, %79, %80, %81, %82, %83, %84, %85, %86, %87, %88, %89, %90, %91, %92, %93, %94, %95, %96, %97, %98, %99, %100, %101, %102, %103, %104, %105, %106, %107, %108, %109, %110, %111, %112, %113, %114, %115, %116, %117, %118, %119}, %120, %121, p, 1, 1, 0, 1;\n}\n"
    : "+f"(d[0]), "+f"(d[1]), "+f"(d[2]), "+f"(d[3]), "+f"(d[4]), "+f"(d[5]), "+f"(d[6]), "+f"(d[7]), "+f"(d[8]), "+f"(d[9]), "+f"(d[10]), "+f"(d[11]), "+f"(d[12]), "+f"(d[13]), "+f"(d[14]), "+f"(d[15]), "+f"(d[16]), "+f"(d[17]), "+f"(d[18]), "+f"(d[19]), "+f"(d[20]), "+f"(d[21]), "+f"(d[22]), "+f"(d[23]), "+f"(d[24]), "+f"(d[25]), "+f"(d[26]), "+f"(d[27]), "+f"(d[28]), "+f"(d[29]), "+f"(d[30]), "+f"(d[31]), "+f"(d[32]), "+f"(d[33]), "+f"(d[34]), "+f"(d[35]), "+f"(d[36]), "+f"(d[37]), "+f"(d[38]), "+f"(d[39]), "+f"(d[40]), "+f"(d[41]), "+f"(d[42]), "+f"(d[43]), "+f"(d[44]), "+f"(d[45]), "+f"(d[46]), "+f"(d[47]), "+f"(d[48]), "+f"(d[49]), "+f"(d[50]), "+f"(d[51]), "+f"(d[52]), "+f"(d[53]), "+f"(d[54]), "+f"(d[55]), "+f"(d[56]), "+f"(d[57]), "+f"(d[58]), "+f"(d[59]), "+f"(d[60]), "+f"(d[61]), "+f"(d[62]), "+f"(d[63]), "+f"(d[64]), "+f"(d[65]), "+f"(d[66]), "+f"(d[67]), "+f"(d[68]), "+f"(d[69]), "+f"(d[70]), "+f"(d[71]), "+f"(d[72]), "+f"(d[73]), "+f"(d[74]), "+f"(d[75]), "+f"(d[76]), "+f"(d[77]), "+f"(d[78]), "+f"(d[79]), "+f"(d[80]), "+f"(d[81]), "+f"(d[82]), "+f"(d[83]), "+f"(d[84]), "+f"(d[85]), "+f"(d[86]), "+f"(d[87]), "+f"(d[88]), "+f"(d[89]), "+f"(d[90]), "+f"(d[91]), "+f"(d[92]), "+f"(d[93]), "+f"(d[94]), "+f"(d[95]), "+f"(d[96]), "+f"(d[97]), "+f"(d[98]), "+f"(d[99]), "+f"(d[100]), "+f"(d[101]), "+f"(d[102]), "+f"(d[103]), "+f"(d[104]), "+f"(d[105]), "+f"(d[106]), "+f"(d[107]), "+f"(d[108]), "+f"(d[109]), "+f"(d[110]), "+f"(d[111]), "+f"(d[112]), "+f"(d[113]), "+f"(d[114]), "+f"(d[115]), "+f"(d[116]), "+f"(d[117]), "+f"(d[118]), "+f"(d[119])
    : "l"(descA), "l"(descB), "r"(scaleD));
}
__device__ __forceinline__ void wgmma_ss_n192_tb(float (&d)[96], uint64_t descA, uint64_t descB, int scaleD) {
  asm volatile("{\n.reg .pred p;\nsetp.ne.b32 p, %98, 0;\n"
    "wgmma.mma_async.sync.aligned.m64n192k16.f32.bf16.bf16 {%0, %1, %2, %3, %4, %5, %6, %7, %8, %9, %10, %11, %12, %13, %14, %15, %16, %17, %18, %19, %20, %21, %22, %23, %24, %25, %26, %27, %28, %29, %30, %31, %32, %33, %34, %35, %36, %37, %38, %39, %40, %41, %42, %43, %44, %45, %46, %47, %48, %49, %50, %51, %52, %53, %54, %55, %56, %57, %58, %59, %60, %61, %62, %63, %64, %65, %66, %67, %68, %69, %70, %71, %72, %73, %74, %75, %76, %77, %78, %79, %80, %81, %82, %83, %84, %85, %86, %87, %88, %89, %90, %91, %92, %93, %94, %95}, %96, %97, p, 1, 1, 0, 1;\n}\n"
    : "+f"(d[0]), "+f"(d[1]), "+f"(d[2]), "+f"(d[3]), "+f"(d[4]), "+f"(d[5]), "+f"(d[6]), "+f"(d[7]), "+f"(d[8]), "+f"(d[9]), "+f"(d[10]), "+f"(d[11]), "+f"(d[12]), "+f"(d[13]), "+f"(d[14]), "+f"(d[15]), "+f"(d[16]), "+f"(d[17]), "+f"(d[18]), "+f"(d[19]), "+f"(d[20]), "+f"(d[21]), "+f"(d[22]), "+f"(d[23]), "+f"(d[24]), "+f"(d[25]), "+f"(d[26]), "+f"(d[27]), "+f"(d[28]), "+f"(d[29]), "+f"(d[30]), "+f"(d[31]), "+f"(d[32]), "+f"(d[33]), "+f"(d[34]), "+f"(d[35]), "+f"(d[36]), "+f"(d[37]), "+f"(d[38]), "+f"(d[39]), "+f"(d[40]), "+f"(d[41]), "+f"(d[42]), "+f"(d[43]), "+f"(d[44]), "+f"(d[45]), "+f"(d[46]), "+f"(d[47]), "+f"(d[48]), "+f"(d[49]), "+f"(d[50]), "+f"(d[51]), "+f"(d[52]), "+f"(d[53]), "+f"(d[54]), "+f"(d[55]), "+f"(d[56]), "+f"(d[57]), "+f"(d[58]), "+f"(d[59]), "+f"(d[60]), "+f"(d[61]), "+f"(d[62]), "+f"(d[63]), "+f"(d[64]), "+f"(d[65]), "+f"(d[66]), "+f"(d[67]), "+f"(d[68]), "+f"(d[69]), "+f"(d[70]), "+f"(d[71]), "+f"(d[72]), "+f"(d[73]), "+f"(d[74]), "+f"(d[75]), "+f"(d[76]), "+f"(d[77]), "+f"(d[78]), "+f"(d[79]), "+f"(d[80]), "+f"(d[81]), "+f"(d[82]), "+f"(d[83]), "+f"(d[84]), "+f"(d[85]), "+f"(d[86]), "+f"(d[87]), "+f"(d[88]), "+f"(d[89]), "+f"(d[90]), "+f"(d[91]), "+f"(d[92]), "+f"(d[93]), "+f"(d[94]), "+f"(d[95])
    : "l"(descA), "l"(descB), "r"(scaleD));
}
__device__ __forceinline__ void wgmma_ss_n64_tb(float (&d)[32], uint64_t descA, uint64_t descB, int scaleD) {
  asm volatile("{\n.reg .pred p;\nsetp.ne.b32 p, %34, 0;\n"
    "wgmma.mma_async.sync.aligned.m64n64k16.f32.bf16.bf16 {%0, %1, %2, %3, %4, %5, %6, %7, %8, %9, %10, %11, %12, %13, %14, %15, %16, %17, %18, %19, %20, %21, %22, %23, %24, %25, %26, %27, %28, %29, %30, %31}, %32, %33, p, 1, 1, 0, 1;\n}\n"
    : "+f"(d[0]), "+f"(d[1]), "+f"(d[2]), "+f"(d[3]), "+f"(d[4]), "+f"(d[5]), "+f"(d[6]), "+f"(d[7]), "+f"(d[8]), "+f"(d[9]), "+f"(d[10]), "+f"(d[11]), "+f"(d[12]), "+f"(d[13]), "+f"(d[14]), "+f"(d[15]), "+f"(d[16]), "+f"(d[17]), "+f"(d[18]), "+f"(d[19]), "+f"(d[20]), "+f"(d[21]), "+f"(d[22]), "+f"(d[23]), "+f"(d[24]), "+f"(d[25]), "+f"(d[26]), "+f"(d[27]), "+f"(d[28]), "+f"(d[29]), "+f"(d[30]), "+f"(d[31])
    : "l"(descA), "l"(descB), "r"(scaleD));
}
__device__ __forceinline__ void wgmma_ss_n16_tb(float (&d)[8], uint64_t descA, uint64_t descB, int scaleD) {
  asm volatile("{\n.reg .pred p;\nsetp.ne.b32 p, %10, 0;\n"
    "wgmma.mma_async.sync.aligned.m64n16k16.f32.bf16.bf16 {%0, %1, %2, %3, %4, %5, %6, %7}, %8, %9, p, 1, 1, 0, 1;\n}\n"
    : "+f"(d[0]), "+f"(d[1]), "+f"(d[2]), "+f"(d[3]), "+f"(d[4]), "+f"(d[5]), "+f"(d[6]), "+f"(d[7])
    : "l"(descA), "l"(descB), "r"(scaleD));
}
__device__ __forceinline__ void wgmma_rs_n128(float (&d)[64], uint32_t a0, uint32_t a1, uint32_t a2, uint32_t a3, uint64_t descB, int scaleD) {
  asm volatile("{\n.reg .pred p;\nsetp.ne.b32 p, %69, 0;\n"
    "wgmma.mma_async.sync.aligned.m64n128k16.f32.bf16.bf16 {%0, %1, %2, %3, %4, %5, %6, %7, %8, %9, %10, %11, %12, %13, %14, %15, %16, %17, %18, %19, %20, %21, %22, %23, %24, %25, %26, %27, %28, %29, %30, %31, %32, %33, %34, %35, %36, %37, %38, %39, %40, %41, %42, %43, %44, %45, %46, %47, %48, %49, %50, %51, %52, %53, %54, %55, %56, %57, %58, %59, %60, %61, %62, %63}, {%64, %65, %66, %67}, %68, p, 1, 1, 0;\n}\n"
    : "+f"(d[0]), "+f"(d[1]), "+f"(d[2]), "+f"(d[3]), "+f"(d[4]), "+f"(d[5]), "+f"(d[6]), "+f"(d[7]), "+f"(d[8]), "+f"(d[9]), "+f"(d[10]), "+f"(d[11]), "+f"(d[12]), "+f"(d[13]), "+f"(d[14]), "+f"(d[15]), "+f"(d[16]), "+f"(d[17]), "+f"(d[18]), "+f"(d[19]), "+f"(d[20]), "+f"(d[21]), "+f"(d[22]), "+f"(d[23]), "+f"(d[24]), "+f"(d[25]), "+f"(d[26]), "+f"(d[27]), "+f"(d[28]), "+f"(d[29]), "+f"(d[30]), "+f"(d[31]), "+f"(d[32]), "+f"(d[33]), "+f"(d[34]), "+f"(d[35]), "+f"(d[36]), "+f"(d[37]), "+f"(d[38]), "+f"(d[39]), "+f"(d[40]), "+f"(d[41]), "+f"(d[42]), "+f"(d[43]), "+f"(d[44]), "+f"(d[45]), "+f"(d[46]), "+f"(d[47]), "+f"(d[48]), "+f"(d[49]), "+f"(d[50]), "+f"(d[51]), "+f"(d[52]), "+f"(d[53]), "+f"(d[54]), "+f"(d[55]), "+f"(d[56]), "+f"(d[57]), "+f"(d[58]), "+f"(d[59]), "+f"(d[60]), "+f"(d[61]), "+f"(d[62]), "+f"(d[63])
    : "r"(a0), "r"(a1), "r"(a2), "r"(a3), "l"(descB), "r"(scaleD));
}
__device__ __forceinline__ void wgmma_rs_n64(float (&d)[32], uint32_t a0, uint32_t a1, uint32_t a2, uint32_t a3, uint64_t descB, int scaleD) {
  asm volatile("{\n.reg .pred p;\nsetp.ne.b32 p, %37, 0;\n"
    "wgmma.mma_async.sync.aligned.m64n64k16.f32.bf16.bf16 {%0, %1, %2, %3, %4, %5, %6, %7, %8, %9, %10, %11, %12, %13, %14, %15, %16, %17, %18, %19, %20, %21, %22, %23, %24, %25, %26, %27, %28, %29, %30, %31}, {%32, %33, %34, %35}, %36, p, 1, 1, 0;\n}\n"
    : "+f"(d[0]), "+f"(d[1]), "+f"(d[2]), "+f"(d[3]), "+f"(d[4]), "+f"(d[5]), "+f"(d[6]), "+f"(d[7]), "+f"(d[8]), "+f"(d[9]), "+f"(d[10]), "+f"(d[11]), "+f"(d[12]), "+f"(d[13]), "+f"(d[14]), "+f"(d[15]), "+f"(d[16]), "+f"(d[17]), "+f"(d[18]), "+f"(d[19]), "+f"(d[20]), "+f"(d[21]), "+f"(d[22]), "+f"(d[23]), "+f"(d[24]), "+f"(d[25]), "+f"(d[26]), "+f"(d[27]), "+f"(d[28]), "+f"(d[29]), "+f"(d[30]), "+f"(d[31])
    : "r"(a0), "r"(a1), "r"(a2), "r"(a3), "l"(descB), "r"(scaleD));
}
__device__ __forceinline__ void wgmma_rs_n24_tb(float (&d)[12], uint32_t a0, uint32_t a1, uint32_t a2, uint32_t a3, uint64_t descB, int scaleD) {
  asm volatile("{\n.reg .pred p;\nsetp.ne.b32 p, %17, 0;\n"
    "wgmma.mma_async.sync.aligned.m64n24k16.f32.bf16.bf16 {%0, %1, %2, %3, %4, %5, %6, %7, %8, %9, %10, %11}, {%12, %13, %14, %15}, %16, p, 1, 1, 1;\n}\n"
    : "+f"(d[0]), "+f"(d[1]), "+f"(d[2]), "+f"(d[3]), "+f"(d[4]), "+f"(d[5]), "+f"(d[6]), "+f"(d[7]), "+f"(d[8]), "+f"(d[9]), "+f"(d[10]), "+f"(d[11])
    : "r"(a0), "r"(a1), "r"(a2), "r"(a3), "l"(descB), "r"(scaleD));
}

constexpr int GT = 384;

__device__ __forceinline__ void release_stage(uint32_t bar, bool leader) {
  if (leader) {
    mbar_arrive_cluster(bar, 0);
    mbar_arrive_cluster(bar, 1);
  }
}

__device__ __forceinline__ float2 ln_row_stats(const bf16* __restrict__ xin, int l16) {
  const uint4* src = reinterpret_cast<const uint4*>(xin);
  uint4 v[5];
#pragma unroll
  for (int j = 0; j < 5; j++) v[j] = __ldg(src + j * 16 + l16);
  float s0 = 0.f, s1 = 0.f, s2 = 0.f, s3 = 0.f;
#pragma unroll
  for (int j = 0; j < 5; j++) {
    s0 += bf_lo(v[j].x) + bf_hi(v[j].x);
    s1 += bf_lo(v[j].y) + bf_hi(v[j].y);
    s2 += bf_lo(v[j].z) + bf_hi(v[j].z);
    s3 += bf_lo(v[j].w) + bf_hi(v[j].w);
  }
  float mean = (s0 + s1) + (s2 + s3);
#pragma unroll
  for (int o = 1; o < 16; o <<= 1) mean += __shfl_xor_sync(0xffffffffu, mean, o);
  mean *= (1.0f / DM);
  s0 = s1 = s2 = s3 = 0.f;
#pragma unroll
  for (int j = 0; j < 5; j++) {
    float d;
    d = bf_lo(v[j].x) - mean; s0 = fmaf(d, d, s0);
    d = bf_hi(v[j].x) - mean; s1 = fmaf(d, d, s1);
    d = bf_lo(v[j].y) - mean; s2 = fmaf(d, d, s2);
    d = bf_hi(v[j].y) - mean; s3 = fmaf(d, d, s3);
    d = bf_lo(v[j].z) - mean; s0 = fmaf(d, d, s0);
    d = bf_hi(v[j].z) - mean; s1 = fmaf(d, d, s1);
    d = bf_lo(v[j].w) - mean; s2 = fmaf(d, d, s2);
    d = bf_hi(v[j].w) - mean; s3 = fmaf(d, d, s3);
  }
  float sq = (s0 + s1) + (s2 + s3);
#pragma unroll
  for (int o = 1; o < 16; o <<= 1) sq += __shfl_xor_sync(0xffffffffu, sq, o);
  const float var_b = bf16_round(sq * (1.0f / DM));
  const float den = bf16_round(sqrtf(bf16_round(var_b + 1e-5f)));
  return make_float2(bf16_round(mean), __frcp_rn(den));
}

constexpr int LG_STAGES = 5;
constexpr int QKV_STAGE = 8192 + 4 * 4096;
constexpr int GLU_STAGE = 8192 + 6 * 4096;

template <int WG>
__device__ __forceinline__ void qkv_mainloop(float (&acc)[120], uint32_t sbase, uint32_t sBar, bool leader) {
  constexpr int STAGE_BYTES = QKV_STAGE, NST = LG_STAGES;
  const uint64_t da_base = make_desc(sbase + WG * 4096, 16, 512, 2);
  const uint64_t db_base = make_desc(sbase + 8192, 4096, 1024, 1);
#pragma unroll 1
  for (int r = 0; r < 20 / NST; r++) {
#pragma unroll
    for (int s = 0; s < NST; s++) {
      mbar_wait(sBar + 8 * s, r & 1);
      wgmma_fence();
#pragma unroll
      for (int ks = 0; ks < 2; ks++)
        wgmma_ss_n240_tb(acc, da_base + (uint64_t)((s * STAGE_BYTES + ks * 32) >> 4), db_base + (uint64_t)((s * STAGE_BYTES + ks * 2048) >> 4), 1);
      wgmma_commit();
      wgmma_wait<1>();
      release_stage(sBar + 8 * (NST + (s + NST - 1) % NST), leader && (s > 0 || r > 0));
    }
  }
}
template <int WG>
__device__ __forceinline__ void glu_mainloop(float (&accg)[96], float (&accu)[96], uint32_t sbase, uint32_t sBar, bool leader) {
  constexpr int STAGE_BYTES = GLU_STAGE, NST = LG_STAGES;
  const uint64_t da_base = make_desc(sbase + WG * 4096, 16, 512, 2);
  const uint64_t db_base = make_desc(sbase + 8192, 4096, 1024, 1);
#pragma unroll 1
  for (int r = 0; r < 20 / NST; r++) {
#pragma unroll
    for (int s = 0; s < NST; s++) {
      mbar_wait(sBar + 8 * s, r & 1);
      wgmma_fence();
#pragma unroll
      for (int ks = 0; ks < 2; ks++) {
        const uint64_t da = da_base + (uint64_t)((s * STAGE_BYTES + ks * 32) >> 4);
        wgmma_ss_n192_tb(accg, da, db_base + (uint64_t)((s * STAGE_BYTES + ks * 2048) >> 4), 1);
        wgmma_ss_n192_tb(accu, da, db_base + (uint64_t)((s * STAGE_BYTES + 3 * 4096 + ks * 2048) >> 4), 1);
      }
      wgmma_commit();
      wgmma_wait<1>();
      release_stage(sBar + 8 * (NST + (s + NST - 1) % NST), leader && (s > 0 || r > 0));
    }
  }
}
constexpr int RG_STAGE_BYTES = 16384 + 8192 + 2048;
template <int NKB, int NST, int WG>
__device__ __forceinline__ void res_mainloop(float (&acc0)[32], float (&acc1)[8], uint32_t sbase, uint32_t sBar, bool leader) {
  const uint64_t da_base = make_desc(sbase + WG * 8192, 16, 1024, 1);
  const uint64_t db0_base = make_desc(sbase + 16384, 8192, 1024, 1);
  const uint64_t db1_base = make_desc(sbase + 16384 + 8192, 2048, 256, 3);
#pragma unroll 1
  for (int r = 0; r < NKB / NST; r++) {
#pragma unroll
    for (int s = 0; s < NST; s++) {
      const uint64_t so = (uint64_t)(s * (RG_STAGE_BYTES >> 4));
      mbar_wait(sBar + 8 * s, r & 1);
      wgmma_fence();
#pragma unroll
      for (int ks = 0; ks < 4; ks++) {
        wgmma_ss_n64_tb(acc0, da_base + so + ks * 2, db0_base + so + ks * 128, 1);
        wgmma_ss_n16_tb(acc1, da_base + so + ks * 2, db1_base + so + ks * 32, 1);
      }
      wgmma_commit();
      wgmma_wait<1>();
      release_stage(sBar + 8 * (NST + (s + NST - 1) % NST), leader && (s > 0 || r > 0));
    }
  }
}

constexpr int KA_CS = LG_STAGES * QKV_STAGE + 128;
constexpr int KA_SMEM = KA_CS + 1024 + 1024;

__global__ void __launch_bounds__(GT, 1)
qkv_kernel(const __grid_constant__ CUtensorMap tmA, const __grid_constant__ CUtensorMap tmB, const bf16* __restrict__ x,
           const bf16* __restrict__ wqkv) {
  constexpr int STAGE_BYTES = QKV_STAGE, NST = LG_STAGES, NKB = 20;
  extern __shared__ uint8_t smem_raw[];
  const uint32_t sbase = (smem_u32(smem_raw) + 1023u) & ~1023u;
  const uint32_t sBar = sbase + NST * STAGE_BYTES;
  const int tid = threadIdx.x, warp = tid >> 5, lane = tid & 31;
  const int rank = blockIdx.x & 1;
  const int pair = blockIdx.x >> 1;
  const int n_blk = pair & 7;
  const int m_blk = (pair >> 3) * 2 + rank;
  TS(0, 0);
  if (tid == 256) {
    prefetch_tmap(&tmA);
    prefetch_tmap(&tmB);
  }
  if (tid == 0) {
    for (int s = 0; s < NST; s++) {
      mbar_init(sBar + 8 * s, 1);
      mbar_init(sBar + 8 * (NST + s), 4);
    }
    fence_mbar_init();
    if (blockIdx.x < 32) g_flag[16 + blockIdx.x] = 0;
  }
  pdl_launch();
  cluster_sync_all();

  if (warp >= 8) {
    asm volatile("setmaxnreg.dec.sync.aligned.u32 40;");
    if (tid == 256) {
      auto issue_b = [&](int kb) {
        const int s = kb % NST;
        const uint32_t full = sBar + 8 * s;
        mbar_expect_tx(full, STAGE_BYTES);
        const uint32_t dst = sbase + s * STAGE_BYTES + 8192;
#pragma unroll
        for (int j = 0; j < 2; j++) {
          const int sl = rank * 2 + j;
          tma_load_2d_mc(dst + sl * 4096, &tmB, n_blk * 240 + sl * 64, kb * 32, full, (uint16_t)3);
        }
      };
      for (int kb = 0; kb < NKB; kb++) {
        const int s = kb % NST;
        if (kb >= NST) mbar_wait(sBar + 8 * (NST + s), ((kb / NST) & 1) ^ 1);
        issue_b(kb);
        tma_load_2d(sbase + s * STAGE_BYTES, &tmA, kb * 32, m_blk * 128, sBar + 8 * s);
      }
    }
  } else {
    asm volatile("setmaxnreg.inc.sync.aligned.u32 232;");
    const int wg = __shfl_sync(0xffffffffu, warp >> 2, 0);
    const int wwarp = warp & 3;
    {
      float cs = 0.f;
      if (tid < 240) {
        const bf16* w = wqkv + (size_t)(m_blk * 40) * (3 * DM) + n_blk * 240 + tid;
#pragma unroll 8
        for (int r = 0; r < 40; r++) cs += __bfloat162float(w[(size_t)r * (3 * DM)]);
      }
      const int row = m_blk * 128 + n_blk * 16 + warp * 2 + (lane >> 4);
      const float2 rs = ln_row_stats(x + (size_t)row * DM, lane & 15);
      if ((lane & 15) == 0) g_rs[row] = rs;
      if (tid < 240) g_csp[m_blk * (3 * DM) + n_blk * 240 + tid] = cs;
      named_bar_sync(3, 256);
      if (tid == 0) {
        __threadfence();
        atomicAdd(&g_flag[m_blk], 1);
        atomicAdd(&g_flag[48 + n_blk], 1);
      }
    }
    TS(0, 1);
    mbar_wait(sBar, 0);
    TS(0, 3);
    float acc[120];
#pragma unroll
    for (int i = 0; i < 120; i++) acc[i] = 0.f;
    if (wg == 0) qkv_mainloop<0>(acc, sbase, sBar, (tid & 127) == 0);
    else qkv_mainloop<1>(acc, sbase, sBar, (tid & 127) == 0);
    wgmma_wait<0>();
    fence_regs(acc);
    TS(0, 4);
    const int g = lane >> 2, c4 = lane & 3;
    float* cs_s = reinterpret_cast<float*>(smem_raw + (sbase - smem_u32(smem_raw)) + KA_CS);
    flag_wait(&g_flag[m_blk], 8);
    flag_wait(&g_flag[48 + n_blk], 16);
    if (tid < 240) {
      float c = 0.f;
#pragma unroll
      for (int mm = 0; mm < 16; mm++) c += g_csp[mm * (3 * DM) + n_blk * 240 + tid];
      cs_s[tid] = c;
    }
    const float2 rs0 = g_rs[m_blk * 128 + wg * 64 + wwarp * 16 + g], rs1 = g_rs[m_blk * 128 + wg * 64 + wwarp * 16 + g + 8];
    named_bar_sync(3, 256);
    const uint32_t stg = sbase + wg * (12 * 3072) + (wwarp * 2) * 384 + g * 16;
    const int hbase = n_blk * 12;
#pragma unroll
    for (int j = 0; j < 30; j++) {
      const int cb = (j * 8) % 20;
      const int hb = (j * 8) / 20;
      int d = cb + c4 * 2;
      int hl = hb;
      if (cb == 16 && c4 >= 2) { d -= 20; hl += 1; }
      const uint32_t a0 = stg + hl * 3072 + (d >> 3) * 128 + (d & 7) * 2;
      const int hg = hbase + hl;
      const float sc = hg < 32 ? ATT_SCALE_LOG2E : 1.0f;
      const float2 cc = *reinterpret_cast<const float2*>(cs_s + j * 8 + c4 * 2);
      const float i0 = rs0.y * sc, i1 = rs1.y * sc;
      st_shared_b32(a0, pack_bf16(fmaf(-rs0.x, cc.x, acc[4 * j]) * i0, fmaf(-rs0.x, cc.y, acc[4 * j + 1]) * i0));
      st_shared_b32(a0 + 384, pack_bf16(fmaf(-rs1.x, cc.x, acc[4 * j + 2]) * i1, fmaf(-rs1.x, cc.y, acc[4 * j + 3]) * i1));
      if (d == 18) {
        const uint32_t pad0 = hg < 32 ? 0u : (hg < 64 ? 0x3f803f80u : 0x00003f80u);
        const uint32_t pad1 = (hg >= 32 && hg < 64) ? 0x00003f80u : 0u;
        st_shared_v2(a0 + 4, pad0, pad1);
        st_shared_v2(a0 + 388, pad0, pad1);
      }
      if (j % 10 == 9) {
        fence_proxy_async();
        named_bar_sync(1 + wg, 128);
        if ((tid & 127) < 4) {
          const int hs = (j / 10) * 4 + (tid & 127);
          bf16* dst = g_img + (size_t)(hbase + hs) * IMG_HEAD_ELEMS + (size_t)(m_blk * 16 + wg * 8) * 192;
          bulk_s2g(dst, sbase + wg * (12 * 3072) + hs * 3072, 3072);
          bulk_commit();
        }
      }
    }
    if ((tid & 127) < 4) bulk_wait_read();
  }
  __syncwarp();
  TS(0, 5);
  cluster_sync_relaxed();
  TS(0, 6);
}

constexpr int KC_NST1 = 5, KC_NST3 = 6;
constexpr int KC_STAGING = 160 * 1024;
constexpr int KC_BAR = KC_STAGING + 48 * 1024;
constexpr int KC_CS = KC_BAR + 512;
constexpr int KC_SMEM = KC_CS + 1536 + 1024;

__global__ void __launch_bounds__(GT, 1)
mlp_kernel(const __grid_constant__ CUtensorMap tmO, const __grid_constant__ CUtensorMap tmWo64, const __grid_constant__ CUtensorMap tmWo16,
           const __grid_constant__ CUtensorMap tmH, const __grid_constant__ CUtensorMap tmWg, const __grid_constant__ CUtensorMap tmWu,
           const __grid_constant__ CUtensorMap tmHHs, const __grid_constant__ CUtensorMap tmHH, const __grid_constant__ CUtensorMap tmWd64,
           const __grid_constant__ CUtensorMap tmWd16, const __grid_constant__ CUtensorMap tmHs, const __grid_constant__ CUtensorMap tmOut,
           const bf16* __restrict__ x) {
  extern __shared__ uint8_t smem_raw[];
  const uint32_t sbase = (smem_u32(smem_raw) + 1023u) & ~1023u;
  const uint32_t bar1 = sbase + KC_BAR;
  const uint32_t bar2 = bar1 + 128;
  const uint32_t bar3 = bar2 + 128;
  const uint32_t barD = bar3 + 128;
  const int tid = threadIdx.x, warp = tid >> 5, lane = tid & 31;
  const int rank = blockIdx.x & 1;
  const int pair = blockIdx.x >> 1;
  const int j_blk = pair & 7;
  const int m_blk = (pair >> 3) * 2 + rank;
  const int n0 = j_blk * 80;
  TS(2, 0);
  if (tid == 256) {
    prefetch_tmap(&tmO); prefetch_tmap(&tmWo64); prefetch_tmap(&tmWo16); prefetch_tmap(&tmH); prefetch_tmap(&tmWg);
    prefetch_tmap(&tmWu); prefetch_tmap(&tmHHs); prefetch_tmap(&tmHH); prefetch_tmap(&tmWd64); prefetch_tmap(&tmWd16);
    prefetch_tmap(&tmHs); prefetch_tmap(&tmOut);
  }
  if (tid == 0) {
    for (int s = 0; s < 5; s++) {
      mbar_init(bar1 + 8 * s, 1); mbar_init(bar1 + 8 * (5 + s), 4);
      mbar_init(bar2 + 8 * s, 1); mbar_init(bar2 + 8 * (5 + s), 4);
    }
    for (int s = 0; s < 6; s++) { mbar_init(bar3 + 8 * s, 1); mbar_init(bar3 + 8 * (6 + s), 4); }
    mbar_init(barD, 4); mbar_init(barD + 8, 4);
    fence_mbar_init();
  }
  cluster_sync_all();

  if (warp >= 8) {
    asm volatile("setmaxnreg.dec.sync.aligned.u32 40;");
    if (tid == 256) {
      auto issue_b80 = [&](const CUtensorMap* t64, const CUtensorMap* t16, uint32_t bars, int nst, int kb) {
        const int s = kb % nst;
        const uint32_t full = bars + 8 * s;
        const uint32_t st = sbase + s * RG_STAGE_BYTES;
        mbar_expect_tx(full, RG_STAGE_BYTES);
        tma_load_2d_mc(st + 16384 + rank * 4096, t64, n0, kb * 64 + rank * 32, full, (uint16_t)3);
        tma_load_2d_mc(st + 16384 + 8192 + rank * 1024, t16, n0 + 64, kb * 64 + rank * 32, full, (uint16_t)3);
      };
      for (int kb = 0; kb < KC_NST1; kb++) issue_b80(&tmWo64, &tmWo16, bar1, KC_NST1, kb);
      pdl_wait();
      for (int kb = 0; kb < 10; kb++) {
        const int s = kb % KC_NST1;
        if (kb >= KC_NST1) {
          mbar_wait(bar1 + 8 * (KC_NST1 + s), ((kb / KC_NST1) & 1) ^ 1);
          issue_b80(&tmWo64, &tmWo16, bar1, KC_NST1, kb);
        }
        tma_load_2d(sbase + s * RG_STAGE_BYTES, &tmO, kb * 64, m_blk * 128, bar1 + 8 * s);
      }
      auto issue_bglu = [&](int kb) {
        const int s = kb % LG_STAGES;
        const uint32_t full = bar2 + 8 * s;
        mbar_expect_tx(full, GLU_STAGE);
        const uint32_t dst = sbase + s * GLU_STAGE + 8192;
#pragma unroll
        for (int j = 0; j < 3; j++)
          tma_load_2d_mc(dst + (rank * 3 + j) * 4096, rank == 0 ? &tmWg : &tmWu, j_blk * 192 + j * 64, kb * 32, full, (uint16_t)3);
      };
      mbar_wait(barD, 0);
      for (int kb = 0; kb < LG_STAGES; kb++) issue_bglu(kb);
      flag_wait(&g_flag[16 + m_blk], 16);
      fence_proxy_async_all();
      for (int kb = 0; kb < 20; kb++) {
        const int s = kb % LG_STAGES;
        if (kb >= LG_STAGES) {
          mbar_wait(bar2 + 8 * (LG_STAGES + s), ((kb / LG_STAGES) & 1) ^ 1);
          issue_bglu(kb);
        }
        tma_load_2d(sbase + s * GLU_STAGE, &tmH, kb * 32, m_blk * 128, bar2 + 8 * s);
      }
      mbar_wait(barD + 8, 0);
      for (int kb = 0; kb < KC_NST3; kb++) issue_b80(&tmWd64, &tmWd16, bar3, KC_NST3, kb);
      flag_wait(&g_flag[32 + m_blk], 16);
      fence_proxy_async_all();
      for (int kb = 0; kb < 24; kb++) {
        const int s = kb % KC_NST3;
        if (kb >= KC_NST3) {
          mbar_wait(bar3 + 8 * (KC_NST3 + s), ((kb / KC_NST3) & 1) ^ 1);
          issue_b80(&tmWd64, &tmWd16, bar3, KC_NST3, kb);
        }
        tma_load_2d(sbase + s * RG_STAGE_BYTES, &tmHH, kb * 64, m_blk * 128, bar3 + 8 * s);
      }
    }
  } else {
    asm volatile("setmaxnreg.inc.sync.aligned.u32 232;");
    const int wg = __shfl_sync(0xffffffffu, warp >> 2, 0);
    const int wwarp = warp & 3;
    const int g = lane >> 2, c4 = lane & 3;
    const int row0 = m_blk * 128 + wg * 64 + wwarp * 16 + g;
    const bool leader = (tid & 127) == 0;
    const uint32_t stg80_base = sbase + KC_STAGING + wg * 24576;
    const uint32_t stg80 = stg80_base + (wwarp * 16 + g) * 160 + c4 * 4;
    {
      uint32_t res[20];
#pragma unroll
      for (int j = 0; j < 10; j++) {
        res[2 * j] = __ldg(reinterpret_cast<const uint32_t*>(x + (size_t)row0 * DM + n0 + j * 8 + c4 * 2));
        res[2 * j + 1] = __ldg(reinterpret_cast<const uint32_t*>(x + (size_t)(row0 + 8) * DM + n0 + j * 8 + c4 * 2));
      }
      float acc0[32], acc1[8];
#pragma unroll
      for (int i = 0; i < 32; i++) acc0[i] = 0.f;
#pragma unroll
      for (int i = 0; i < 8; i++) acc1[i] = 0.f;
      TS(2, 1);
      if (wg == 0) res_mainloop<10, KC_NST1, 0>(acc0, acc1, sbase, bar1, leader);
      else res_mainloop<10, KC_NST1, 1>(acc0, acc1, sbase, bar1, leader);
      wgmma_wait<0>();
      fence_regs(acc0); fence_regs(acc1);
      release_stage(barD, leader);
      TS(2, 4);
      float sum0 = 0.f, sum1 = 0.f;
#pragma unroll
      for (int j = 0; j < 10; j++) {
        const uint32_t a01 = j < 8 ? pack_bf16(acc0[4 * j], acc0[4 * j + 1]) : pack_bf16(acc1[4 * (j - 8)], acc1[4 * (j - 8) + 1]);
        const uint32_t a23 = j < 8 ? pack_bf16(acc0[4 * j + 2], acc0[4 * j + 3]) : pack_bf16(acc1[4 * (j - 8) + 2], acc1[4 * (j - 8) + 3]);
        res[2 * j] = pack_bf16(bf_lo(res[2 * j]) + bf_lo(a01), bf_hi(res[2 * j]) + bf_hi(a01));
        res[2 * j + 1] = pack_bf16(bf_lo(res[2 * j + 1]) + bf_lo(a23), bf_hi(res[2 * j + 1]) + bf_hi(a23));
        st_shared_b32(stg80 + j * 16, res[2 * j]);
        st_shared_b32(stg80 + 8 * 160 + j * 16, res[2 * j + 1]);
        sum0 += bf_lo(res[2 * j]) + bf_hi(res[2 * j]);
        sum1 += bf_lo(res[2 * j + 1]) + bf_hi(res[2 * j + 1]);
      }
      sum0 += __shfl_xor_sync(0xffffffffu, sum0, 1); sum1 += __shfl_xor_sync(0xffffffffu, sum1, 1);
      sum0 += __shfl_xor_sync(0xffffffffu, sum0, 2); sum1 += __shfl_xor_sync(0xffffffffu, sum1, 2);
      const float mu0 = sum0 * (1.0f / 80.0f), mu1 = sum1 * (1.0f / 80.0f);
      float q0 = 0.f, q1 = 0.f;
#pragma unroll
      for (int j = 0; j < 10; j++) {
        float d;
        d = bf_lo(res[2 * j]) - mu0; q0 = fmaf(d, d, q0);
        d = bf_hi(res[2 * j]) - mu0; q0 = fmaf(d, d, q0);
        d = bf_lo(res[2 * j + 1]) - mu1; q1 = fmaf(d, d, q1);
        d = bf_hi(res[2 * j + 1]) - mu1; q1 = fmaf(d, d, q1);
      }
      q0 += __shfl_xor_sync(0xffffffffu, q0, 1); q1 += __shfl_xor_sync(0xffffffffu, q1, 1);
      q0 += __shfl_xor_sync(0xffffffffu, q0, 2); q1 += __shfl_xor_sync(0xffffffffu, q1, 2);
      if (c4 == 0) {
        g_stats[row0 * 8 + j_blk] = make_float2(mu0, q0);
        g_stats[(row0 + 8) * 8 + j_blk] = make_float2(mu1, q1);
      }
      fence_proxy_async();
      named_bar_sync(1 + wg, 128);
      if (leader) {
        tma_store_2d(&tmHs, stg80_base, n0, m_blk * 128 + wg * 64);
        bulk_commit();
        bulk_wait_all();
        fence_proxy_async_all();
        flag_signal(&g_flag[16 + m_blk]);
      }
      TS(2, 5);
    }
    {
      pdl_wait();
      {
        float* cs_s = reinterpret_cast<float*>(smem_raw + (sbase - smem_u32(smem_raw)) + KC_CS);
        for (int i = tid; i < 384; i += 256) cs_s[i] = g_cs[(i >= 192 ? FF - 192 : 0) + j_blk * 192 + i];
        named_bar_sync(3, 256);
      }
      flag_wait(&g_flag[16 + m_blk], 16);
      float mb[2], iv[2];
#pragma unroll
      for (int h = 0; h < 2; h++) {
        const float4* sp = reinterpret_cast<const float4*>(g_stats + (row0 + 8 * h) * 8);
        const float4 p0 = sp[0], p1 = sp[1], p2 = sp[2], p3 = sp[3];
        const float mean = (((p0.x + p0.z) + (p1.x + p1.z)) + ((p2.x + p2.z) + (p3.x + p3.z))) * 0.125f;
        float m2 = ((p0.y + p0.w) + (p1.y + p1.w)) + ((p2.y + p2.w) + (p3.y + p3.w));
        float dd = 0.f, d;
        d = p0.x - mean; dd = fmaf(d, d, dd); d = p0.z - mean; dd = fmaf(d, d, dd);
        d = p1.x - mean; dd = fmaf(d, d, dd); d = p1.z - mean; dd = fmaf(d, d, dd);
        d = p2.x - mean; dd = fmaf(d, d, dd); d = p2.z - mean; dd = fmaf(d, d, dd);
        d = p3.x - mean; dd = fmaf(d, d, dd); d = p3.z - mean; dd = fmaf(d, d, dd);
        m2 = fmaf(dd, 80.0f, m2);
        const float var_b = bf16_round(m2 * (1.0f / DM));
        const float den = bf16_round(sqrtf(bf16_round(var_b + 1e-5f)));
        iv[h] = __frcp_rn(den);
        mb[h] = bf16_round(mean);
      }
      float accg[96], accu[96];
#pragma unroll
      for (int i = 0; i < 96; i++) { accg[i] = 0.f; accu[i] = 0.f; }
      TS(3, 3);
      if (wg == 0) glu_mainloop<0>(accg, accu, sbase, bar2, leader);
      else glu_mainloop<1>(accg, accu, sbase, bar2, leader);
      wgmma_wait<0>();
      fence_regs(accg); fence_regs(accu);
      release_stage(barD + 8, leader);
      TS(3, 4);
      const uint32_t stg = sbase + KC_STAGING + wg * 24576 + (wwarp * 16 + g) * 128 + c4 * 4;
      const float* csg = reinterpret_cast<const float*>(smem_raw + (sbase - smem_u32(smem_raw)) + KC_CS) + c4 * 2;
      const float nm0 = -mb[0] * iv[0], nm1 = -mb[1] * iv[1];
#pragma unroll
      for (int sl = 0; sl < 3; sl++) {
#pragma unroll
        for (int jj = 0; jj < 8; jj++) {
          const int j = sl * 8 + jj;
          const float2 cg = *reinterpret_cast<const float2*>(csg + j * 8);
          const float2 cu = *reinterpret_cast<const float2*>(csg + 192 + j * 8);
          const float r0 = fmaxf(fmaf(accg[4 * j], iv[0], nm0 * cg.x), 0.f) * fmaf(accu[4 * j], iv[0], nm0 * cu.x);
          const float r1 = fmaxf(fmaf(accg[4 * j + 1], iv[0], nm0 * cg.y), 0.f) * fmaf(accu[4 * j + 1], iv[0], nm0 * cu.y);
          const float r2 = fmaxf(fmaf(accg[4 * j + 2], iv[1], nm1 * cg.x), 0.f) * fmaf(accu[4 * j + 2], iv[1], nm1 * cu.x);
          const float r3 = fmaxf(fmaf(accg[4 * j + 3], iv[1], nm1 * cg.y), 0.f) * fmaf(accu[4 * j + 3], iv[1], nm1 * cu.y);
          const uint32_t a0 = stg + sl * 8192 + ((jj ^ g) << 4);
          st_shared_b32(a0, pack_bf16(r0, r1));
          st_shared_b32(a0 + 1024, pack_bf16(r2, r3));
        }
        fence_proxy_async();
        named_bar_sync(1 + wg, 128);
        if (leader) {
          tma_store_2d(&tmHHs, sbase + KC_STAGING + wg * 24576 + sl * 8192, j_blk * 192 + sl * 64, m_blk * 128 + wg * 64);
          bulk_commit();
        }
      }
      TS(3, 7);
      if (leader) {
        bulk_wait_all();
        TS(3, 8);
        fence_proxy_async_all();
        flag_signal(&g_flag[32 + m_blk]);
      }
      TS(3, 9);
    }
    {
      uint32_t res[20];
#pragma unroll
      for (int j = 0; j < 10; j++) {
        res[2 * j] = *reinterpret_cast<const uint32_t*>(g_h + (size_t)row0 * DM + n0 + j * 8 + c4 * 2);
        res[2 * j + 1] = *reinterpret_cast<const uint32_t*>(g_h + (size_t)(row0 + 8) * DM + n0 + j * 8 + c4 * 2);
      }
      float acc0[32], acc1[8];
#pragma unroll
      for (int i = 0; i < 32; i++) acc0[i] = 0.f;
#pragma unroll
      for (int i = 0; i < 8; i++) acc1[i] = 0.f;
      mbar_wait(bar3, 0);
      TS(4, 3);
      if (wg == 0) res_mainloop<24, KC_NST3, 0>(acc0, acc1, sbase, bar3, leader);
      else res_mainloop<24, KC_NST3, 1>(acc0, acc1, sbase, bar3, leader);
      wgmma_wait<0>();
      fence_regs(acc0); fence_regs(acc1);
      TS(4, 4);
#pragma unroll
      for (int j = 0; j < 10; j++) {
        const uint32_t a01 = j < 8 ? pack_bf16(acc0[4 * j], acc0[4 * j + 1]) : pack_bf16(acc1[4 * (j - 8)], acc1[4 * (j - 8) + 1]);
        const uint32_t a23 = j < 8 ? pack_bf16(acc0[4 * j + 2], acc0[4 * j + 3]) : pack_bf16(acc1[4 * (j - 8) + 2], acc1[4 * (j - 8) + 3]);
        st_shared_b32(stg80 + j * 16, pack_bf16(bf_lo(res[2 * j]) + bf_lo(a01), bf_hi(res[2 * j]) + bf_hi(a01)));
        st_shared_b32(stg80 + 8 * 160 + j * 16, pack_bf16(bf_lo(res[2 * j + 1]) + bf_lo(a23), bf_hi(res[2 * j + 1]) + bf_hi(a23)));
      }
      fence_proxy_async();
      named_bar_sync(1 + wg, 128);
      if (leader) {
        tma_store_2d(&tmOut, stg80_base, n0, m_blk * 128 + wg * 64);
        bulk_commit();
        bulk_wait_read();
      }
      TS(4, 5);
    }
  }
  __syncwarp();
  cluster_sync_relaxed();
  TS(4, 6);
}

constexpr int AT_THREADS = 512;
constexpr int AT_WGS = AT_THREADS / 128;
#define AT_CHUNK_MASK 3
#define AT_STAGGER 0
constexpr int AT_KV_BYTES = IMG_HEAD_ELEMS * 2;
constexpr int AT_SMEM = 2 * AT_KV_BYTES + 256 + 1024;
constexpr int AT_CHUNKS = 8;

__device__ __forceinline__ float exp2_poly(float x) {
  const float u = __saturatef(fmaf(x, 1.0f / 64.0f, 62.0f / 64.0f));
  const float MAGIC = 12582912.0f - 62.0f;
  const float r = fmaf(u, 64.0f, MAGIC);
  const float q = MAGIC - r;
  const float fr = fmaf(u, 64.0f, q);
  float p = fmaf(fr, 0.009570102207362652f, 0.05591785907745361f);
  p = fmaf(p, fr, 0.240247443318367f);
  p = fmaf(p, fr, 0.6931217908859253f);
  p = fmaf(p, fr, 0.9999992847442627f);
  return __uint_as_float(__float_as_uint(p) + (__float_as_uint(r) << 23));
}
#define AT_VARIANT 0
#define AT_POLY_MOD 8
__device__ __forceinline__ bool use_poly(int e) {
  return (e % AT_POLY_MOD) == 1;
}

struct AttnState {
  uint32_t qa0, qa1, qa2, qa3, qa4, qa5;
  float M0, M1;
};

__device__ __forceinline__ bool attn_exp_fast(const float (&s)[32], uint32_t (&p)[16]) {
#pragma unroll
  for (int j = 0; j < 16; j++) {
    const float e0 = use_poly(2 * j) ? exp2_poly(s[2 * j]) : ex2(s[2 * j]);
    const float e1 = use_poly(2 * j + 1) ? exp2_poly(s[2 * j + 1]) : ex2(s[2 * j + 1]);
    p[j] = pack_bf16(e0, e1);
  }
  uint32_t acc_or = 0;
#pragma unroll
  for (int j = 0; j < 16; j++) acc_or |= p[j];
  return __any_sync(0xffffffffu, (acc_or & 0x40004000u) != 0);
}
__device__ __forceinline__ void attn_exp_exact(const float (&s)[32], uint32_t (&p)[16], float (&o)[12], AttnState& st, bool first, int c4) {
  float mx0 = fmaxf(s[0], s[1]), mx1 = fmaxf(s[2], s[3]);
#pragma unroll
  for (int j = 1; j < 8; j++) {
    mx0 = fmaxf(mx0, fmaxf(s[4 * j], s[4 * j + 1]));
    mx1 = fmaxf(mx1, fmaxf(s[4 * j + 2], s[4 * j + 3]));
  }
  mx0 = fmaxf(mx0, __shfl_xor_sync(0xffffffffu, mx0, 1));
  mx1 = fmaxf(mx1, __shfl_xor_sync(0xffffffffu, mx1, 1));
  mx0 = fmaxf(mx0, __shfl_xor_sync(0xffffffffu, mx0, 2));
  mx1 = fmaxf(mx1, __shfl_xor_sync(0xffffffffu, mx1, 2));
  float d0 = mx0 + 7.0f, d1 = mx1 + 7.0f;
  if (!first) { d0 = fmaxf(d0, 0.f); d1 = fmaxf(d1, 0.f); }
  const float T0 = st.M0 + d0, T1 = st.M1 + d1;
  const float h0 = bf16_round(T0), h1 = bf16_round(T1);
  const float i0 = bf16_round(T0 - h0), i1 = bf16_round(T1 - h1);
  const float l0 = bf16_round((T0 - h0) - i0), l1 = bf16_round((T1 - h1) - i1);
  const float N0 = (h0 + i0) + l0, N1 = (h1 + i1) + l1;
  d0 = N0 - st.M0; d1 = N1 - st.M1;
  st.M0 = N0; st.M1 = N1;
  if (c4 == 2) { st.qa4 = pack_bf16(-h0, -i0); st.qa5 = pack_bf16(-h1, -i1); }
  if (c4 == 3) { st.qa4 = pack_bf16(-l0, 0.f); st.qa5 = pack_bf16(-l1, 0.f); }
  if (!first) {
    const float al0 = ex2(-d0), al1 = ex2(-d1);
#pragma unroll
    for (int j = 0; j < 3; j++) {
      o[4 * j] *= al0; o[4 * j + 1] *= al0;
      o[4 * j + 2] *= al1; o[4 * j + 3] *= al1;
    }
  }
#pragma unroll
  for (int j = 0; j < 8; j++) {
    p[2 * j] = pack_bf16(ex2(s[4 * j] - d0), ex2(s[4 * j + 1] - d0));
    p[2 * j + 1] = pack_bf16(ex2(s[4 * j + 2] - d1), ex2(s[4 * j + 3] - d1));
  }
}
__device__ __forceinline__ void attn_step(float (&s)[32], const uint32_t (&pp)[16], uint32_t (&pn)[16], float (&o)[12], AttnState& st,
                                          uint32_t k_addr, uint32_t v_addr_prev, int keep, int c4, int wgdbg = 0, int tdbg = 0) {
  PH(wgdbg, tdbg, 0);
  const uint64_t dk = make_desc(k_addr, 128, 384, 0);
  const uint64_t dv_prev = make_desc(v_addr_prev, 384, 128, 0);
  wgmma_fence();
  wgmma_rs_n64(s, st.qa0, st.qa1, st.qa2, st.qa3, dk, 0);
  wgmma_rs_n64(s, st.qa4, st.qa5, 0u, 0u, dk + 16, 1);
  wgmma_commit();
#pragma unroll
  for (int kk = 0; kk < 4; kk++) wgmma_rs_n24_tb(o, pp[4 * kk], pp[4 * kk + 1], pp[4 * kk + 2], pp[4 * kk + 3], dv_prev + kk * 48, kk == 0 ? keep : 1);
  wgmma_commit();
  wgmma_wait<1>();
  fence_regs(s);
  PH(wgdbg, tdbg, 1);
  const bool redo = attn_exp_fast(s, pn);
  PH(wgdbg, tdbg, 2);
  wgmma_wait<0>();
  fence_regs(o);
  if (redo) attn_exp_exact(s, pn, o, st, false, c4);
}

__global__ void __launch_bounds__(AT_THREADS, 1) attn_kernel(const bf16* __restrict__ wo, const bf16* __restrict__ wgt, const bf16* __restrict__ wup, const bf16* __restrict__ wdn) {
  extern __shared__ uint8_t smem_raw[];
  const uint32_t sbase = (smem_u32(smem_raw) + 1023u) & ~1023u;
  const uint32_t sK = sbase, sV = sbase + AT_KV_BYTES;
  const uint32_t sBar = sV + AT_KV_BYTES;
  const int tid = threadIdx.x, warp = tid >> 5, lane = tid & 31;
  const int head = blockIdx.x >> 2, quarter = blockIdx.x & 3;
  if (blockIdx.x >= 128) {
    pdl_launch();
    const int b = blockIdx.x - 128;
    const bf16* w = (b >> 1) ? wup : wgt;
    const int cgrp = tid % 96, rgrp = tid / 96;
    float acc[8];
#pragma unroll
    for (int i = 0; i < 8; i++) acc[i] = 0.f;
    float* red = reinterpret_cast<float*>(smem_raw);
    if (rgrp < 5) {
      const uint4* src = reinterpret_cast<const uint4*>(w + (size_t)(rgrp * 128) * FF + (b & 1) * 768 + cgrp * 8);
#pragma unroll 8
      for (int r = 0; r < 128; r++) {
        const uint4 v = __ldg(src + (size_t)r * (FF / 8));
        acc[0] += bf_lo(v.x); acc[1] += bf_hi(v.x); acc[2] += bf_lo(v.y); acc[3] += bf_hi(v.y);
        acc[4] += bf_lo(v.z); acc[5] += bf_hi(v.z); acc[6] += bf_lo(v.w); acc[7] += bf_hi(v.w);
      }
#pragma unroll
      for (int i = 0; i < 8; i++) red[rgrp * 768 + cgrp * 8 + i] = acc[i];
    }
    __syncthreads();
    pdl_wait();
    for (int c = tid; c < 768; c += AT_THREADS)
      g_cs[(b >> 1) * FF + (b & 1) * 768 + c] = ((red[c] + red[768 + c]) + (red[1536 + c] + red[2304 + c])) + red[3072 + c];
    if (b == 0 && tid < 16) g_flag[tid] = 0;
    if (b == 0 && tid < 8) g_flag[48 + tid] = 0;
    return;
  }
  TS(1, 0);
  if (tid == 0) {
    for (int i = 0; i < AT_CHUNKS; i++) mbar_init(sBar + 8 * i, 1);
    fence_mbar_init();
  }
  pdl_launch();
  if (tid == 32) {
    prefetch_l2(reinterpret_cast<const uint8_t*>(wo) + blockIdx.x * 6400, 6400);
    prefetch_l2(reinterpret_cast<const uint8_t*>(wgt) + blockIdx.x * 15360, 15360);
    prefetch_l2(reinterpret_cast<const uint8_t*>(wup) + blockIdx.x * 15360, 15360);
    prefetch_l2(reinterpret_cast<const uint8_t*>(wdn) + blockIdx.x * 15360, 15360);
  }
  __syncthreads();
  TS(1, 1);
  pdl_wait();
  TS(1, 2);
  if (tid == 0) {
    const uint8_t* kg = reinterpret_cast<const uint8_t*>(g_img + (size_t)(32 + head) * IMG_HEAD_ELEMS);
    const uint8_t* vg = reinterpret_cast<const uint8_t*>(g_img + (size_t)(64 + head) * IMG_HEAD_ELEMS);
    constexpr int CB = AT_KV_BYTES / AT_CHUNKS;
    for (int i = 0; i < AT_CHUNKS; i++) {
      mbar_expect_tx(sBar + 8 * i, 2 * CB);
      bulk_g2s(sK + i * CB, kg + i * CB, CB, sBar + 8 * i);
      bulk_g2s(sV + i * CB, vg + i * CB, CB, sBar + 8 * i);
    }
  }
  const int wg = warp >> 2, wwarp = warp & 3;
  const int g = lane >> 2, c4 = lane & 3;
  const uint64_t dk_base = make_desc(sK, 128, 384, 0);
  const uint64_t dv_base = make_desc(sV, 384, 128, 0);

#pragma unroll 1
  for (int rep = 0; rep < 8 / AT_WGS; rep++) {
    const int row0 = quarter * 512 + (rep * AT_WGS + wg) * 64 + wwarp * 16 + g;
    AttnState st;
    {
      const bf16* q0 = g_img + (size_t)head * IMG_HEAD_ELEMS + (size_t)(row0 >> 3) * 192 + g * 8 + c4 * 2;
      const bf16* q1 = q0 + 192;
      st.qa0 = *reinterpret_cast<const uint32_t*>(q0);
      st.qa1 = *reinterpret_cast<const uint32_t*>(q1);
      st.qa2 = *reinterpret_cast<const uint32_t*>(q0 + 64);
      st.qa3 = *reinterpret_cast<const uint32_t*>(q1 + 64);
      st.qa4 = *reinterpret_cast<const uint32_t*>(q0 + 128);
      st.qa5 = *reinterpret_cast<const uint32_t*>(q1 + 128);
    }
    float o[12];
    float s[32];
    uint32_t pa[16], pb[16];
    st.M0 = st.M1 = 0.f;
    if (rep == 0) mbar_wait(sBar, 0);
    wgmma_fence();
    wgmma_rs_n64(s, st.qa0, st.qa1, st.qa2, st.qa3, dk_base, 0);
    wgmma_rs_n64(s, st.qa4, st.qa5, 0u, 0u, dk_base + 16, 1);
    wgmma_commit();
    wgmma_wait<0>();
    fence_regs(s);
    attn_exp_exact(s, pa, o, st, true, c4);
    attn_step(s, pa, pb, o, st, sK + 3072, sV, 0, c4);
#pragma unroll 1
    for (int tt = 1; tt < 16; tt++) {
      if (rep == 0 && !(tt & 1)) mbar_wait(sBar + 8 * (tt >> 1), 0);
      attn_step(s, pb, pa, o, st, sK + tt * 6144, sV + tt * 6144 - 3072, 1, c4, wg, rep * 32 + tt * 2);
      attn_step(s, pa, pb, o, st, sK + tt * 6144 + 3072, sV + tt * 6144, 1, c4, wg, rep * 32 + tt * 2 + 1);
    }
    wgmma_fence();
#pragma unroll
    for (int kk = 0; kk < 4; kk++) wgmma_rs_n24_tb(o, pb[4 * kk], pb[4 * kk + 1], pb[4 * kk + 2], pb[4 * kk + 3], dv_base + 31 * 192 + kk * 48, 1);
    wgmma_commit();
    wgmma_wait<0>();
    fence_regs(o);
    TS(1, 3 + rep);
    const float l0 = __shfl_sync(0xffffffffu, o[8], (lane & ~3) | 2);
    const float l1 = __shfl_sync(0xffffffffu, o[10], (lane & ~3) | 2);
    const float i0 = 1.0f / l0, i1 = 1.0f / l1;
    bf16* o0 = g_o + (size_t)row0 * DM + head * DH;
    bf16* o1 = o0 + 8 * DM;
#pragma unroll
    for (int j = 0; j < 3; j++) {
      if (j < 2 || c4 < 2) {
        *reinterpret_cast<uint32_t*>(o0 + j * 8 + c4 * 2) = pack_bf16(o[4 * j] * i0, o[4 * j + 1] * i0);
        *reinterpret_cast<uint32_t*>(o1 + j * 8 + c4 * 2) = pack_bf16(o[4 * j + 2] * i1, o[4 * j + 3] * i1);
      }
    }
  }
}

typedef CUresult (*EncodeTiledFn)(CUtensorMap*, CUtensorMapDataType, cuuint32_t, void*, const cuuint64_t*, const cuuint64_t*,
                                  const cuuint32_t*, const cuuint32_t*, CUtensorMapInterleave, CUtensorMapSwizzle,
                                  CUtensorMapL2promotion, CUtensorMapFloatOOBfill);

static void make_map(EncodeTiledFn fn, CUtensorMap* tm, const void* ptr, uint64_t rows, uint64_t cols, uint32_t box_rows,
                     uint32_t box_cols, CUtensorMapSwizzle sw) {
  cuuint64_t dims[2] = {cols, rows};
  cuuint64_t strides[1] = {cols * 2};
  cuuint32_t box[2] = {box_cols, box_rows};
  cuuint32_t es[2] = {1, 1};
  fn(tm, CU_TENSOR_MAP_DATA_TYPE_BFLOAT16, 2, const_cast<void*>(ptr), dims, strides, box, es, CU_TENSOR_MAP_INTERLEAVE_NONE, sw,
     CU_TENSOR_MAP_L2_PROMOTION_L2_256B, CU_TENSOR_MAP_FLOAT_OOB_FILL_NONE);
}

template <typename... KArgs, typename... Args>
static void launch(void (*kern)(KArgs...), int grid, int block, int smem, int cluster, bool pdl, Args... args) {
  cudaLaunchConfig_t cfg = {};
  cfg.gridDim = dim3(grid);
  cfg.blockDim = dim3(block);
  cfg.dynamicSmemBytes = smem;
  cfg.stream = cudaStreamPerThread;
  cudaLaunchAttribute at[2];
  int n = 0;
  if (cluster > 1) {
    at[n].id = cudaLaunchAttributeClusterDimension;
    at[n].val.clusterDim.x = cluster; at[n].val.clusterDim.y = 1; at[n].val.clusterDim.z = 1;
    n++;
  }
  if (pdl) {
    at[n].id = cudaLaunchAttributeProgrammaticStreamSerialization;
    at[n].val.programmaticStreamSerializationAllowed = 1;
    n++;
  }
  cfg.attrs = at;
  cfg.numAttrs = n;
  cudaLaunchKernelEx(&cfg, kern, KArgs(args)...);
}

extern "C" void kernel_launch(void* const* d_in, const int* in_sizes, int n_in, void* d_out, int out_size) {
  const bf16* x = (const bf16*)d_in[0];
  const bf16* wqkv = (const bf16*)d_in[1];
  const bf16* wo = (const bf16*)d_in[2];
  const bf16* wg = (const bf16*)d_in[4];
  const bf16* wu = (const bf16*)d_in[5];
  const bf16* wd = (const bf16*)d_in[6];
  bf16* out = (bf16*)d_out;

  static EncodeTiledFn enc = nullptr;
  static void *p_o = nullptr, *p_h = nullptr, *p_hh = nullptr;
  if (!enc) {
    void* fn = nullptr;
    cudaDriverEntryPointQueryResult qr;
    cudaGetDriverEntryPoint("cuTensorMapEncodeTiled", &fn, cudaEnableDefault, &qr);
    enc = (EncodeTiledFn)fn;
    cudaGetSymbolAddress(&p_o, g_o);
    cudaGetSymbolAddress(&p_h, g_h);
    cudaGetSymbolAddress(&p_hh, g_hh);
    cudaFuncSetAttribute(qkv_kernel, cudaFuncAttributeMaxDynamicSharedMemorySize, KA_SMEM);
    cudaFuncSetAttribute(mlp_kernel, cudaFuncAttributeMaxDynamicSharedMemorySize, KC_SMEM);
    cudaFuncSetAttribute(attn_kernel, cudaFuncAttributeMaxDynamicSharedMemorySize, AT_SMEM);
  }
  CUtensorMap tm_wqkv, tm_wg, tm_wu, tm_wo64, tm_wo16, tm_wd64, tm_wd16, tm_o, tm_h, tm_hh, tm_hhs, tm_xn, tm_hs, tm_out;
  make_map(enc, &tm_wqkv, wqkv, DM, 3 * DM, 32, 64, CU_TENSOR_MAP_SWIZZLE_128B);
  make_map(enc, &tm_wg, wg, DM, FF, 32, 64, CU_TENSOR_MAP_SWIZZLE_128B);
  make_map(enc, &tm_wu, wu, DM, FF, 32, 64, CU_TENSOR_MAP_SWIZZLE_128B);
  make_map(enc, &tm_wo64, wo, DM, DM, 32, 64, CU_TENSOR_MAP_SWIZZLE_128B);
  make_map(enc, &tm_wo16, wo, DM, DM, 32, 16, CU_TENSOR_MAP_SWIZZLE_32B);
  make_map(enc, &tm_wd64, wd, FF, DM, 32, 64, CU_TENSOR_MAP_SWIZZLE_128B);
  make_map(enc, &tm_wd16, wd, FF, DM, 32, 16, CU_TENSOR_MAP_SWIZZLE_32B);
  make_map(enc, &tm_o, p_o, SEQ, DM, 128, 64, CU_TENSOR_MAP_SWIZZLE_128B);
  make_map(enc, &tm_h, p_h, SEQ, DM, 128, 32, CU_TENSOR_MAP_SWIZZLE_64B);
  make_map(enc, &tm_hh, p_hh, SEQ, FF, 128, 64, CU_TENSOR_MAP_SWIZZLE_128B);
  make_map(enc, &tm_hhs, p_hh, SEQ, FF, 64, 64, CU_TENSOR_MAP_SWIZZLE_128B);
  make_map(enc, &tm_xn, x, SEQ, DM, 128, 32, CU_TENSOR_MAP_SWIZZLE_64B);
  make_map(enc, &tm_hs, p_h, SEQ, DM, 64, 80, CU_TENSOR_MAP_SWIZZLE_NONE);
  make_map(enc, &tm_out, out, SEQ, DM, 64, 80, CU_TENSOR_MAP_SWIZZLE_NONE);

  launch(qkv_kernel, 128, GT, KA_SMEM, 2, false, tm_xn, tm_wqkv, x, wqkv);
  launch(attn_kernel, 132, AT_THREADS, AT_SMEM, 1, true, wo, wg, wu, wd);
  launch(mlp_kernel, 128, GT, KC_SMEM, 2, true, tm_o, tm_wo64, tm_wo16, tm_h, tm_wg, tm_wu, tm_hhs, tm_hh, tm_wd64, tm_wd16, tm_hs, tm_out, x);
}
```

```cpp
#include <cuda_runtime.h>
#include <cuda_bf16.h>
#include <cuda.h>
#include <stdint.h>

typedef __nv_bfloat16 bf16;
#define FLAGV 0

constexpr int SEQ = 2048, DM = 640, NH = 32, DH = 20, FF = 1536;
constexpr float ATT_SCALE_LOG2E = 0.22360679774997896f * 1.4426950408889634f;
constexpr int IMG_HEAD_ELEMS = (SEQ / 8) * 192;

__device__ __align__(1024) bf16 g_img[3 * NH * IMG_HEAD_ELEMS];
__device__ __align__(1024) bf16 g_o[SEQ * DM];
__device__ __align__(1024) bf16 g_h[SEQ * DM];
__device__ float2 g_stats[SEQ * 8];
__device__ float g_cs[2 * FF];
__device__ int g_flag[4 * 16];
__device__ float2 g_rs[SEQ];
__device__ float g_csp[16 * 3 * DM];
__device__ __align__(1024) bf16 g_hh[SEQ * FF];

#define TS(k, i)
#define PH(w, t, i)
__device__ __forceinline__ uint32_t smem_u32(const void* p) { return (uint32_t)__cvta_generic_to_shared(p); }
__device__ __forceinline__ void mbar_init(uint32_t bar, uint32_t cnt) {
  asm volatile("mbarrier.init.shared::cta.b64 [%0], %1;" ::"r"(bar), "r"(cnt) : "memory");
}
__device__ __forceinline__ void mbar_expect_tx(uint32_t bar, uint32_t bytes) {
  asm volatile("mbarrier.arrive.expect_tx.shared::cta.b64 _, [%0], %1;" ::"r"(bar), "r"(bytes) : "memory");
}
__device__ __forceinline__ void mbar_arrive(uint32_t bar) {
  asm volatile("mbarrier.arrive.shared::cta.b64 _, [%0];" ::"r"(bar) : "memory");
}
__device__ __forceinline__ void mbar_arrive_cluster(uint32_t bar, uint32_t cta) {
  asm volatile(
      "{\n.reg .b32 r;\nmapa.shared::cluster.u32 r, %0, %1;\n"
      "mbarrier.arrive.shared::cluster.b64 _, [r];\n}\n" ::"r"(bar), "r"(cta)
      : "memory");
}
__device__ __forceinline__ void mbar_wait(uint32_t bar, uint32_t parity) {
  asm volatile(
      "{\n.reg .pred p;\nLAB_WAIT:\n"
      "mbarrier.try_wait.parity.shared::cta.b64 p, [%0], %1;\n"
      "@p bra DONE;\nbra LAB_WAIT;\nDONE:\n}\n" ::"r"(bar), "r"(parity)
      : "memory");
}
__device__ __forceinline__ void mbar_wait_cluster(uint32_t bar, uint32_t parity) {
  asm volatile(
      "{\n.reg .pred p;\nLAB_WAIT:\n"
      "mbarrier.try_wait.parity.acquire.cluster.shared::cta.b64 p, [%0], %1;\n"
      "@p bra DONE;\nbra LAB_WAIT;\nDONE:\n}\n" ::"r"(bar), "r"(parity)
      : "memory");
}
__device__ __forceinline__ void fence_mbar_init() { asm volatile("fence.mbarrier_init.release.cluster;" ::: "memory"); }
__device__ __forceinline__ void fence_proxy_async() { asm volatile("fence.proxy.async.shared::cta;" ::: "memory"); }
__device__ __forceinline__ void cluster_sync_all() {
  asm volatile("barrier.cluster.arrive.release.aligned;\nbarrier.cluster.wait.acquire.aligned;" ::: "memory");
}
__device__ __forceinline__ void cluster_sync_relaxed() {
  asm volatile("barrier.cluster.arrive.relaxed.aligned;\nbarrier.cluster.wait.aligned;" ::: "memory");
}
__device__ __forceinline__ void named_bar_sync(int id, int n) { asm volatile("bar.sync %0, %1;" ::"r"(id), "r"(n) : "memory"); }
__device__ __forceinline__ bool wg_any(bool pred, int id) {
  uint32_t r;
  asm volatile("{\n.reg .pred p, q;\nsetp.ne.u32 p, %1, 0;\nbar.red.or.pred q, %2, 128, p;\nselp.u32 %0, 1, 0, q;\n}\n" : "=r"(r) : "r"((uint32_t)pred), "r"(id) : "memory");
  return r != 0;
}
__device__ __forceinline__ void fence_proxy_async_all() { asm volatile("fence.proxy.async;" ::: "memory"); }
__device__ __forceinline__ void flag_signal(int* f) {
  __threadfence();
  atomicAdd(f, 1);
}
__device__ __forceinline__ void flag_wait(const int* f, int target) {
  int v;
  unsigned spins = 0;
  do {
    asm volatile("ld.acquire.gpu.global.s32 %0, [%1];" : "=r"(v) : "l"(f) : "memory");
    if (++spins > (1u << 24)) __trap();
  } while (v < target);
}
__device__ __forceinline__ void pdl_launch() { asm volatile("griddepcontrol.launch_dependents;" ::: "memory"); }
__device__ __forceinline__ void pdl_wait() { asm volatile("griddepcontrol.wait;" ::: "memory"); }

__device__ __forceinline__ void tma_load_2d(uint32_t dst, const CUtensorMap* tm, int c0, int c1, uint32_t bar) {
  asm volatile(
      "cp.async.bulk.tensor.2d.shared::cluster.global.mbarrier::complete_tx::bytes [%0], [%1, {%3, %4}], [%2];" ::"r"(dst),
      "l"((uint64_t)tm), "r"(bar), "r"(c0), "r"(c1)
      : "memory");
}
__device__ __forceinline__ void tma_load_2d_mc(uint32_t dst, const CUtensorMap* tm, int c0, int c1, uint32_t bar, uint16_t mask) {
  asm volatile(
      "cp.async.bulk.tensor.2d.shared::cluster.global.mbarrier::complete_tx::bytes.multicast::cluster [%0], [%1, {%3, %4}], [%2], %5;" ::"r"(dst),
      "l"((uint64_t)tm), "r"(bar), "r"(c0), "r"(c1), "h"(mask)
      : "memory");
}
__device__ __forceinline__ void bulk_g2s(uint32_t dst, const void* src, uint32_t bytes, uint32_t bar) {
  asm volatile("cp.async.bulk.shared::cluster.global.mbarrier::complete_tx::bytes [%0], [%1], %2, [%3];" ::"r"(dst), "l"(src),
               "r"(bytes), "r"(bar)
               : "memory");
}
__device__ __forceinline__ void bulk_s2g(void* dst, uint32_t src, uint32_t bytes) {
  asm volatile("cp.async.bulk.global.shared::cta.bulk_group [%0], [%1], %2;" ::"l"(dst), "r"(src), "r"(bytes) : "memory");
}
__device__ __forceinline__ void tma_store_2d(const CUtensorMap* tm, uint32_t src, int c0, int c1) {
  asm volatile("cp.async.bulk.tensor.2d.global.shared::cta.bulk_group [%0, {%2, %3}], [%1];" ::"l"((uint64_t)tm), "r"(src), "r"(c0), "r"(c1) : "memory");
}
__device__ __forceinline__ void bulk_commit() { asm volatile("cp.async.bulk.commit_group;" ::: "memory"); }
__device__ __forceinline__ void bulk_wait_read() { asm volatile("cp.async.bulk.wait_group.read 0;" ::: "memory"); }
__device__ __forceinline__ void prefetch_l2(const void* p, uint32_t bytes) {
  asm volatile("cp.async.bulk.prefetch.L2.global [%0], %1;" ::"l"(p), "r"(bytes) : "memory");
}
__device__ __forceinline__ void bulk_wait_all() { asm volatile("cp.async.bulk.wait_group 0;" ::: "memory"); }
__device__ __forceinline__ void st_shared_b32(uint32_t addr, uint32_t v) { asm volatile("st.shared.b32 [%0], %1;" ::"r"(addr), "r"(v) : "memory"); }
__device__ __forceinline__ void st_shared_v2(uint32_t addr, uint32_t a, uint32_t b) { asm volatile("st.shared.v2.b32 [%0], {%1, %2};" ::"r"(addr), "r"(a), "r"(b) : "memory"); }
__device__ __forceinline__ void prefetch_tmap(const CUtensorMap* tm) {
  asm volatile("prefetch.tensormap [%0];" ::"l"((uint64_t)tm) : "memory");
}
__device__ __forceinline__ void wgmma_fence() { asm volatile("wgmma.fence.sync.aligned;" ::: "memory"); }
__device__ __forceinline__ void wgmma_commit() { asm volatile("wgmma.commit_group.sync.aligned;" ::: "memory"); }
template <int N>
__device__ __forceinline__ void wgmma_wait() { asm volatile("wgmma.wait_group.sync.aligned %0;" ::"n"(N) : "memory"); }

template <int N>
__device__ __forceinline__ void fence_regs(float (&r)[N]) {
#pragma unroll
  for (int i = 0; i < N; i++) asm volatile("" : "+f"(r[i])::"memory");
}
template <int N>
__device__ __forceinline__ void fence_regs(uint32_t (&r)[N]) {
#pragma unroll
  for (int i = 0; i < N; i++) asm volatile("" : "+r"(r[i])::"memory");
}
__device__ __forceinline__ uint64_t make_desc(uint32_t addr, uint32_t lbo, uint32_t sbo, uint32_t layout) {
  return (uint64_t)((addr & 0x3FFFF) >> 4) | ((uint64_t)((lbo & 0x3FFFF) >> 4) << 16) | ((uint64_t)((sbo & 0x3FFFF) >> 4) << 32) |
         ((uint64_t)layout << 62);
}
__device__ __forceinline__ uint32_t pack_bf16(float lo, float hi) {
  uint32_t r;
  asm("cvt.rn.bf16x2.f32 %0, %1, %2;" : "=r"(r) : "f"(hi), "f"(lo));
  return r;
}
__device__ __forceinline__ float bf16_round(float x) { return __bfloat162float(__float2bfloat16_rn(x)); }
__device__ __forceinline__ float bf_lo(uint32_t u) { return __uint_as_float(u << 16); }
__device__ __forceinline__ float bf_hi(uint32_t u) { return __uint_as_float(u & 0xffff0000u); }
__device__ __forceinline__ float ex2(float x) {
  float y;
  asm("ex2.approx.ftz.f32 %0, %1;" : "=f"(y) : "f"(x));
  return y;
}

__device__ __forceinline__ void wgmma_ss_n240_tb(float (&d)[120], uint64_t descA, uint64_t descB, int scaleD) {
  asm volatile("{\n.reg .pred p;\nsetp.ne.b32 p, %122, 0;\n"
    "wgmma.mma_async.sync.aligned.m64n240k16.f32.bf16.bf16 {%0, %1, %2, %3, %4, %5, %6, %7, %8, %9, %10, %11, %12, %13, %14, %15, %16, %17, %18, %19, %20, %21, %22, %23, %24, %25, %26, %27, %28, %29, %30, %31, %32, %33, %34, %35, %36, %37, %38, %39, %40, %41, %42, %43, %44, %45, %46, %47, %48, %49, %50, %51, %52, %53, %54, %55, %56, %57, %58, %59, %60, %61, %62, %63, %64, %65, %66, %67, %68, %69, %70, %71, %72, %73, %74, %75, %76, %77, %78, %79, %80, %81, %82, %83, %84, %85, %86, %87, %88, %89, %90, %91, %92, %93, %94, %95, %96, %97, %98, %99, %100, %101, %102, %103, %104, %105, %106, %107, %108, %109, %110, %111, %112, %113, %114, %115, %116, %117, %118, %119}, %120, %121, p, 1, 1, 0, 1;\n}\n"
    : "+f"(d[0]), "+f"(d[1]), "+f"(d[2]), "+f"(d[3]), "+f"(d[4]), "+f"(d[5]), "+f"(d[6]), "+f"(d[7]), "+f"(d[8]), "+f"(d[9]), "+f"(d[10]), "+f"(d[11]), "+f"(d[12]), "+f"(d[13]), "+f"(d[14]), "+f"(d[15]), "+f"(d[16]), "+f"(d[17]), "+f"(d[18]), "+f"(d[19]), "+f"(d[20]), "+f"(d[21]), "+f"(d[22]), "+f"(d[23]), "+f"(d[24]), "+f"(d[25]), "+f"(d[26]), "+f"(d[27]), "+f"(d[28]), "+f"(d[29]), "+f"(d[30]), "+f"(d[31]), "+f"(d[32]), "+f"(d[33]), "+f"(d[34]), "+f"(d[35]), "+f"(d[36]), "+f"(d[37]), "+f"(d[38]), "+f"(d[39]), "+f"(d[40]), "+f"(d[41]), "+f"(d[42]), "+f"(d[43]), "+f"(d[44]), "+f"(d[45]), "+f"(d[46]), "+f"(d[47]), "+f"(d[48]), "+f"(d[49]), "+f"(d[50]), "+f"(d[51]), "+f"(d[52]), "+f"(d[53]), "+f"(d[54]), "+f"(d[55]), "+f"(d[56]), "+f"(d[57]), "+f"(d[58]), "+f"(d[59]), "+f"(d[60]), "+f"(d[61]), "+f"(d[62]), "+f"(d[63]), "+f"(d[64]), "+f"(d[65]), "+f"(d[66]), "+f"(d[67]), "+f"(d[68]), "+f"(d[69]), "+f"(d[70]), "+f"(d[71]), "+f"(d[72]), "+f"(d[73]), "+f"(d[74]), "+f"(d[75]), "+f"(d[76]), "+f"(d[77]), "+f"(d[78]), "+f"(d[79]), "+f"(d[80]), "+f"(d[81]), "+f"(d[82]), "+f"(d[83]), "+f"(d[84]), "+f"(d[85]), "+f"(d[86]), "+f"(d[87]), "+f"(d[88]), "+f"(d[89]), "+f"(d[90]), "+f"(d[91]), "+f"(d[92]), "+f"(d[93]), "+f"(d[94]), "+f"(d[95]), "+f"(d[96]), "+f"(d[97]), "+f"(d[98]), "+f"(d[99]), "+f"(d[100]), "+f"(d[101]), "+f"(d[102]), "+f"(d[103]), "+f"(d[104]), "+f"(d[105]), "+f"(d[106]), "+f"(d[107]), "+f"(d[108]), "+f"(d[109]), "+f"(d[110]), "+f"(d[111]), "+f"(d[112]), "+f"(d[113]), "+f"(d[114]), "+f"(d[115]), "+f"(d[116]), "+f"(d[117]), "+f"(d[118]), "+f"(d[119])
    : "l"(descA), "l"(descB), "r"(scaleD));
}
__device__ __forceinline__ void wgmma_ss_n192_tb(float (&d)[96], uint64_t descA, uint64_t descB, int scaleD) {
  asm volatile("{\n.reg .pred p;\nsetp.ne.b32 p, %98, 0;\n"
    "wgmma.mma_async.sync.aligned.m64n192k16.f32.bf16.bf16 {%0, %1, %2, %3, %4, %5, %6, %7, %8, %9, %10, %11, %12, %13, %14, %15, %16, %17, %18, %19, %20, %21, %22, %23, %24, %25, %26, %27, %28, %29, %30, %31, %32, %33, %34, %35, %36, %37, %38, %39, %40, %41, %42, %43, %44, %45, %46, %47, %48, %49, %50, %51, %52, %53, %54, %55, %56, %57, %58, %59, %60, %61, %62, %63, %64, %65, %66, %67, %68, %69, %70, %71, %72, %73, %74, %75, %76, %77, %78, %79, %80, %81, %82, %83, %84, %85, %86, %87, %88, %89, %90, %91, %92, %93, %94, %95}, %96, %97, p, 1, 1, 0, 1;\n}\n"
    : "+f"(d[0]), "+f"(d[1]), "+f"(d[2]), "+f"(d[3]), "+f"(d[4]), "+f"(d[5]), "+f"(d[6]), "+f"(d[7]), "+f"(d[8]), "+f"(d[9]), "+f"(d[10]), "+f"(d[11]), "+f"(d[12]), "+f"(d[13]), "+f"(d[14]), "+f"(d[15]), "+f"(d[16]), "+f"(d[17]), "+f"(d[18]), "+f"(d[19]), "+f"(d[20]), "+f"(d[21]), "+f"(d[22]), "+f"(d[23]), "+f"(d[24]), "+f"(d[25]), "+f"(d[26]), "+f"(d[27]), "+f"(d[28]), "+f"(d[29]), "+f"(d[30]), "+f"(d[31]), "+f"(d[32]), "+f"(d[33]), "+f"(d[34]), "+f"(d[35]), "+f"(d[36]), "+f"(d[37]), "+f"(d[38]), "+f"(d[39]), "+f"(d[40]), "+f"(d[41]), "+f"(d[42]), "+f"(d[43]), "+f"(d[44]), "+f"(d[45]), "+f"(d[46]), "+f"(d[47]), "+f"(d[48]), "+f"(d[49]), "+f"(d[50]), "+f"(d[51]), "+f"(d[52]), "+f"(d[53]), "+f"(d[54]), "+f"(d[55]), "+f"(d[56]), "+f"(d[57]), "+f"(d[58]), "+f"(d[59]), "+f"(d[60]), "+f"(d[61]), "+f"(d[62]), "+f"(d[63]), "+f"(d[64]), "+f"(d[65]), "+f"(d[66]), "+f"(d[67]), "+f"(d[68]), "+f"(d[69]), "+f"(d[70]), "+f"(d[71]), "+f"(d[72]), "+f"(d[73]), "+f"(d[74]), "+f"(d[75]), "+f"(d[76]), "+f"(d[77]), "+f"(d[78]), "+f"(d[79]), "+f"(d[80]), "+f"(d[81]), "+f"(d[82]), "+f"(d[83]), "+f"(d[84]), "+f"(d[85]), "+f"(d[86]), "+f"(d[87]), "+f"(d[88]), "+f"(d[89]), "+f"(d[90]), "+f"(d[91]), "+f"(d[92]), "+f"(d[93]), "+f"(d[94]), "+f"(d[95])
    : "l"(descA), "l"(descB), "r"(scaleD));
}
__device__ __forceinline__ void wgmma_ss_n64_tb(float (&d)[32], uint64_t descA, uint64_t descB, int scaleD) {
  asm volatile("{\n.reg .pred p;\nsetp.ne.b32 p, %34, 0;\n"
    "wgmma.mma_async.sync.aligned.m64n64k16.f32.bf16.bf16 {%0, %1, %2, %3, %4, %5, %6, %7, %8, %9, %10, %11, %12, %13, %14, %15, %16, %17, %18, %19, %20, %21, %22, %23, %24, %25, %26, %27, %28, %29, %30, %31}, %32, %33, p, 1, 1, 0, 1;\n}\n"
    : "+f"(d[0]), "+f"(d[1]), "+f"(d[2]), "+f"(d[3]), "+f"(d[4]), "+f"(d[5]), "+f"(d[6]), "+f"(d[7]), "+f"(d[8]), "+f"(d[9]), "+f"(d[10]), "+f"(d[11]), "+f"(d[12]), "+f"(d[13]), "+f"(d[14]), "+f"(d[15]), "+f"(d[16]), "+f"(d[17]), "+f"(d[18]), "+f"(d[19]), "+f"(d[20]), "+f"(d[21]), "+f"(d[22]), "+f"(d[23]), "+f"(d[24]), "+f"(d[25]), "+f"(d[26]), "+f"(d[27]), "+f"(d[28]), "+f"(d[29]), "+f"(d[30]), "+f"(d[31])
    : "l"(descA), "l"(descB), "r"(scaleD));
}
__device__ __forceinline__ void wgmma_ss_n16_tb(float (&d)[8], uint64_t descA, uint64_t descB, int scaleD) {
  asm volatile("{\n.reg .pred p;\nsetp.ne.b32 p, %10, 0;\n"
    "wgmma.mma_async.sync.aligned.m64n16k16.f32.bf16.bf16 {%0, %1, %2, %3, %4, %5, %6, %7}, %8, %9, p, 1, 1, 0, 1;\n}\n"
    : "+f"(d[0]), "+f"(d[1]), "+f"(d[2]), "+f"(d[3]), "+f"(d[4]), "+f"(d[5]), "+f"(d[6]), "+f"(d[7])
    : "l"(descA), "l"(descB), "r"(scaleD));
}
__device__ __forceinline__ void wgmma_rs_n128(float (&d)[64], uint32_t a0, uint32_t a1, uint32_t a2, uint32_t a3, uint64_t descB, int scaleD) {
  asm volatile("{\n.reg .pred p;\nsetp.ne.b32 p, %69, 0;\n"
    "wgmma.mma_async.sync.aligned.m64n128k16.f32.bf16.bf16 {%0, %1, %2, %3, %4, %5, %6, %7, %8, %9, %10, %11, %12, %13, %14, %15, %16, %17, %18, %19, %20, %21, %22, %23, %24, %25, %26, %27, %28, %29, %30, %31, %32, %33, %34, %35, %36, %37, %38, %39, %40, %41, %42, %43, %44, %45, %46, %47, %48, %49, %50, %51, %52, %53, %54, %55, %56, %57, %58, %59, %60, %61, %62, %63}, {%64, %65, %66, %67}, %68, p, 1, 1, 0;\n}\n"
    : "+f"(d[0]), "+f"(d[1]), "+f"(d[2]), "+f"(d[3]), "+f"(d[4]), "+f"(d[5]), "+f"(d[6]), "+f"(d[7]), "+f"(d[8]), "+f"(d[9]), "+f"(d[10]), "+f"(d[11]), "+f"(d[12]), "+f"(d[13]), "+f"(d[14]), "+f"(d[15]), "+f"(d[16]), "+f"(d[17]), "+f"(d[18]), "+f"(d[19]), "+f"(d[20]), "+f"(d[21]), "+f"(d[22]), "+f"(d[23]), "+f"(d[24]), "+f"(d[25]), "+f"(d[26]), "+f"(d[27]), "+f"(d[28]), "+f"(d[29]), "+f"(d[30]), "+f"(d[31]), "+f"(d[32]), "+f"(d[33]), "+f"(d[34]), "+f"(d[35]), "+f"(d[36]), "+f"(d[37]), "+f"(d[38]), "+f"(d[39]), "+f"(d[40]), "+f"(d[41]), "+f"(d[42]), "+f"(d[43]), "+f"(d[44]), "+f"(d[45]), "+f"(d[46]), "+f"(d[47]), "+f"(d[48]), "+f"(d[49]), "+f"(d[50]), "+f"(d[51]), "+f"(d[52]), "+f"(d[53]), "+f"(d[54]), "+f"(d[55]), "+f"(d[56]), "+f"(d[57]), "+f"(d[58]), "+f"(d[59]), "+f"(d[60]), "+f"(d[61]), "+f"(d[62]), "+f"(d[63])
    : "r"(a0), "r"(a1), "r"(a2), "r"(a3), "l"(descB), "r"(scaleD));
}
__device__ __forceinline__ void wgmma_rs_n64(float (&d)[32], uint32_t a0, uint32_t a1, uint32_t a2, uint32_t a3, uint64_t descB, int scaleD) {
  asm volatile("{\n.reg .pred p;\nsetp.ne.b32 p, %37, 0;\n"
    "wgmma.mma_async.sync.aligned.m64n64k16.f32.bf16.bf16 {%0, %1, %2, %3, %4, %5, %6, %7, %8, %9, %10, %11, %12, %13, %14, %15, %16, %17, %18, %19, %20, %21, %22, %23, %24, %25, %26, %27, %28, %29, %30, %31}, {%32, %33, %34, %35}, %36, p, 1, 1, 0;\n}\n"
    : "+f"(d[0]), "+f"(d[1]), "+f"(d[2]), "+f"(d[3]), "+f"(d[4]), "+f"(d[5]), "+f"(d[6]), "+f"(d[7]), "+f"(d[8]), "+f"(d[9]), "+f"(d[10]), "+f"(d[11]), "+f"(d[12]), "+f"(d[13]), "+f"(d[14]), "+f"(d[15]), "+f"(d[16]), "+f"(d[17]), "+f"(d[18]), "+f"(d[19]), "+f"(d[20]), "+f"(d[21]), "+f"(d[22]), "+f"(d[23]), "+f"(d[24]), "+f"(d[25]), "+f"(d[26]), "+f"(d[27]), "+f"(d[28]), "+f"(d[29]), "+f"(d[30]), "+f"(d[31])
    : "r"(a0), "r"(a1), "r"(a2), "r"(a3), "l"(descB), "r"(scaleD));
}
__device__ __forceinline__ void wgmma_rs_n24_tb(float (&d)[12], uint32_t a0, uint32_t a1, uint32_t a2, uint32_t a3, uint64_t descB, int scaleD) {
  asm volatile("{\n.reg .pred p;\nsetp.ne.b32 p, %17, 0;\n"
    "wgmma.mma_async.sync.aligned.m64n24k16.f32.bf16.bf16 {%0, %1, %2, %3, %4, %5, %6, %7, %8, %9, %10, %11}, {%12, %13, %14, %15}, %16, p, 1, 1, 1;\n}\n"
    : "+f"(d[0]), "+f"(d[1]), "+f"(d[2]), "+f"(d[3]), "+f"(d[4]), "+f"(d[5]), "+f"(d[6]), "+f"(d[7]), "+f"(d[8]), "+f"(d[9]), "+f"(d[10]), "+f"(d[11])
    : "r"(a0), "r"(a1), "r"(a2), "r"(a3), "l"(descB), "r"(scaleD));
}

constexpr int GT = 384;

__device__ __forceinline__ void release_stage(uint32_t bar, bool leader) {
  if (leader) {
    mbar_arrive_cluster(bar, 0);
    mbar_arrive_cluster(bar, 1);
  }
}

__device__ __forceinline__ float2 ln_row_stats(const bf16* __restrict__ xin, int l16) {
  const uint4* src = reinterpret_cast<const uint4*>(xin);
  uint4 v[5];
#pragma unroll
  for (int j = 0; j < 5; j++) v[j] = __ldg(src + j * 16 + l16);
  float s0 = 0.f, s1 = 0.f, s2 = 0.f, s3 = 0.f;
#pragma unroll
  for (int j = 0; j < 5; j++) {
    s0 += bf_lo(v[j].x) + bf_hi(v[j].x);
    s1 += bf_lo(v[j].y) + bf_hi(v[j].y);
    s2 += bf_lo(v[j].z) + bf_hi(v[j].z);
    s3 += bf_lo(v[j].w) + bf_hi(v[j].w);
  }
  float mean = (s0 + s1) + (s2 + s3);
#pragma unroll
  for (int o = 1; o < 16; o <<= 1) mean += __shfl_xor_sync(0xffffffffu, mean, o);
  mean *= (1.0f / DM);
  s0 = s1 = s2 = s3 = 0.f;
#pragma unroll
  for (int j = 0; j < 5; j++) {
    float d;
    d = bf_lo(v[j].x) - mean; s0 = fmaf(d, d, s0);
    d = bf_hi(v[j].x) - mean; s1 = fmaf(d, d, s1);
    d = bf_lo(v[j].y) - mean; s2 = fmaf(d, d, s2);
    d = bf_hi(v[j].y) - mean; s3 = fmaf(d, d, s3);
    d = bf_lo(v[j].z) - mean; s0 = fmaf(d, d, s0);
    d = bf_hi(v[j].z) - mean; s1 = fmaf(d, d, s1);
    d = bf_lo(v[j].w) - mean; s2 = fmaf(d, d, s2);
    d = bf_hi(v[j].w) - mean; s3 = fmaf(d, d, s3);
  }
  float sq = (s0 + s1) + (s2 + s3);
#pragma unroll
  for (int o = 1; o < 16; o <<= 1) sq += __shfl_xor_sync(0xffffffffu, sq, o);
  const float var_b = bf16_round(sq * (1.0f / DM));
  const float den = bf16_round(sqrtf(bf16_round(var_b + 1e-5f)));
  return make_float2(bf16_round(mean), __frcp_rn(den));
}

constexpr int LG_STAGES = 5;
constexpr int QKV_STAGE = 8192 + 4 * 4096;
constexpr int GLU_STAGE = 8192 + 6 * 4096;

template <int WG>
__device__ __forceinline__ void qkv_mainloop(float (&acc)[120], uint32_t sbase, uint32_t sBar, bool leader) {
  constexpr int STAGE_BYTES = QKV_STAGE, NST = LG_STAGES;
  const uint64_t da_base = make_desc(sbase + WG * 4096, 16, 512, 2);
  const uint64_t db_base = make_desc(sbase + 8192, 4096, 1024, 1);
#pragma unroll 1
  for (int r = 0; r < 20 / NST; r++) {
#pragma unroll
    for (int s = 0; s < NST; s++) {
      mbar_wait(sBar + 8 * s, r & 1);
      wgmma_fence();
#pragma unroll
      for (int ks = 0; ks < 2; ks++)
        wgmma_ss_n240_tb(acc, da_base + (uint64_t)((s * STAGE_BYTES + ks * 32) >> 4), db_base + (uint64_t)((s * STAGE_BYTES + ks * 2048) >> 4), 1);
      wgmma_commit();
      wgmma_wait<1>();
      release_stage(sBar + 8 * (NST + (s + NST - 1) % NST), leader && (s > 0 || r > 0));
    }
  }
}
template <int WG>
__device__ __forceinline__ void glu_mainloop(float (&accg)[96], float (&accu)[96], uint32_t sbase, uint32_t sBar, bool leader) {
  constexpr int STAGE_BYTES = GLU_STAGE, NST = LG_STAGES;
  const uint64_t da_base = make_desc(sbase + WG * 4096, 16, 512, 2);
  const uint64_t db_base = make_desc(sbase + 8192, 4096, 1024, 1);
#pragma unroll 1
  for (int r = 0; r < 20 / NST; r++) {
#pragma unroll
    for (int s = 0; s < NST; s++) {
      mbar_wait(sBar + 8 * s, r & 1);
      wgmma_fence();
#pragma unroll
      for (int ks = 0; ks < 2; ks++) {
        const uint64_t da = da_base + (uint64_t)((s * STAGE_BYTES + ks * 32) >> 4);
        wgmma_ss_n192_tb(accg, da, db_base + (uint64_t)((s * STAGE_BYTES + ks * 2048) >> 4), 1);
        wgmma_ss_n192_tb(accu, da, db_base + (uint64_t)((s * STAGE_BYTES + 3 * 4096 + ks * 2048) >> 4), 1);
      }
      wgmma_commit();
      wgmma_wait<1>();
      release_stage(sBar + 8 * (NST + (s + NST - 1) % NST), leader && (s > 0 || r > 0));
    }
  }
}
constexpr int RG_STAGE_BYTES = 16384 + 8192 + 2048;
template <int NKB, int NST, int WG>
__device__ __forceinline__ void res_mainloop(float (&acc0)[32], float (&acc1)[8], uint32_t sbase, uint32_t sBar, bool leader) {
  const uint64_t da_base = make_desc(sbase + WG * 8192, 16, 1024, 1);
  const uint64_t db0_base = make_desc(sbase + 16384, 8192, 1024, 1);
  const uint64_t db1_base = make_desc(sbase + 16384 + 8192, 2048, 256, 3);
#pragma unroll 1
  for (int r = 0; r < NKB / NST; r++) {
#pragma unroll
    for (int s = 0; s < NST; s++) {
      const uint64_t so = (uint64_t)(s * (RG_STAGE_BYTES >> 4));
      mbar_wait(sBar + 8 * s, r & 1);
      wgmma_fence();
#pragma unroll
      for (int ks = 0; ks < 4; ks++) {
        wgmma_ss_n64_tb(acc0, da_base + so + ks * 2, db0_base + so + ks * 128, 1);
        wgmma_ss_n16_tb(acc1, da_base + so + ks * 2, db1_base + so + ks * 32, 1);
      }
      wgmma_commit();
      wgmma_wait<1>();
      release_stage(sBar + 8 * (NST + (s + NST - 1) % NST), leader && (s > 0 || r > 0));
    }
  }
}

constexpr int KA_CS = LG_STAGES * QKV_STAGE + 128;
constexpr int KA_SMEM = KA_CS + 1024 + 3072 + 1024;

__global__ void __launch_bounds__(GT, 1)
qkv_kernel(const __grid_constant__ CUtensorMap tmA, const __grid_constant__ CUtensorMap tmB, const bf16* __restrict__ x,
           const bf16* __restrict__ wqkv) {
  constexpr int STAGE_BYTES = QKV_STAGE, NST = LG_STAGES, NKB = 20;
  extern __shared__ uint8_t smem_raw[];
  const uint32_t sbase = (smem_u32(smem_raw) + 1023u) & ~1023u;
  const uint32_t sBar = sbase + NST * STAGE_BYTES;
  const int tid = threadIdx.x, warp = tid >> 5, lane = tid & 31;
  const int rank = blockIdx.x & 1;
  const int pair = blockIdx.x >> 1;
  const int n_blk = pair & 7;
  const int m_blk = (pair >> 3) * 2 + rank;
  TS(0, 0);
  if (tid == 256) {
    prefetch_tmap(&tmA);
    prefetch_tmap(&tmB);
  }
  if (tid == 0) {
    for (int s = 0; s < NST; s++) {
      mbar_init(sBar + 8 * s, 1);
      mbar_init(sBar + 8 * (NST + s), 4);
    }
    fence_mbar_init();
    if (blockIdx.x < 32) g_flag[16 + blockIdx.x] = 0;
  }
  pdl_launch();
  cluster_sync_all();

  if (warp >= 8) {
    asm volatile("setmaxnreg.dec.sync.aligned.u32 56;");
    if (warp >= 9) {
      const int w3 = warp - 9;
      float* red = reinterpret_cast<float*>(smem_raw + (sbase - smem_u32(smem_raw)) + KA_CS + 1024);
      if (lane < 30) {
        float a[8];
#pragma unroll
        for (int i = 0; i < 8; i++) a[i] = 0.f;
        const uint4* w = reinterpret_cast<const uint4*>(wqkv + (size_t)(m_blk * 40) * (3 * DM) + n_blk * 240) + lane;
#pragma unroll 7
        for (int r = w3; r < 40; r += 3) {
          const uint4 v = __ldg(w + (size_t)r * (3 * DM / 8));
          a[0] += bf_lo(v.x); a[1] += bf_hi(v.x); a[2] += bf_lo(v.y); a[3] += bf_hi(v.y);
          a[4] += bf_lo(v.z); a[5] += bf_hi(v.z); a[6] += bf_lo(v.w); a[7] += bf_hi(v.w);
        }
#pragma unroll
        for (int i = 0; i < 8; i++) red[w3 * 240 + lane * 8 + i] = a[i];
      }
#pragma unroll 1
      for (int r = w3 * 2; r < 16; r += 6) {
        const int row = m_blk * 128 + n_blk * 16 + r + (lane >> 4);
        const float2 rs = ln_row_stats(x + (size_t)row * DM, lane & 15);
        if ((lane & 15) == 0) g_rs[row] = rs;
      }
      named_bar_sync(4, 96);
      for (int c = tid - 288; c < 240; c += 96) g_csp[m_blk * (3 * DM) + n_blk * 240 + c] = (red[c] + red[240 + c]) + red[480 + c];
      named_bar_sync(4, 96);
      if (tid == 288) {
        __threadfence();
        atomicAdd(&g_flag[m_blk], 1);
        atomicAdd(&g_flag[48 + n_blk], 1);
      }
    }
    if (tid == 256) {
      auto issue_b = [&](int kb) {
        const int s = kb % NST;
        const uint32_t full = sBar + 8 * s;
        mbar_expect_tx(full, STAGE_BYTES);
        const uint32_t dst = sbase + s * STAGE_BYTES + 8192;
#pragma unroll
        for (int j = 0; j < 2; j++) {
          const int sl = rank * 2 + j;
          tma_load_2d_mc(dst + sl * 4096, &tmB, n_blk * 240 + sl * 64, kb * 32, full, (uint16_t)3);
        }
      };
      for (int kb = 0; kb < NKB; kb++) {
        const int s = kb % NST;
        if (kb >= NST) mbar_wait(sBar + 8 * (NST + s), ((kb / NST) & 1) ^ 1);
        issue_b(kb);
        tma_load_2d(sbase + s * STAGE_BYTES, &tmA, kb * 32, m_blk * 128, sBar + 8 * s);
      }
    }
  } else {
    asm volatile("setmaxnreg.inc.sync.aligned.u32 224;");
    const int wg = __shfl_sync(0xffffffffu, warp >> 2, 0);
    const int wwarp = warp & 3;
    TS(0, 1);
    mbar_wait(sBar, 0);
    TS(0, 3);
    float acc[120];
#pragma unroll
    for (int i = 0; i < 120; i++) acc[i] = 0.f;
    if (wg == 0) qkv_mainloop<0>(acc, sbase, sBar, (tid & 127) == 0);
    else qkv_mainloop<1>(acc, sbase, sBar, (tid & 127) == 0);
    wgmma_wait<0>();
    fence_regs(acc);
    TS(0, 4);
    const int g = lane >> 2, c4 = lane & 3;
    float* cs_s = reinterpret_cast<float*>(smem_raw + (sbase - smem_u32(smem_raw)) + KA_CS);
    flag_wait(&g_flag[m_blk], 8);
    flag_wait(&g_flag[48 + n_blk], 16);
    if (tid < 240) {
      float c = 0.f;
#pragma unroll
      for (int mm = 0; mm < 16; mm++) c += g_csp[mm * (3 * DM) + n_blk * 240 + tid];
      cs_s[tid] = c;
    }
    const float2 rs0 = g_rs[m_blk * 128 + wg * 64 + wwarp * 16 + g], rs1 = g_rs[m_blk * 128 + wg * 64 + wwarp * 16 + g + 8];
    named_bar_sync(3, 256);
    const uint32_t stg = sbase + wg * (12 * 3072) + (wwarp * 2) * 384 + g * 16;
    const int hbase = n_blk * 12;
#pragma unroll
    for (int j = 0; j < 30; j++) {
      const int cb = (j * 8) % 20;
      const int hb = (j * 8) / 20;
      int d = cb + c4 * 2;
      int hl = hb;
      if (cb == 16 && c4 >= 2) { d -= 20; hl += 1; }
      const uint32_t a0 = stg + hl * 3072 + (d >> 3) * 128 + (d & 7) * 2;
      const int hg = hbase + hl;
      const float sc = hg < 32 ? ATT_SCALE_LOG2E : 1.0f;
      const float2 cc = *reinterpret_cast<const float2*>(cs_s + j * 8 + c4 * 2);
      const float i0 = rs0.y * sc, i1 = rs1.y * sc;
      st_shared_b32(a0, pack_bf16(fmaf(-rs0.x, cc.x, acc[4 * j]) * i0, fmaf(-rs0.x, cc.y, acc[4 * j + 1]) * i0));
      st_shared_b32(a0 + 384, pack_bf16(fmaf(-rs1.x, cc.x, acc[4 * j + 2]) * i1, fmaf(-rs1.x, cc.y, acc[4 * j + 3]) * i1));
      if (d == 18) {
        const uint32_t pad0 = hg < 32 ? 0u : (hg < 64 ? 0x3f803f80u : 0x00003f80u);
        const uint32_t pad1 = (hg >= 32 && hg < 64) ? 0x00003f80u : 0u;
        st_shared_v2(a0 + 4, pad0, pad1);
        st_shared_v2(a0 + 388, pad0, pad1);
      }
      if (j % 10 == 9) {
        fence_proxy_async();
        named_bar_sync(1 + wg, 128);
        if ((tid & 127) < 4) {
          const int hs = (j / 10) * 4 + (tid & 127);
          bf16* dst = g_img + (size_t)(hbase + hs) * IMG_HEAD_ELEMS + (size_t)(m_blk * 16 + wg * 8) * 192;
          bulk_s2g(dst, sbase + wg * (12 * 3072) + hs * 3072, 3072);
          bulk_commit();
        }
      }
    }
    if ((tid & 127) < 4) bulk_wait_read();
  }
  __syncwarp();
  TS(0, 5);
  cluster_sync_relaxed();
  TS(0, 6);
}

constexpr int KC_NST1 = 5, KC_NST3 = 6;
constexpr int KC_STAGING = 160 * 1024;
constexpr int KC_BAR = KC_STAGING + 48 * 1024;
constexpr int KC_CS = KC_BAR + 512;
constexpr int KC_SMEM = KC_CS + 1536 + 1024;

__global__ void __launch_bounds__(GT, 1)
mlp_kernel(const __grid_constant__ CUtensorMap tmO, const __grid_constant__ CUtensorMap tmWo64, const __grid_constant__ CUtensorMap tmWo16,
           const __grid_constant__ CUtensorMap tmH, const __grid_constant__ CUtensorMap tmWg, const __grid_constant__ CUtensorMap tmWu,
           const __grid_constant__ CUtensorMap tmHHs, const __grid_constant__ CUtensorMap tmHH, const __grid_constant__ CUtensorMap tmWd64,
           const __grid_constant__ CUtensorMap tmWd16, const __grid_constant__ CUtensorMap tmHs, const __grid_constant__ CUtensorMap tmOut,
           const bf16* __restrict__ x) {
  extern __shared__ uint8_t smem_raw[];
  const uint32_t sbase = (smem_u32(smem_raw) + 1023u) & ~1023u;
  const uint32_t bar1 = sbase + KC_BAR;
  const uint32_t bar2 = bar1 + 128;
  const uint32_t bar3 = bar2 + 128;
  const uint32_t barD = bar3 + 128;
  const int tid = threadIdx.x, warp = tid >> 5, lane = tid & 31;
  const int rank = blockIdx.x & 1;
  const int pair = blockIdx.x >> 1;
  const int j_blk = pair & 7;
  const int m_blk = (pair >> 3) * 2 + rank;
  const int n0 = j_blk * 80;
  TS(2, 0);
  if (tid == 256) {
    prefetch_tmap(&tmO); prefetch_tmap(&tmWo64); prefetch_tmap(&tmWo16); prefetch_tmap(&tmH); prefetch_tmap(&tmWg);
    prefetch_tmap(&tmWu); prefetch_tmap(&tmHHs); prefetch_tmap(&tmHH); prefetch_tmap(&tmWd64); prefetch_tmap(&tmWd16);
    prefetch_tmap(&tmHs); prefetch_tmap(&tmOut);
  }
  if (tid == 0) {
    for (int s = 0; s < 5; s++) {
      mbar_init(bar1 + 8 * s, 1); mbar_init(bar1 + 8 * (5 + s), 4);
      mbar_init(bar2 + 8 * s, 1); mbar_init(bar2 + 8 * (5 + s), 4);
    }
    for (int s = 0; s < 6; s++) { mbar_init(bar3 + 8 * s, 1); mbar_init(bar3 + 8 * (6 + s), 4); }
    mbar_init(barD, 4); mbar_init(barD + 8, 4);
    fence_mbar_init();
  }
  cluster_sync_all();

  if (warp >= 8) {
    asm volatile("setmaxnreg.dec.sync.aligned.u32 40;");
    if (tid == 256) {
      auto issue_b80 = [&](const CUtensorMap* t64, const CUtensorMap* t16, uint32_t bars, int nst, int kb) {
        const int s = kb % nst;
        const uint32_t full = bars + 8 * s;
        const uint32_t st = sbase + s * RG_STAGE_BYTES;
        mbar_expect_tx(full, RG_STAGE_BYTES);
        tma_load_2d_mc(st + 16384 + rank * 4096, t64, n0, kb * 64 + rank * 32, full, (uint16_t)3);
        tma_load_2d_mc(st + 16384 + 8192 + rank * 1024, t16, n0 + 64, kb * 64 + rank * 32, full, (uint16_t)3);
      };
      for (int kb = 0; kb < KC_NST1; kb++) issue_b80(&tmWo64, &tmWo16, bar1, KC_NST1, kb);
      pdl_wait();
      for (int kb = 0; kb < 10; kb++) {
        const int s = kb % KC_NST1;
        if (kb >= KC_NST1) {
          mbar_wait(bar1 + 8 * (KC_NST1 + s), ((kb / KC_NST1) & 1) ^ 1);
          issue_b80(&tmWo64, &tmWo16, bar1, KC_NST1, kb);
        }
        tma_load_2d(sbase + s * RG_STAGE_BYTES, &tmO, kb * 64, m_blk * 128, bar1 + 8 * s);
      }
      auto issue_bglu = [&](int kb) {
        const int s = kb % LG_STAGES;
        const uint32_t full = bar2 + 8 * s;
        mbar_expect_tx(full, GLU_STAGE);
        const uint32_t dst = sbase + s * GLU_STAGE + 8192;
#pragma unroll
        for (int j = 0; j < 3; j++)
          tma_load_2d_mc(dst + (rank * 3 + j) * 4096, rank == 0 ? &tmWg : &tmWu, j_blk * 192 + j * 64, kb * 32, full, (uint16_t)3);
      };
      mbar_wait(barD, 0);
      for (int kb = 0; kb < LG_STAGES; kb++) issue_bglu(kb);
      flag_wait(&g_flag[16 + m_blk], 16);
      fence_proxy_async_all();
      for (int kb = 0; kb < 20; kb++) {
        const int s = kb % LG_STAGES;
        if (kb >= LG_STAGES) {
          mbar_wait(bar2 + 8 * (LG_STAGES + s), ((kb / LG_STAGES) & 1) ^ 1);
          issue_bglu(kb);
        }
        tma_load_2d(sbase + s * GLU_STAGE, &tmH, kb * 32, m_blk * 128, bar2 + 8 * s);
      }
      mbar_wait(barD + 8, 0);
      for (int kb = 0; kb < KC_NST3; kb++) issue_b80(&tmWd64, &tmWd16, bar3, KC_NST3, kb);
      flag_wait(&g_flag[32 + m_blk], 16);
      fence_proxy_async_all();
      for (int kb = 0; kb < 24; kb++) {
        const int s = kb % KC_NST3;
        if (kb >= KC_NST3) {
          mbar_wait(bar3 + 8 * (KC_NST3 + s), ((kb / KC_NST3) & 1) ^ 1);
          issue_b80(&tmWd64, &tmWd16, bar3, KC_NST3, kb);
        }
        tma_load_2d(sbase + s * RG_STAGE_BYTES, &tmHH, kb * 64, m_blk * 128, bar3 + 8 * s);
      }
    }
  } else {
    asm volatile("setmaxnreg.inc.sync.aligned.u32 232;");
    const int wg = __shfl_sync(0xffffffffu, warp >> 2, 0);
    const int wwarp = warp & 3;
    const int g = lane >> 2, c4 = lane & 3;
    const int row0 = m_blk * 128 + wg * 64 + wwarp * 16 + g;
    const bool leader = (tid & 127) == 0;
    const uint32_t stg80_base = sbase + KC_STAGING + wg * 24576;
    const uint32_t stg80 = stg80_base + (wwarp * 16 + g) * 160 + c4 * 4;
    {
      uint32_t res[20];
#pragma unroll
      for (int j = 0; j < 10; j++) {
        res[2 * j] = __ldg(reinterpret_cast<const uint32_t*>(x + (size_t)row0 * DM + n0 + j * 8 + c4 * 2));
        res[2 * j + 1] = __ldg(reinterpret_cast<const uint32_t*>(x + (size_t)(row0 + 8) * DM + n0 + j * 8 + c4 * 2));
      }
      float acc0[32], acc1[8];
#pragma unroll
      for (int i = 0; i < 32; i++) acc0[i] = 0.f;
#pragma unroll
      for (int i = 0; i < 8; i++) acc1[i] = 0.f;
      TS(2, 1);
      if (wg == 0) res_mainloop<10, KC_NST1, 0>(acc0, acc1, sbase, bar1, leader);
      else res_mainloop<10, KC_NST1, 1>(acc0, acc1, sbase, bar1, leader);
      wgmma_wait<0>();
      fence_regs(acc0); fence_regs(acc1);
      release_stage(barD, leader);
      TS(2, 4);
      float sum0 = 0.f, sum1 = 0.f;
#pragma unroll
      for (int j = 0; j < 10; j++) {
        const uint32_t a01 = j < 8 ? pack_bf16(acc0[4 * j], acc0[4 * j + 1]) : pack_bf16(acc1[4 * (j - 8)], acc1[4 * (j - 8) + 1]);
        const uint32_t a23 = j < 8 ? pack_bf16(acc0[4 * j + 2], acc0[4 * j + 3]) : pack_bf16(acc1[4 * (j - 8) + 2], acc1[4 * (j - 8) + 3]);
        res[2 * j] = pack_bf16(bf_lo(res[2 * j]) + bf_lo(a01), bf_hi(res[2 * j]) + bf_hi(a01));
        res[2 * j + 1] = pack_bf16(bf_lo(res[2 * j + 1]) + bf_lo(a23), bf_hi(res[2 * j + 1]) + bf_hi(a23));
        st_shared_b32(stg80 + j * 16, res[2 * j]);
        st_shared_b32(stg80 + 8 * 160 + j * 16, res[2 * j + 1]);
        sum0 += bf_lo(res[2 * j]) + bf_hi(res[2 * j]);
        sum1 += bf_lo(res[2 * j + 1]) + bf_hi(res[2 * j + 1]);
      }
      sum0 += __shfl_xor_sync(0xffffffffu, sum0, 1); sum1 += __shfl_xor_sync(0xffffffffu, sum1, 1);
      sum0 += __shfl_xor_sync(0xffffffffu, sum0, 2); sum1 += __shfl_xor_sync(0xffffffffu, sum1, 2);
      const float mu0 = sum0 * (1.0f / 80.0f), mu1 = sum1 * (1.0f / 80.0f);
      float q0 = 0.f, q1 = 0.f;
#pragma unroll
      for (int j = 0; j < 10; j++) {
        float d;
        d = bf_lo(res[2 * j]) - mu0; q0 = fmaf(d, d, q0);
        d = bf_hi(res[2 * j]) - mu0; q0 = fmaf(d, d, q0);
        d = bf_lo(res[2 * j + 1]) - mu1; q1 = fmaf(d, d, q1);
        d = bf_hi(res[2 * j + 1]) - mu1; q1 = fmaf(d, d, q1);
      }
      q0 += __shfl_xor_sync(0xffffffffu, q0, 1); q1 += __shfl_xor_sync(0xffffffffu, q1, 1);
      q0 += __shfl_xor_sync(0xffffffffu, q0, 2); q1 += __shfl_xor_sync(0xffffffffu, q1, 2);
      if (c4 == 0) {
        g_stats[row0 * 8 + j_blk] = make_float2(mu0, q0);
        g_stats[(row0 + 8) * 8 + j_blk] = make_float2(mu1, q1);
      }
      fence_proxy_async();
      named_bar_sync(1 + wg, 128);
      if (leader) {
        tma_store_2d(&tmHs, stg80_base, n0, m_blk * 128 + wg * 64);
        bulk_commit();
        bulk_wait_all();
        fence_proxy_async_all();
        flag_signal(&g_flag[16 + m_blk]);
      }
      TS(2, 5);
    }
    {
      pdl_wait();
      {
        float* cs_s = reinterpret_cast<float*>(smem_raw + (sbase - smem_u32(smem_raw)) + KC_CS);
        for (int i = tid; i < 384; i += 256) cs_s[i] = g_cs[(i >= 192 ? FF - 192 : 0) + j_blk * 192 + i];
        named_bar_sync(3, 256);
      }
      flag_wait(&g_flag[16 + m_blk], 16);
      float mb[2], iv[2];
#pragma unroll
      for (int h = 0; h < 2; h++) {
        const float4* sp = reinterpret_cast<const float4*>(g_stats + (row0 + 8 * h) * 8);
        const float4 p0 = sp[0], p1 = sp[1], p2 = sp[2], p3 = sp[3];
        const float mean = (((p0.x + p0.z) + (p1.x + p1.z)) + ((p2.x + p2.z) + (p3.x + p3.z))) * 0.125f;
        float m2 = ((p0.y + p0.w) + (p1.y + p1.w)) + ((p2.y + p2.w) + (p3.y + p3.w));
        float dd = 0.f, d;
        d = p0.x - mean; dd = fmaf(d, d, dd); d = p0.z - mean; dd = fmaf(d, d, dd);
        d = p1.x - mean; dd = fmaf(d, d, dd); d = p1.z - mean; dd = fmaf(d, d, dd);
        d = p2.x - mean; dd = fmaf(d, d, dd); d = p2.z - mean; dd = fmaf(d, d, dd);
        d = p3.x - mean; dd = fmaf(d, d, dd); d = p3.z - mean; dd = fmaf(d, d, dd);
        m2 = fmaf(dd, 80.0f, m2);
        const float var_b = bf16_round(m2 * (1.0f / DM));
        const float den = bf16_round(sqrtf(bf16_round(var_b + 1e-5f)));
        iv[h] = __frcp_rn(den);
        mb[h] = bf16_round(mean);
      }
      float accg[96], accu[96];
#pragma unroll
      for (int i = 0; i < 96; i++) { accg[i] = 0.f; accu[i] = 0.f; }
      TS(3, 3);
      if (wg == 0) glu_mainloop<0>(accg, accu, sbase, bar2, leader);
      else glu_mainloop<1>(accg, accu, sbase, bar2, leader);
      wgmma_wait<0>();
      fence_regs(accg); fence_regs(accu);
      release_stage(barD + 8, leader);
      TS(3, 4);
      const uint32_t stg = sbase + KC_STAGING + wg * 24576 + (wwarp * 16 + g) * 128 + c4 * 4;
      const float* csg = reinterpret_cast<const float*>(smem_raw + (sbase - smem_u32(smem_raw)) + KC_CS) + c4 * 2;
      const float nm0 = -mb[0] * iv[0], nm1 = -mb[1] * iv[1];
#pragma unroll
      for (int sl = 0; sl < 3; sl++) {
#pragma unroll
        for (int jj = 0; jj < 8; jj++) {
          const int j = sl * 8 + jj;
          const float2 cg = *reinterpret_cast<const float2*>(csg + j * 8);
          const float2 cu = *reinterpret_cast<const float2*>(csg + 192 + j * 8);
          const float r0 = fmaxf(fmaf(accg[4 * j], iv[0], nm0 * cg.x), 0.f) * fmaf(accu[4 * j], iv[0], nm0 * cu.x);
          const float r1 = fmaxf(fmaf(accg[4 * j + 1], iv[0], nm0 * cg.y), 0.f) * fmaf(accu[4 * j + 1], iv[0], nm0 * cu.y);
          const float r2 = fmaxf(fmaf(accg[4 * j + 2], iv[1], nm1 * cg.x), 0.f) * fmaf(accu[4 * j + 2], iv[1], nm1 * cu.x);
          const float r3 = fmaxf(fmaf(accg[4 * j + 3], iv[1], nm1 * cg.y), 0.f) * fmaf(accu[4 * j + 3], iv[1], nm1 * cu.y);
          const uint32_t a0 = stg + sl * 8192 + ((jj ^ g) << 4);
          st_shared_b32(a0, pack_bf16(r0, r1));
          st_shared_b32(a0 + 1024, pack_bf16(r2, r3));
        }
        fence_proxy_async();
        named_bar_sync(1 + wg, 128);
        if (leader) {
          tma_store_2d(&tmHHs, sbase + KC_STAGING + wg * 24576 + sl * 8192, j_blk * 192 + sl * 64, m_blk * 128 + wg * 64);
          bulk_commit();
        }
      }
      TS(3, 7);
      if (leader) {
        bulk_wait_all();
        TS(3, 8);
        fence_proxy_async_all();
        flag_signal(&g_flag[32 + m_blk]);
      }
      TS(3, 9);
    }
    {
      uint32_t res[20];
#pragma unroll
      for (int j = 0; j < 10; j++) {
        res[2 * j] = *reinterpret_cast<const uint32_t*>(g_h + (size_t)row0 * DM + n0 + j * 8 + c4 * 2);
        res[2 * j + 1] = *reinterpret_cast<const uint32_t*>(g_h + (size_t)(row0 + 8) * DM + n0 + j * 8 + c4 * 2);
      }
      float acc0[32], acc1[8];
#pragma unroll
      for (int i = 0; i < 32; i++) acc0[i] = 0.f;
#pragma unroll
      for (int i = 0; i < 8; i++) acc1[i] = 0.f;
      mbar_wait(bar3, 0);
      TS(4, 3);
      if (wg == 0) res_mainloop<24, KC_NST3, 0>(acc0, acc1, sbase, bar3, leader);
      else res_mainloop<24, KC_NST3, 1>(acc0, acc1, sbase, bar3, leader);
      wgmma_wait<0>();
      fence_regs(acc0); fence_regs(acc1);
      TS(4, 4);
#pragma unroll
      for (int j = 0; j < 10; j++) {
        const uint32_t a01 = j < 8 ? pack_bf16(acc0[4 * j], acc0[4 * j + 1]) : pack_bf16(acc1[4 * (j - 8)], acc1[4 * (j - 8) + 1]);
        const uint32_t a23 = j < 8 ? pack_bf16(acc0[4 * j + 2], acc0[4 * j + 3]) : pack_bf16(acc1[4 * (j - 8) + 2], acc1[4 * (j - 8) + 3]);
        st_shared_b32(stg80 + j * 16, pack_bf16(bf_lo(res[2 * j]) + bf_lo(a01), bf_hi(res[2 * j]) + bf_hi(a01)));
        st_shared_b32(stg80 + 8 * 160 + j * 16, pack_bf16(bf_lo(res[2 * j + 1]) + bf_lo(a23), bf_hi(res[2 * j + 1]) + bf_hi(a23)));
      }
      fence_proxy_async();
      named_bar_sync(1 + wg, 128);
      if (leader) {
        tma_store_2d(&tmOut, stg80_base, n0, m_blk * 128 + wg * 64);
        bulk_commit();
        bulk_wait_read();
      }
      TS(4, 5);
    }
  }
  __syncwarp();
  cluster_sync_relaxed();
  TS(4, 6);
}

constexpr int AT_THREADS = 512;
constexpr int AT_WGS = AT_THREADS / 128;
#define AT_CHUNK_MASK 3
#define AT_STAGGER 0
constexpr int AT_KV_BYTES = IMG_HEAD_ELEMS * 2;
constexpr int AT_SMEM = 2 * AT_KV_BYTES + 256 + 1024;
constexpr int AT_CHUNKS = 8;

__device__ __forceinline__ float exp2_poly(float x) {
  const float u = __saturatef(fmaf(x, 1.0f / 64.0f, 62.0f / 64.0f));
  const float MAGIC = 12582912.0f - 62.0f;
  const float r = fmaf(u, 64.0f, MAGIC);
  const float q = MAGIC - r;
  const float fr = fmaf(u, 64.0f, q);
  float p = fmaf(fr, 0.009570102207362652f, 0.05591785907745361f);
  p = fmaf(p, fr, 0.240247443318367f);
  p = fmaf(p, fr, 0.6931217908859253f);
  p = fmaf(p, fr, 0.9999992847442627f);
  return __uint_as_float(__float_as_uint(p) + (__float_as_uint(r) << 23));
}
#define AT_VARIANT 0
#define AT_POLY_MOD 8
__device__ __forceinline__ bool use_poly(int e) {
  return (e % AT_POLY_MOD) == 1;
}

struct AttnState {
  uint32_t qa0, qa1, qa2, qa3, qa4, qa5;
  float M0, M1;
};

__device__ __forceinline__ bool attn_exp_fast(const float (&s)[32], uint32_t (&p)[16]) {
#pragma unroll
  for (int j = 0; j < 16; j++) {
    const float e0 = use_poly(2 * j) ? exp2_poly(s[2 * j]) : ex2(s[2 * j]);
    const float e1 = use_poly(2 * j + 1) ? exp2_poly(s[2 * j + 1]) : ex2(s[2 * j + 1]);
    p[j] = pack_bf16(e0, e1);
  }
  uint32_t acc_or = 0;
#pragma unroll
  for (int j = 0; j < 16; j++) acc_or |= p[j];
  return __any_sync(0xffffffffu, (acc_or & 0x40004000u) != 0);
}
__device__ __forceinline__ void attn_exp_exact(const float (&s)[32], uint32_t (&p)[16], float (&o)[12], AttnState& st, bool first, int c4) {
  float mx0 = fmaxf(s[0], s[1]), mx1 = fmaxf(s[2], s[3]);
#pragma unroll
  for (int j = 1; j < 8; j++) {
    mx0 = fmaxf(mx0, fmaxf(s[4 * j], s[4 * j + 1]));
    mx1 = fmaxf(mx1, fmaxf(s[4 * j + 2], s[4 * j + 3]));
  }
  mx0 = fmaxf(mx0, __shfl_xor_sync(0xffffffffu, mx0, 1));
  mx1 = fmaxf(mx1, __shfl_xor_sync(0xffffffffu, mx1, 1));
  mx0 = fmaxf(mx0, __shfl_xor_sync(0xffffffffu, mx0, 2));
  mx1 = fmaxf(mx1, __shfl_xor_sync(0xffffffffu, mx1, 2));
  float d0 = mx0 + 7.0f, d1 = mx1 + 7.0f;
  if (!first) { d0 = fmaxf(d0, 0.f); d1 = fmaxf(d1, 0.f); }
  const float T0 = st.M0 + d0, T1 = st.M1 + d1;
  const float h0 = bf16_round(T0), h1 = bf16_round(T1);
  const float i0 = bf16_round(T0 - h0), i1 = bf16_round(T1 - h1);
  const float l0 = bf16_round((T0 - h0) - i0), l1 = bf16_round((T1 - h1) - i1);
  const float N0 = (h0 + i0) + l0, N1 = (h1 + i1) + l1;
  d0 = N0 - st.M0; d1 = N1 - st.M1;
  st.M0 = N0; st.M1 = N1;
  if (c4 == 2) { st.qa4 = pack_bf16(-h0, -i0); st.qa5 = pack_bf16(-h1, -i1); }
  if (c4 == 3) { st.qa4 = pack_bf16(-l0, 0.f); st.qa5 = pack_bf16(-l1, 0.f); }
  if (!first) {
    const float al0 = ex2(-d0), al1 = ex2(-d1);
#pragma unroll
    for (int j = 0; j < 3; j++) {
      o[4 * j] *= al0; o[4 * j + 1] *= al0;
      o[4 * j + 2] *= al1; o[4 * j + 3] *= al1;
    }
  }
#pragma unroll
  for (int j = 0; j < 8; j++) {
    p[2 * j] = pack_bf16(ex2(s[4 * j] - d0), ex2(s[4 * j + 1] - d0));
    p[2 * j + 1] = pack_bf16(ex2(s[4 * j + 2] - d1), ex2(s[4 * j + 3] - d1));
  }
}
__device__ __forceinline__ void attn_step(float (&s)[32], const uint32_t (&pp)[16], uint32_t (&pn)[16], float (&o)[12], AttnState& st,
                                          uint32_t k_addr, uint32_t v_addr_prev, int keep, int c4, int wgdbg = 0, int tdbg = 0) {
  PH(wgdbg, tdbg, 0);
  const uint64_t dk = make_desc(k_addr, 128, 384, 0);
  const uint64_t dv_prev = make_desc(v_addr_prev, 384, 128, 0);
  wgmma_fence();
  wgmma_rs_n64(s, st.qa0, st.qa1, st.qa2, st.qa3, dk, 0);
  wgmma_rs_n64(s, st.qa4, st.qa5, 0u, 0u, dk + 16, 1);
  wgmma_commit();
#pragma unroll
  for (int kk = 0; kk < 4; kk++) wgmma_rs_n24_tb(o, pp[4 * kk], pp[4 * kk + 1], pp[4 * kk + 2], pp[4 * kk + 3], dv_prev + kk * 48, kk == 0 ? keep : 1);
  wgmma_commit();
  wgmma_wait<1>();
  fence_regs(s);
  PH(wgdbg, tdbg, 1);
  const bool redo = attn_exp_fast(s, pn);
  PH(wgdbg, tdbg, 2);
  wgmma_wait<0>();
  fence_regs(o);
  if (redo) attn_exp_exact(s, pn, o, st, false, c4);
}

__global__ void __launch_bounds__(AT_THREADS, 1) attn_kernel(const bf16* __restrict__ wo, const bf16* __restrict__ wgt, const bf16* __restrict__ wup, const bf16* __restrict__ wdn) {
  extern __shared__ uint8_t smem_raw[];
  const uint32_t sbase = (smem_u32(smem_raw) + 1023u) & ~1023u;
  const uint32_t sK = sbase, sV = sbase + AT_KV_BYTES;
  const uint32_t sBar = sV + AT_KV_BYTES;
  const int tid = threadIdx.x, warp = tid >> 5, lane = tid & 31;
  const int head = blockIdx.x >> 2, quarter = blockIdx.x & 3;
  if (blockIdx.x >= 128) {
    pdl_launch();
    const int b = blockIdx.x - 128;
    const bf16* w = (b >> 1) ? wup : wgt;
    const int cgrp = tid % 96, rgrp = tid / 96;
    float acc[8];
#pragma unroll
    for (int i = 0; i < 8; i++) acc[i] = 0.f;
    float* red = reinterpret_cast<float*>(smem_raw);
    if (rgrp < 5) {
      const uint4* src = reinterpret_cast<const uint4*>(w + (size_t)(rgrp * 128) * FF + (b & 1) * 768 + cgrp * 8);
#pragma unroll 8
      for (int r = 0; r < 128; r++) {
        const uint4 v = __ldg(src + (size_t)r * (FF / 8));
        acc[0] += bf_lo(v.x); acc[1] += bf_hi(v.x); acc[2] += bf_lo(v.y); acc[3] += bf_hi(v.y);
        acc[4] += bf_lo(v.z); acc[5] += bf_hi(v.z); acc[6] += bf_lo(v.w); acc[7] += bf_hi(v.w);
      }
#pragma unroll
      for (int i = 0; i < 8; i++) red[rgrp * 768 + cgrp * 8 + i] = acc[i];
    }
    __syncthreads();
    pdl_wait();
    for (int c = tid; c < 768; c += AT_THREADS)
      g_cs[(b >> 1) * FF + (b & 1) * 768 + c] = ((red[c] + red[768 + c]) + (red[1536 + c] + red[2304 + c])) + red[3072 + c];
    if (b == 0 && tid < 16) g_flag[tid] = 0;
    if (b == 0 && tid < 8) g_flag[48 + tid] = 0;
    return;
  }
  TS(1, 0);
  if (tid == 0) {
    for (int i = 0; i < AT_CHUNKS; i++) mbar_init(sBar + 8 * i, 1);
    fence_mbar_init();
  }
  pdl_launch();
  if (tid == 32) {
    prefetch_l2(reinterpret_cast<const uint8_t*>(wo) + blockIdx.x * 6400, 6400);
    prefetch_l2(reinterpret_cast<const uint8_t*>(wgt) + blockIdx.x * 15360, 15360);
    prefetch_l2(reinterpret_cast<const uint8_t*>(wup) + blockIdx.x * 15360, 15360);
    prefetch_l2(reinterpret_cast<const uint8_t*>(wdn) + blockIdx.x * 15360, 15360);
  }
  __syncthreads();
  TS(1, 1);
  pdl_wait();
  TS(1, 2);
  if (tid == 0) {
    const uint8_t* kg = reinterpret_cast<const uint8_t*>(g_img + (size_t)(32 + head) * IMG_HEAD_ELEMS);
    const uint8_t* vg = reinterpret_cast<const uint8_t*>(g_img + (size_t)(64 + head) * IMG_HEAD_ELEMS);
    constexpr int CB = AT_KV_BYTES / AT_CHUNKS;
    for (int i = 0; i < AT_CHUNKS; i++) {
      mbar_expect_tx(sBar + 8 * i, 2 * CB);
      bulk_g2s(sK + i * CB, kg + i * CB, CB, sBar + 8 * i);
      bulk_g2s(sV + i * CB, vg + i * CB, CB, sBar + 8 * i);
    }
  }
  const int wg = warp >> 2, wwarp = warp & 3;
  const int g = lane >> 2, c4 = lane & 3;
  const uint64_t dk_base = make_desc(sK, 128, 384, 0);
  const uint64_t dv_base = make_desc(sV, 384, 128, 0);

#pragma unroll 1
  for (int rep = 0; rep < 8 / AT_WGS; rep++) {
    const int row0 = quarter * 512 + (rep * AT_WGS + wg) * 64 + wwarp * 16 + g;
    AttnState st;
    {
      const bf16* q0 = g_img + (size_t)head * IMG_HEAD_ELEMS + (size_t)(row0 >> 3) * 192 + g * 8 + c4 * 2;
      const bf16* q1 = q0 + 192;
      st.qa0 = *reinterpret_cast<const uint32_t*>(q0);
      st.qa1 = *reinterpret_cast<const uint32_t*>(q1);
      st.qa2 = *reinterpret_cast<const uint32_t*>(q0 + 64);
      st.qa3 = *reinterpret_cast<const uint32_t*>(q1 + 64);
      st.qa4 = *reinterpret_cast<const uint32_t*>(q0 + 128);
      st.qa5 = *reinterpret_cast<const uint32_t*>(q1 + 128);
    }
    float o[12];
    float s[32];
    uint32_t pa[16], pb[16];
    st.M0 = st.M1 = 0.f;
    if (rep == 0) mbar_wait(sBar, 0);
    wgmma_fence();
    wgmma_rs_n64(s, st.qa0, st.qa1, st.qa2, st.qa3, dk_base, 0);
    wgmma_rs_n64(s, st.qa4, st.qa5, 0u, 0u, dk_base + 16, 1);
    wgmma_commit();
    wgmma_wait<0>();
    fence_regs(s);
    attn_exp_exact(s, pa, o, st, true, c4);
    attn_step(s, pa, pb, o, st, sK + 3072, sV, 0, c4);
#pragma unroll 1
    for (int tt = 1; tt < 16; tt++) {
      if (rep == 0 && !(tt & 1)) mbar_wait(sBar + 8 * (tt >> 1), 0);
      attn_step(s, pb, pa, o, st, sK + tt * 6144, sV + tt * 6144 - 3072, 1, c4, wg, rep * 32 + tt * 2);
      attn_step(s, pa, pb, o, st, sK + tt * 6144 + 3072, sV + tt * 6144, 1, c4, wg, rep * 32 + tt * 2 + 1);
    }
    wgmma_fence();
#pragma unroll
    for (int kk = 0; kk < 4; kk++) wgmma_rs_n24_tb(o, pb[4 * kk], pb[4 * kk + 1], pb[4 * kk + 2], pb[4 * kk + 3], dv_base + 31 * 192 + kk * 48, 1);
    wgmma_commit();
    wgmma_wait<0>();
    fence_regs(o);
    TS(1, 3 + rep);
    const float l0 = __shfl_sync(0xffffffffu, o[8], (lane & ~3) | 2);
    const float l1 = __shfl_sync(0xffffffffu, o[10], (lane & ~3) | 2);
    const float i0 = 1.0f / l0, i1 = 1.0f / l1;
    bf16* o0 = g_o + (size_t)row0 * DM + head * DH;
    bf16* o1 = o0 + 8 * DM;
#pragma unroll
    for (int j = 0; j < 3; j++) {
      if (j < 2 || c4 < 2) {
        *reinterpret_cast<uint32_t*>(o0 + j * 8 + c4 * 2) = pack_bf16(o[4 * j] * i0, o[4 * j + 1] * i0);
        *reinterpret_cast<uint32_t*>(o1 + j * 8 + c4 * 2) = pack_bf16(o[4 * j + 2] * i1, o[4 * j + 3] * i1);
      }
    }
  }
}

typedef CUresult (*EncodeTiledFn)(CUtensorMap*, CUtensorMapDataType, cuuint32_t, void*, const cuuint64_t*, const cuuint64_t*,
                                  const cuuint32_t*, const cuuint32_t*, CUtensorMapInterleave, CUtensorMapSwizzle,
                                  CUtensorMapL2promotion, CUtensorMapFloatOOBfill);

static void make_map(EncodeTiledFn fn, CUtensorMap* tm, const void* ptr, uint64_t rows, uint64_t cols, uint32_t box_rows,
                     uint32_t box_cols, CUtensorMapSwizzle sw) {
  cuuint64_t dims[2] = {cols, rows};
  cuuint64_t strides[1] = {cols * 2};
  cuuint32_t box[2] = {box_cols, box_rows};
  cuuint32_t es[2] = {1, 1};
  fn(tm, CU_TENSOR_MAP_DATA_TYPE_BFLOAT16, 2, const_cast<void*>(ptr), dims, strides, box, es, CU_TENSOR_MAP_INTERLEAVE_NONE, sw,
     CU_TENSOR_MAP_L2_PROMOTION_L2_256B, CU_TENSOR_MAP_FLOAT_OOB_FILL_NONE);
}

template <typename... KArgs, typename... Args>
static void launch(void (*kern)(KArgs...), int grid, int block, int smem, int cluster, bool pdl, Args... args) {
  cudaLaunchConfig_t cfg = {};
  cfg.gridDim = dim3(grid);
  cfg.blockDim = dim3(block);
  cfg.dynamicSmemBytes = smem;
  cfg.stream = cudaStreamPerThread;
  cudaLaunchAttribute at[2];
  int n = 0;
  if (cluster > 1) {
    at[n].id = cudaLaunchAttributeClusterDimension;
    at[n].val.clusterDim.x = cluster; at[n].val.clusterDim.y = 1; at[n].val.clusterDim.z = 1;
    n++;
  }
  if (pdl) {
    at[n].id = cudaLaunchAttributeProgrammaticStreamSerialization;
    at[n].val.programmaticStreamSerializationAllowed = 1;
    n++;
  }
  cfg.attrs = at;
  cfg.numAttrs = n;
  cudaLaunchKernelEx(&cfg, kern, KArgs(args)...);
}

extern "C" void kernel_launch(void* const* d_in, const int* in_sizes, int n_in, void* d_out, int out_size) {
  const bf16* x = (const bf16*)d_in[0];
  const bf16* wqkv = (const bf16*)d_in[1];
  const bf16* wo = (const bf16*)d_in[2];
  const bf16* wg = (const bf16*)d_in[4];
  const bf16* wu = (const bf16*)d_in[5];
  const bf16* wd = (const bf16*)d_in[6];
  bf16* out = (bf16*)d_out;

  static EncodeTiledFn enc = nullptr;
  static void *p_o = nullptr, *p_h = nullptr, *p_hh = nullptr;
  if (!enc) {
    void* fn = nullptr;
    cudaDriverEntryPointQueryResult qr;
    cudaGetDriverEntryPoint("cuTensorMapEncodeTiled", &fn, cudaEnableDefault, &qr);
    enc = (EncodeTiledFn)fn;
    cudaGetSymbolAddress(&p_o, g_o);
    cudaGetSymbolAddress(&p_h, g_h);
    cudaGetSymbolAddress(&p_hh, g_hh);
    cudaFuncSetAttribute(qkv_kernel, cudaFuncAttributeMaxDynamicSharedMemorySize, KA_SMEM);
    cudaFuncSetAttribute(mlp_kernel, cudaFuncAttributeMaxDynamicSharedMemorySize, KC_SMEM);
    cudaFuncSetAttribute(attn_kernel, cudaFuncAttributeMaxDynamicSharedMemorySize, AT_SMEM);
  }
  CUtensorMap tm_wqkv, tm_wg, tm_wu, tm_wo64, tm_wo16, tm_wd64, tm_wd16, tm_o, tm_h, tm_hh, tm_hhs, tm_xn, tm_hs, tm_out;
  make_map(enc, &tm_wqkv, wqkv, DM, 3 * DM, 32, 64, CU_TENSOR_MAP_SWIZZLE_128B);
  make_map(enc, &tm_wg, wg, DM, FF, 32, 64, CU_TENSOR_MAP_SWIZZLE_128B);
  make_map(enc, &tm_wu, wu, DM, FF, 32, 64, CU_TENSOR_MAP_SWIZZLE_128B);
  make_map(enc, &tm_wo64, wo, DM, DM, 32, 64, CU_TENSOR_MAP_SWIZZLE_128B);
  make_map(enc, &tm_wo16, wo, DM, DM, 32, 16, CU_TENSOR_MAP_SWIZZLE_32B);
  make_map(enc, &tm_wd64, wd, FF, DM, 32, 64, CU_TENSOR_MAP_SWIZZLE_128B);
  make_map(enc, &tm_wd16, wd, FF, DM, 32, 16, CU_TENSOR_MAP_SWIZZLE_32B);
  make_map(enc, &tm_o, p_o, SEQ, DM, 128, 64, CU_TENSOR_MAP_SWIZZLE_128B);
  make_map(enc, &tm_h, p_h, SEQ, DM, 128, 32, CU_TENSOR_MAP_SWIZZLE_64B);
  make_map(enc, &tm_hh, p_hh, SEQ, FF, 128, 64, CU_TENSOR_MAP_SWIZZLE_128B);
  make_map(enc, &tm_hhs, p_hh, SEQ, FF, 64, 64, CU_TENSOR_MAP_SWIZZLE_128B);
  make_map(enc, &tm_xn, x, SEQ, DM, 128, 32, CU_TENSOR_MAP_SWIZZLE_64B);
  make_map(enc, &tm_hs, p_h, SEQ, DM, 64, 80, CU_TENSOR_MAP_SWIZZLE_NONE);
  make_map(enc, &tm_out, out, SEQ, DM, 64, 80, CU_TENSOR_MAP_SWIZZLE_NONE);

  launch(qkv_kernel, 128, GT, KA_SMEM, 2, false, tm_xn, tm_wqkv, x, wqkv);
  launch(attn_kernel, 132, AT_THREADS, AT_SMEM, 1, true, wo, wg, wu, wd);
  launch(mlp_kernel, 128, GT, KC_SMEM, 2, true, tm_o, tm_wo64, tm_wo16, tm_h, tm_wg, tm_wu, tm_hhs, tm_hh, tm_wd64, tm_wd16, tm_hs, tm_out, x);
}
```

```cpp
#include <cuda_runtime.h>
#include <cuda_bf16.h>
#include <cuda.h>
#include <stdint.h>

typedef __nv_bfloat16 bf16;
#define FLAGV 0

constexpr int SEQ = 2048, DM = 640, NH = 32, DH = 20, FF = 1536;
constexpr float ATT_SCALE_LOG2E = 0.22360679774997896f * 1.4426950408889634f;
constexpr int IMG_HEAD_ELEMS = (SEQ / 8) * 192;

__device__ __align__(1024) bf16 g_img[3 * NH * IMG_HEAD_ELEMS];
__device__ __align__(1024) bf16 g_o[SEQ * DM];
__device__ __align__(1024) bf16 g_h[SEQ * DM];
__device__ float2 g_stats[SEQ * 8];
__device__ float g_cs[2 * FF];
__device__ int g_flag[4 * 16];
__device__ float2 g_rs[SEQ];
__device__ float g_csp[16 * 3 * DM];
__device__ __align__(1024) bf16 g_hh[SEQ * FF];

#define TS(k, i)
#define PH(w, t, i)
__device__ __forceinline__ uint32_t smem_u32(const void* p) { return (uint32_t)__cvta_generic_to_shared(p); }
__device__ __forceinline__ void mbar_init(uint32_t bar, uint32_t cnt) {
  asm volatile("mbarrier.init.shared::cta.b64 [%0], %1;" ::"r"(bar), "r"(cnt) : "memory");
}
__device__ __forceinline__ void mbar_expect_tx(uint32_t bar, uint32_t bytes) {
  asm volatile("mbarrier.arrive.expect_tx.shared::cta.b64 _, [%0], %1;" ::"r"(bar), "r"(bytes) : "memory");
}
__device__ __forceinline__ void mbar_arrive(uint32_t bar) {
  asm volatile("mbarrier.arrive.shared::cta.b64 _, [%0];" ::"r"(bar) : "memory");
}
__device__ __forceinline__ void mbar_arrive_cluster(uint32_t bar, uint32_t cta) {
  asm volatile(
      "{\n.reg .b32 r;\nmapa.shared::cluster.u32 r, %0, %1;\n"
      "mbarrier.arrive.shared::cluster.b64 _, [r];\n}\n" ::"r"(bar), "r"(cta)
      : "memory");
}
__device__ __forceinline__ void mbar_wait(uint32_t bar, uint32_t parity) {
  asm volatile(
      "{\n.reg .pred p;\nLAB_WAIT:\n"
      "mbarrier.try_wait.parity.shared::cta.b64 p, [%0], %1;\n"
      "@p bra DONE;\nbra LAB_WAIT;\nDONE:\n}\n" ::"r"(bar), "r"(parity)
      : "memory");
}
__device__ __forceinline__ void mbar_wait_cluster(uint32_t bar, uint32_t parity) {
  asm volatile(
      "{\n.reg .pred p;\nLAB_WAIT:\n"
      "mbarrier.try_wait.parity.acquire.cluster.shared::cta.b64 p, [%0], %1;\n"
      "@p bra DONE;\nbra LAB_WAIT;\nDONE:\n}\n" ::"r"(bar), "r"(parity)
      : "memory");
}
__device__ __forceinline__ void fence_mbar_init() { asm volatile("fence.mbarrier_init.release.cluster;" ::: "memory"); }
__device__ __forceinline__ void fence_proxy_async() { asm volatile("fence.proxy.async.shared::cta;" ::: "memory"); }
__device__ __forceinline__ void cluster_sync_all() {
  asm volatile("barrier.cluster.arrive.release.aligned;\nbarrier.cluster.wait.acquire.aligned;" ::: "memory");
}
__device__ __forceinline__ void cluster_sync_relaxed() {
  asm volatile("barrier.cluster.arrive.relaxed.aligned;\nbarrier.cluster.wait.aligned;" ::: "memory");
}
__device__ __forceinline__ void named_bar_sync(int id, int n) { asm volatile("bar.sync %0, %1;" ::"r"(id), "r"(n) : "memory"); }
__device__ __forceinline__ bool wg_any(bool pred, int id) {
  uint32_t r;
  asm volatile("{\n.reg .pred p, q;\nsetp.ne.u32 p, %1, 0;\nbar.red.or.pred q, %2, 128, p;\nselp.u32 %0, 1, 0, q;\n}\n" : "=r"(r) : "r"((uint32_t)pred), "r"(id) : "memory");
  return r != 0;
}
__device__ __forceinline__ void fence_proxy_async_all() { asm volatile("fence.proxy.async;" ::: "memory"); }
__device__ __forceinline__ void flag_signal(int* f) {
  __threadfence();
  atomicAdd(f, 1);
}
__device__ __forceinline__ void flag_wait(const int* f, int target) {
  int v;
  unsigned spins = 0;
  do {
    asm volatile("ld.acquire.gpu.global.s32 %0, [%1];" : "=r"(v) : "l"(f) : "memory");
    if (++spins > (1u << 24)) __trap();
  } while (v < target);
}
__device__ __forceinline__ void pdl_launch() { asm volatile("griddepcontrol.launch_dependents;" ::: "memory"); }
__device__ __forceinline__ void pdl_wait() { asm volatile("griddepcontrol.wait;" ::: "memory"); }

__device__ __forceinline__ void tma_load_2d(uint32_t dst, const CUtensorMap* tm, int c0, int c1, uint32_t bar) {
  asm volatile(
      "cp.async.bulk.tensor.2d.shared::cluster.global.mbarrier::complete_tx::bytes [%0], [%1, {%3, %4}], [%2];" ::"r"(dst),
      "l"((uint64_t)tm), "r"(bar), "r"(c0), "r"(c1)
      : "memory");
}
__device__ __forceinline__ void tma_load_2d_mc(uint32_t dst, const CUtensorMap* tm, int c0, int c1, uint32_t bar, uint16_t mask) {
  asm volatile(
      "cp.async.bulk.tensor.2d.shared::cluster.global.mbarrier::complete_tx::bytes.multicast::cluster [%0], [%1, {%3, %4}], [%2], %5;" ::"r"(dst),
      "l"((uint64_t)tm), "r"(bar), "r"(c0), "r"(c1), "h"(mask)
      : "memory");
}
__device__ __forceinline__ void bulk_g2s(uint32_t dst, const void* src, uint32_t bytes, uint32_t bar) {
  asm volatile("cp.async.bulk.shared::cluster.global.mbarrier::complete_tx::bytes [%0], [%1], %2, [%3];" ::"r"(dst), "l"(src),
               "r"(bytes), "r"(bar)
               : "memory");
}
__device__ __forceinline__ void bulk_s2g(void* dst, uint32_t src, uint32_t bytes) {
  asm volatile("cp.async.bulk.global.shared::cta.bulk_group [%0], [%1], %2;" ::"l"(dst), "r"(src), "r"(bytes) : "memory");
}
__device__ __forceinline__ void tma_store_2d(const CUtensorMap* tm, uint32_t src, int c0, int c1) {
  asm volatile("cp.async.bulk.tensor.2d.global.shared::cta.bulk_group [%0, {%2, %3}], [%1];" ::"l"((uint64_t)tm), "r"(src), "r"(c0), "r"(c1) : "memory");
}
__device__ __forceinline__ void bulk_commit() { asm volatile("cp.async.bulk.commit_group;" ::: "memory"); }
__device__ __forceinline__ void bulk_wait_read() { asm volatile("cp.async.bulk.wait_group.read 0;" ::: "memory"); }
__device__ __forceinline__ void prefetch_l2(const void* p, uint32_t bytes) {
  asm volatile("cp.async.bulk.prefetch.L2.global [%0], %1;" ::"l"(p), "r"(bytes) : "memory");
}
__device__ __forceinline__ void bulk_wait_all() { asm volatile("cp.async.bulk.wait_group 0;" ::: "memory"); }
__device__ __forceinline__ void st_shared_b32(uint32_t addr, uint32_t v) { asm volatile("st.shared.b32 [%0], %1;" ::"r"(addr), "r"(v) : "memory"); }
__device__ __forceinline__ void st_shared_v2(uint32_t addr, uint32_t a, uint32_t b) { asm volatile("st.shared.v2.b32 [%0], {%1, %2};" ::"r"(addr), "r"(a), "r"(b) : "memory"); }
__device__ __forceinline__ void prefetch_tmap(const CUtensorMap* tm) {
  asm volatile("prefetch.tensormap [%0];" ::"l"((uint64_t)tm) : "memory");
}
__device__ __forceinline__ void wgmma_fence() { asm volatile("wgmma.fence.sync.aligned;" ::: "memory"); }
__device__ __forceinline__ void wgmma_commit() { asm volatile("wgmma.commit_group.sync.aligned;" ::: "memory"); }
template <int N>
__device__ __forceinline__ void wgmma_wait() { asm volatile("wgmma.wait_group.sync.aligned %0;" ::"n"(N) : "memory"); }

template <int N>
__device__ __forceinline__ void fence_regs(float (&r)[N]) {
#pragma unroll
  for (int i = 0; i < N; i++) asm volatile("" : "+f"(r[i])::"memory");
}
template <int N>
__device__ __forceinline__ void fence_regs(uint32_t (&r)[N]) {
#pragma unroll
  for (int i = 0; i < N; i++) asm volatile("" : "+r"(r[i])::"memory");
}
__device__ __forceinline__ uint64_t make_desc(uint32_t addr, uint32_t lbo, uint32_t sbo, uint32_t layout) {
  return (uint64_t)((addr & 0x3FFFF) >> 4) | ((uint64_t)((lbo & 0x3FFFF) >> 4) << 16) | ((uint64_t)((sbo & 0x3FFFF) >> 4) << 32) |
         ((uint64_t)layout << 62);
}
__device__ __forceinline__ uint32_t pack_bf16(float lo, float hi) {
  uint32_t r;
  asm("cvt.rn.bf16x2.f32 %0, %1, %2;" : "=r"(r) : "f"(hi), "f"(lo));
  return r;
}
__device__ __forceinline__ float bf16_round(float x) { return __bfloat162float(__float2bfloat16_rn(x)); }
__device__ __forceinline__ float bf_lo(uint32_t u) { return __uint_as_float(u << 16); }
__device__ __forceinline__ float bf_hi(uint32_t u) { return __uint_as_float(u & 0xffff0000u); }
__device__ __forceinline__ float ex2(float x) {
  float y;
  asm("ex2.approx.ftz.f32 %0, %1;" : "=f"(y) : "f"(x));
  return y;
}

__device__ __forceinline__ void wgmma_ss_n240_tb(float (&d)[120], uint64_t descA, uint64_t descB, int scaleD) {
  asm volatile("{\n.reg .pred p;\nsetp.ne.b32 p, %122, 0;\n"
    "wgmma.mma_async.sync.aligned.m64n240k16.f32.bf16.bf16 {%0, %1, %2, %3, %4, %5, %6, %7, %8, %9, %10, %11, %12, %13, %14, %15, %16, %17, %18, %19, %20, %21, %22, %23, %24, %25, %26, %27, %28, %29, %30, %31, %32, %33, %34, %35, %36, %37, %38, %39, %40, %41, %42, %43, %44, %45, %46, %47, %48, %49, %50, %51, %52, %53, %54, %55, %56, %57, %58, %59, %60, %61, %62, %63, %64, %65, %66, %67, %68, %69, %70, %71, %72, %73, %74, %75, %76, %77, %78, %79, %80, %81, %82, %83, %84, %85, %86, %87, %88, %89, %90, %91, %92, %93, %94, %95, %96, %97, %98, %99, %100, %101, %102, %103, %104, %105, %106, %107, %108, %109, %110, %111, %112, %113, %114, %115, %116, %117, %118, %119}, %120, %121, p, 1, 1, 0, 1;\n}\n"
    : "+f"(d[0]), "+f"(d[1]), "+f"(d[2]), "+f"(d[3]), "+f"(d[4]), "+f"(d[5]), "+f"(d[6]), "+f"(d[7]), "+f"(d[8]), "+f"(d[9]), "+f"(d[10]), "+f"(d[11]), "+f"(d[12]), "+f"(d[13]), "+f"(d[14]), "+f"(d[15]), "+f"(d[16]), "+f"(d[17]), "+f"(d[18]), "+f"(d[19]), "+f"(d[20]), "+f"(d[21]), "+f"(d[22]), "+f"(d[23]), "+f"(d[24]), "+f"(d[25]), "+f"(d[26]), "+f"(d[27]), "+f"(d[28]), "+f"(d[29]), "+f"(d[30]), "+f"(d[31]), "+f"(d[32]), "+f"(d[33]), "+f"(d[34]), "+f"(d[35]), "+f"(d[36]), "+f"(d[37]), "+f"(d[38]), "+f"(d[39]), "+f"(d[40]), "+f"(d[41]), "+f"(d[42]), "+f"(d[43]), "+f"(d[44]), "+f"(d[45]), "+f"(d[46]), "+f"(d[47]), "+f"(d[48]), "+f"(d[49]), "+f"(d[50]), "+f"(d[51]), "+f"(d[52]), "+f"(d[53]), "+f"(d[54]), "+f"(d[55]), "+f"(d[56]), "+f"(d[57]), "+f"(d[58]), "+f"(d[59]), "+f"(d[60]), "+f"(d[61]), "+f"(d[62]), "+f"(d[63]), "+f"(d[64]), "+f"(d[65]), "+f"(d[66]), "+f"(d[67]), "+f"(d[68]), "+f"(d[69]), "+f"(d[70]), "+f"(d[71]), "+f"(d[72]), "+f"(d[73]), "+f"(d[74]), "+f"(d[75]), "+f"(d[76]), "+f"(d[77]), "+f"(d[78]), "+f"(d[79]), "+f"(d[80]), "+f"(d[81]), "+f"(d[82]), "+f"(d[83]), "+f"(d[84]), "+f"(d[85]), "+f"(d[86]), "+f"(d[87]), "+f"(d[88]), "+f"(d[89]), "+f"(d[90]), "+f"(d[91]), "+f"(d[92]), "+f"(d[93]), "+f"(d[94]), "+f"(d[95]), "+f"(d[96]), "+f"(d[97]), "+f"(d[98]), "+f"(d[99]), "+f"(d[100]), "+f"(d[101]), "+f"(d[102]), "+f"(d[103]), "+f"(d[104]), "+f"(d[105]), "+f"(d[106]), "+f"(d[107]), "+f"(d[108]), "+f"(d[109]), "+f"(d[110]), "+f"(d[111]), "+f"(d[112]), "+f"(d[113]), "+f"(d[114]), "+f"(d[115]), "+f"(d[116]), "+f"(d[117]), "+f"(d[118]), "+f"(d[119])
    : "l"(descA), "l"(descB), "r"(scaleD));
}
__device__ __forceinline__ void wgmma_ss_n192_tb(float (&d)[96], uint64_t descA, uint64_t descB, int scaleD) {
  asm volatile("{\n.reg .pred p;\nsetp.ne.b32 p, %98, 0;\n"
    "wgmma.mma_async.sync.aligned.m64n192k16.f32.bf16.bf16 {%0, %1, %2, %3, %4, %5, %6, %7, %8, %9, %10, %11, %12, %13, %14, %15, %16, %17, %18, %19, %20, %21, %22, %23, %24, %25, %26, %27, %28, %29, %30, %31, %32, %33, %34, %35, %36, %37, %38, %39, %40, %41, %42, %43, %44, %45, %46, %47, %48, %49, %50, %51, %52, %53, %54, %55, %56, %57, %58, %59, %60, %61, %62, %63, %64, %65, %66, %67, %68, %69, %70, %71, %72, %73, %74, %75, %76, %77, %78, %79, %80, %81, %82, %83, %84, %85, %86, %87, %88, %89, %90, %91, %92, %93, %94, %95}, %96, %97, p, 1, 1, 0, 1;\n}\n"
    : "+f"(d[0]), "+f"(d[1]), "+f"(d[2]), "+f"(d[3]), "+f"(d[4]), "+f"(d[5]), "+f"(d[6]), "+f"(d[7]), "+f"(d[8]), "+f"(d[9]), "+f"(d[10]), "+f"(d[11]), "+f"(d[12]), "+f"(d[13]), "+f"(d[14]), "+f"(d[15]), "+f"(d[16]), "+f"(d[17]), "+f"(d[18]), "+f"(d[19]), "+f"(d[20]), "+f"(d[21]), "+f"(d[22]), "+f"(d[23]), "+f"(d[24]), "+f"(d[25]), "+f"(d[26]), "+f"(d[27]), "+f"(d[28]), "+f"(d[29]), "+f"(d[30]), "+f"(d[31]), "+f"(d[32]), "+f"(d[33]), "+f"(d[34]), "+f"(d[35]), "+f"(d[36]), "+f"(d[37]), "+f"(d[38]), "+f"(d[39]), "+f"(d[40]), "+f"(d[41]), "+f"(d[42]), "+f"(d[43]), "+f"(d[44]), "+f"(d[45]), "+f"(d[46]), "+f"(d[47]), "+f"(d[48]), "+f"(d[49]), "+f"(d[50]), "+f"(d[51]), "+f"(d[52]), "+f"(d[53]), "+f"(d[54]), "+f"(d[55]), "+f"(d[56]), "+f"(d[57]), "+f"(d[58]), "+f"(d[59]), "+f"(d[60]), "+f"(d[61]), "+f"(d[62]), "+f"(d[63]), "+f"(d[64]), "+f"(d[65]), "+f"(d[66]), "+f"(d[67]), "+f"(d[68]), "+f"(d[69]), "+f"(d[70]), "+f"(d[71]), "+f"(d[72]), "+f"(d[73]), "+f"(d[74]), "+f"(d[75]), "+f"(d[76]), "+f"(d[77]), "+f"(d[78]), "+f"(d[79]), "+f"(d[80]), "+f"(d[81]), "+f"(d[82]), "+f"(d[83]), "+f"(d[84]), "+f"(d[85]), "+f"(d[86]), "+f"(d[87]), "+f"(d[88]), "+f"(d[89]), "+f"(d[90]), "+f"(d[91]), "+f"(d[92]), "+f"(d[93]), "+f"(d[94]), "+f"(d[95])
    : "l"(descA), "l"(descB), "r"(scaleD));
}
__device__ __forceinline__ void wgmma_ss_n64_tb(float (&d)[32], uint64_t descA, uint64_t descB, int scaleD) {
  asm volatile("{\n.reg .pred p;\nsetp.ne.b32 p, %34, 0;\n"
    "wgmma.mma_async.sync.aligned.m64n64k16.f32.bf16.bf16 {%0, %1, %2, %3, %4, %5, %6, %7, %8, %9, %10, %11, %12, %13, %14, %15, %16, %17, %18, %19, %20, %21, %22, %23, %24, %25, %26, %27, %28, %29, %30, %31}, %32, %33, p, 1, 1, 0, 1;\n}\n"
    : "+f"(d[0]), "+f"(d[1]), "+f"(d[2]), "+f"(d[3]), "+f"(d[4]), "+f"(d[5]), "+f"(d[6]), "+f"(d[7]), "+f"(d[8]), "+f"(d[9]), "+f"(d[10]), "+f"(d[11]), "+f"(d[12]), "+f"(d[13]), "+f"(d[14]), "+f"(d[15]), "+f"(d[16]), "+f"(d[17]), "+f"(d[18]), "+f"(d[19]), "+f"(d[20]), "+f"(d[21]), "+f"(d[22]), "+f"(d[23]), "+f"(d[24]), "+f"(d[25]), "+f"(d[26]), "+f"(d[27]), "+f"(d[28]), "+f"(d[29]), "+f"(d[30]), "+f"(d[31])
    : "l"(descA), "l"(descB), "r"(scaleD));
}
__device__ __forceinline__ void wgmma_ss_n16_tb(float (&d)[8], uint64_t descA, uint64_t descB, int scaleD) {
  asm volatile("{\n.reg .pred p;\nsetp.ne.b32 p, %10, 0;\n"
    "wgmma.mma_async.sync.aligned.m64n16k16.f32.bf16.bf16 {%0, %1, %2, %3, %4, %5, %6, %7}, %8, %9, p, 1, 1, 0, 1;\n}\n"
    : "+f"(d[0]), "+f"(d[1]), "+f"(d[2]), "+f"(d[3]), "+f"(d[4]), "+f"(d[5]), "+f"(d[6]), "+f"(d[7])
    : "l"(descA), "l"(descB), "r"(scaleD));
}
__device__ __forceinline__ void wgmma_rs_n128(float (&d)[64], uint32_t a0, uint32_t a1, uint32_t a2, uint32_t a3, uint64_t descB, int scaleD) {
  asm volatile("{\n.reg .pred p;\nsetp.ne.b32 p, %69, 0;\n"
    "wgmma.mma_async.sync.aligned.m64n128k16.f32.bf16.bf16 {%0, %1, %2, %3, %4, %5, %6, %7, %8, %9, %10, %11, %12, %13, %14, %15, %16, %17, %18, %19, %20, %21, %22, %23, %24, %25, %26, %27, %28, %29, %30, %31, %32, %33, %34, %35, %36, %37, %38, %39, %40, %41, %42, %43, %44, %45, %46, %47, %48, %49, %50, %51, %52, %53, %54, %55, %56, %57, %58, %59, %60, %61, %62, %63}, {%64, %65, %66, %67}, %68, p, 1, 1, 0;\n}\n"
    : "+f"(d[0]), "+f"(d[1]), "+f"(d[2]), "+f"(d[3]), "+f"(d[4]), "+f"(d[5]), "+f"(d[6]), "+f"(d[7]), "+f"(d[8]), "+f"(d[9]), "+f"(d[10]), "+f"(d[11]), "+f"(d[12]), "+f"(d[13]), "+f"(d[14]), "+f"(d[15]), "+f"(d[16]), "+f"(d[17]), "+f"(d[18]), "+f"(d[19]), "+f"(d[20]), "+f"(d[21]), "+f"(d[22]), "+f"(d[23]), "+f"(d[24]), "+f"(d[25]), "+f"(d[26]), "+f"(d[27]), "+f"(d[28]), "+f"(d[29]), "+f"(d[30]), "+f"(d[31]), "+f"(d[32]), "+f"(d[33]), "+f"(d[34]), "+f"(d[35]), "+f"(d[36]), "+f"(d[37]), "+f"(d[38]), "+f"(d[39]), "+f"(d[40]), "+f"(d[41]), "+f"(d[42]), "+f"(d[43]), "+f"(d[44]), "+f"(d[45]), "+f"(d[46]), "+f"(d[47]), "+f"(d[48]), "+f"(d[49]), "+f"(d[50]), "+f"(d[51]), "+f"(d[52]), "+f"(d[53]), "+f"(d[54]), "+f"(d[55]), "+f"(d[56]), "+f"(d[57]), "+f"(d[58]), "+f"(d[59]), "+f"(d[60]), "+f"(d[61]), "+f"(d[62]), "+f"(d[63])
    : "r"(a0), "r"(a1), "r"(a2), "r"(a3), "l"(descB), "r"(scaleD));
}
__device__ __forceinline__ void wgmma_rs_n64(float (&d)[32], uint32_t a0, uint32_t a1, uint32_t a2, uint32_t a3, uint64_t descB, int scaleD) {
  asm volatile("{\n.reg .pred p;\nsetp.ne.b32 p, %37, 0;\n"
    "wgmma.mma_async.sync.aligned.m64n64k16.f32.bf16.bf16 {%0, %1, %2, %3, %4, %5, %6, %7, %8, %9, %10, %11, %12, %13, %14, %15, %16, %17, %18, %19, %20, %21, %22, %23, %24, %25, %26, %27, %28, %29, %30, %31}, {%32, %33, %34, %35}, %36, p, 1, 1, 0;\n}\n"
    : "+f"(d[0]), "+f"(d[1]), "+f"(d[2]), "+f"(d[3]), "+f"(d[4]), "+f"(d[5]), "+f"(d[6]), "+f"(d[7]), "+f"(d[8]), "+f"(d[9]), "+f"(d[10]), "+f"(d[11]), "+f"(d[12]), "+f"(d[13]), "+f"(d[14]), "+f"(d[15]), "+f"(d[16]), "+f"(d[17]), "+f"(d[18]), "+f"(d[19]), "+f"(d[20]), "+f"(d[21]), "+f"(d[22]), "+f"(d[23]), "+f"(d[24]), "+f"(d[25]), "+f"(d[26]), "+f"(d[27]), "+f"(d[28]), "+f"(d[29]), "+f"(d[30]), "+f"(d[31])
    : "r"(a0), "r"(a1), "r"(a2), "r"(a3), "l"(descB), "r"(scaleD));
}
__device__ __forceinline__ void wgmma_rs_n24_tb(float (&d)[12], uint32_t a0, uint32_t a1, uint32_t a2, uint32_t a3, uint64_t descB, int scaleD) {
  asm volatile("{\n.reg .pred p;\nsetp.ne.b32 p, %17, 0;\n"
    "wgmma.mma_async.sync.aligned.m64n24k16.f32.bf16.bf16 {%0, %1, %2, %3, %4, %5, %6, %7, %8, %9, %10, %11}, {%12, %13, %14, %15}, %16, p, 1, 1, 1;\n}\n"
    : "+f"(d[0]), "+f"(d[1]), "+f"(d[2]), "+f"(d[3]), "+f"(d[4]), "+f"(d[5]), "+f"(d[6]), "+f"(d[7]), "+f"(d[8]), "+f"(d[9]), "+f"(d[10]), "+f"(d[11])
    : "r"(a0), "r"(a1), "r"(a2), "r"(a3), "l"(descB), "r"(scaleD));
}

constexpr int GT = 384;

__device__ __forceinline__ void release_stage(uint32_t bar, bool leader) {
  if (leader) {
    mbar_arrive_cluster(bar, 0);
    mbar_arrive_cluster(bar, 1);
  }
}

__device__ __forceinline__ float2 ln_row_stats(const bf16* __restrict__ xin, int l16) {
  const uint4* src = reinterpret_cast<const uint4*>(xin);
  uint4 v[5];
#pragma unroll
  for (int j = 0; j < 5; j++) v[j] = __ldg(src + j * 16 + l16);
  float s0 = 0.f, s1 = 0.f, s2 = 0.f, s3 = 0.f;
#pragma unroll
  for (int j = 0; j < 5; j++) {
    s0 += bf_lo(v[j].x) + bf_hi(v[j].x);
    s1 += bf_lo(v[j].y) + bf_hi(v[j].y);
    s2 += bf_lo(v[j].z) + bf_hi(v[j].z);
    s3 += bf_lo(v[j].w) + bf_hi(v[j].w);
  }
  float mean = (s0 + s1) + (s2 + s3);
#pragma unroll
  for (int o = 1; o < 16; o <<= 1) mean += __shfl_xor_sync(0xffffffffu, mean, o);
  mean *= (1.0f / DM);
  s0 = s1 = s2 = s3 = 0.f;
#pragma unroll
  for (int j = 0; j < 5; j++) {
    float d;
    d = bf_lo(v[j].x) - mean; s0 = fmaf(d, d, s0);
    d = bf_hi(v[j].x) - mean; s1 = fmaf(d, d, s1);
    d = bf_lo(v[j].y) - mean; s2 = fmaf(d, d, s2);
    d = bf_hi(v[j].y) - mean; s3 = fmaf(d, d, s3);
    d = bf_lo(v[j].z) - mean; s0 = fmaf(d, d, s0);
    d = bf_hi(v[j].z) - mean; s1 = fmaf(d, d, s1);
    d = bf_lo(v[j].w) - mean; s2 = fmaf(d, d, s2);
    d = bf_hi(v[j].w) - mean; s3 = fmaf(d, d, s3);
  }
  float sq = (s0 + s1) + (s2 + s3);
#pragma unroll
  for (int o = 1; o < 16; o <<= 1) sq += __shfl_xor_sync(0xffffffffu, sq, o);
  const float var_b = bf16_round(sq * (1.0f / DM));
  const float den = bf16_round(sqrtf(bf16_round(var_b + 1e-5f)));
  return make_float2(bf16_round(mean), __frcp_rn(den));
}

constexpr int LG_STAGES = 5;
constexpr int QKV_STAGE = 8192 + 4 * 4096;
constexpr int GLU_STAGE = 8192 + 6 * 4096;

template <int WG>
__device__ __forceinline__ void qkv_mainloop(float (&acc)[120], uint32_t sbase, uint32_t sBar, bool leader) {
  constexpr int STAGE_BYTES = QKV_STAGE, NST = LG_STAGES;
  const uint64_t da_base = make_desc(sbase + WG * 4096, 16, 512, 2);
  const uint64_t db_base = make_desc(sbase + 8192, 4096, 1024, 1);
#pragma unroll 1
  for (int r = 0; r < 20 / NST; r++) {
#pragma unroll
    for (int s = 0; s < NST; s++) {
      mbar_wait(sBar + 8 * s, r & 1);
      wgmma_fence();
#pragma unroll
      for (int ks = 0; ks < 2; ks++)
        wgmma_ss_n240_tb(acc, da_base + (uint64_t)((s * STAGE_BYTES + ks * 32) >> 4), db_base + (uint64_t)((s * STAGE_BYTES + ks * 2048) >> 4), 1);
      wgmma_commit();
      wgmma_wait<1>();
      release_stage(sBar + 8 * (NST + (s + NST - 1) % NST), leader && (s > 0 || r > 0));
    }
  }
}
template <int WG>
__device__ __forceinline__ void glu_mainloop(float (&accg)[96], float (&accu)[96], uint32_t sbase, uint32_t sBar, bool leader) {
  constexpr int STAGE_BYTES = GLU_STAGE, NST = LG_STAGES;
  const uint64_t da_base = make_desc(sbase + WG * 4096, 16, 512, 2);
  const uint64_t db_base = make_desc(sbase + 8192, 4096, 1024, 1);
#pragma unroll 1
  for (int r = 0; r < 20 / NST; r++) {
#pragma unroll
    for (int s = 0; s < NST; s++) {
      mbar_wait(sBar + 8 * s, r & 1);
      wgmma_fence();
#pragma unroll
      for (int ks = 0; ks < 2; ks++) {
        const uint64_t da = da_base + (uint64_t)((s * STAGE_BYTES + ks * 32) >> 4);
        wgmma_ss_n192_tb(accg, da, db_base + (uint64_t)((s * STAGE_BYTES + ks * 2048) >> 4), 1);
        wgmma_ss_n192_tb(accu, da, db_base + (uint64_t)((s * STAGE_BYTES + 3 * 4096 + ks * 2048) >> 4), 1);
      }
      wgmma_commit();
      wgmma_wait<1>();
      release_stage(sBar + 8 * (NST + (s + NST - 1) % NST), leader && (s > 0 || r > 0));
    }
  }
}
constexpr int RG_STAGE_BYTES = 16384 + 8192 + 2048;
template <int NKB, int NST, int WG>
__device__ __forceinline__ void res_mainloop(float (&acc0)[32], float (&acc1)[8], uint32_t sbase, uint32_t sBar, bool leader) {
  const uint64_t da_base = make_desc(sbase + WG * 8192, 16, 1024, 1);
  const uint64_t db0_base = make_desc(sbase + 16384, 8192, 1024, 1);
  const uint64_t db1_base = make_desc(sbase + 16384 + 8192, 2048, 256, 3);
#pragma unroll 1
  for (int r = 0; r < NKB / NST; r++) {
#pragma unroll
    for (int s = 0; s < NST; s++) {
      const uint64_t so = (uint64_t)(s * (RG_STAGE_BYTES >> 4));
      mbar_wait(sBar + 8 * s, r & 1);
      wgmma_fence();
#pragma unroll
      for (int ks = 0; ks < 4; ks++) {
        wgmma_ss_n64_tb(acc0, da_base + so + ks * 2, db0_base + so + ks * 128, 1);
        wgmma_ss_n16_tb(acc1, da_base + so + ks * 2, db1_base + so + ks * 32, 1);
      }
      wgmma_commit();
      wgmma_wait<1>();
      release_stage(sBar + 8 * (NST + (s + NST - 1) % NST), leader && (s > 0 || r > 0));
    }
  }
}

constexpr int KA_CS = LG_STAGES * QKV_STAGE + 128;
constexpr int KA_SMEM = KA_CS + 1024 + 3072 + 1024;

__global__ void __launch_bounds__(GT, 1)
qkv_kernel(const __grid_constant__ CUtensorMap tmA, const __grid_constant__ CUtensorMap tmB, const bf16* __restrict__ x,
           const bf16* __restrict__ wqkv) {
  constexpr int STAGE_BYTES = QKV_STAGE, NST = LG_STAGES, NKB = 20;
  extern __shared__ uint8_t smem_raw[];
  const uint32_t sbase = (smem_u32(smem_raw) + 1023u) & ~1023u;
  const uint32_t sBar = sbase + NST * STAGE_BYTES;
  const int tid = threadIdx.x, warp = tid >> 5, lane = tid & 31;
  const int rank = blockIdx.x & 1;
  const int pair = blockIdx.x >> 1;
  const int n_blk = pair & 7;
  const int m_blk = (pair >> 3) * 2 + rank;
  TS(0, 0);
  if (tid == 256) {
    prefetch_tmap(&tmA);
    prefetch_tmap(&tmB);
  }
  if (tid == 0) {
    for (int s = 0; s < NST; s++) {
      mbar_init(sBar + 8 * s, 1);
      mbar_init(sBar + 8 * (NST + s), 4);
    }
    fence_mbar_init();
    if (blockIdx.x < 32) g_flag[16 + blockIdx.x] = 0;
  }
  pdl_launch();
  cluster_sync_all();

  if (warp >= 8) {
    asm volatile("setmaxnreg.dec.sync.aligned.u32 56;");
    if (warp >= 9) {
      const int w3 = warp - 9;
      float* red = reinterpret_cast<float*>(smem_raw + (sbase - smem_u32(smem_raw)) + KA_CS + 1024);
      if (lane < 30) {
        float a[8];
#pragma unroll
        for (int i = 0; i < 8; i++) a[i] = 0.f;
        const uint4* w = reinterpret_cast<const uint4*>(wqkv + (size_t)(m_blk * 40) * (3 * DM) + n_blk * 240) + lane;
#pragma unroll
        for (int r = w3; r < 42; r += 3) {
          if (r >= 40) break;
          const uint4 v = __ldg(w + (size_t)r * (3 * DM / 8));
          a[0] += bf_lo(v.x); a[1] += bf_hi(v.x); a[2] += bf_lo(v.y); a[3] += bf_hi(v.y);
          a[4] += bf_lo(v.z); a[5] += bf_hi(v.z); a[6] += bf_lo(v.w); a[7] += bf_hi(v.w);
        }
#pragma unroll
        for (int i = 0; i < 8; i++) red[w3 * 240 + lane * 8 + i] = a[i];
      }
      named_bar_sync(4, 96);
      for (int c = tid - 288; c < 240; c += 96) g_csp[m_blk * (3 * DM) + n_blk * 240 + c] = (red[c] + red[240 + c]) + red[480 + c];
      named_bar_sync(4, 96);
      if (tid == 288) flag_signal(&g_flag[48 + n_blk]);
    }
    if (tid == 256) {
      auto issue_b = [&](int kb) {
        const int s = kb % NST;
        const uint32_t full = sBar + 8 * s;
        mbar_expect_tx(full, STAGE_BYTES);
        const uint32_t dst = sbase + s * STAGE_BYTES + 8192;
#pragma unroll
        for (int j = 0; j < 2; j++) {
          const int sl = rank * 2 + j;
          tma_load_2d_mc(dst + sl * 4096, &tmB, n_blk * 240 + sl * 64, kb * 32, full, (uint16_t)3);
        }
      };
      for (int kb = 0; kb < NKB; kb++) {
        const int s = kb % NST;
        if (kb >= NST) mbar_wait(sBar + 8 * (NST + s), ((kb / NST) & 1) ^ 1);
        issue_b(kb);
        tma_load_2d(sbase + s * STAGE_BYTES, &tmA, kb * 32, m_blk * 128, sBar + 8 * s);
      }
    }
  } else {
    asm volatile("setmaxnreg.inc.sync.aligned.u32 224;");
    const int wg = __shfl_sync(0xffffffffu, warp >> 2, 0);
    const int wwarp = warp & 3;
    {
      const int row = m_blk * 128 + n_blk * 16 + warp * 2 + (lane >> 4);
      const float2 rs = ln_row_stats(x + (size_t)row * DM, lane & 15);
      if ((lane & 15) == 0) g_rs[row] = rs;
      named_bar_sync(3, 256);
      if (tid == 0) flag_signal(&g_flag[m_blk]);
    }
    TS(0, 1);
    mbar_wait(sBar, 0);
    TS(0, 3);
    float acc[120];
#pragma unroll
    for (int i = 0; i < 120; i++) acc[i] = 0.f;
    if (wg == 0) qkv_mainloop<0>(acc, sbase, sBar, (tid & 127) == 0);
    else qkv_mainloop<1>(acc, sbase, sBar, (tid & 127) == 0);
    wgmma_wait<0>();
    fence_regs(acc);
    TS(0, 4);
    const int g = lane >> 2, c4 = lane & 3;
    float* cs_s = reinterpret_cast<float*>(smem_raw + (sbase - smem_u32(smem_raw)) + KA_CS);
    flag_wait(&g_flag[m_blk], 8);
    flag_wait(&g_flag[48 + n_blk], 16);
    if (tid < 240) {
      float c = 0.f;
#pragma unroll
      for (int mm = 0; mm < 16; mm++) c += g_csp[mm * (3 * DM) + n_blk * 240 + tid];
      cs_s[tid] = c;
    }
    const float2 rs0 = g_rs[m_blk * 128 + wg * 64 + wwarp * 16 + g], rs1 = g_rs[m_blk * 128 + wg * 64 + wwarp * 16 + g + 8];
    named_bar_sync(3, 256);
    const uint32_t stg = sbase + wg * (12 * 3072) + (wwarp * 2) * 384 + g * 16;
    const int hbase = n_blk * 12;
#pragma unroll
    for (int j = 0; j < 30; j++) {
      const int cb = (j * 8) % 20;
      const int hb = (j * 8) / 20;
      int d = cb + c4 * 2;
      int hl = hb;
      if (cb == 16 && c4 >= 2) { d -= 20; hl += 1; }
      const uint32_t a0 = stg + hl * 3072 + (d >> 3) * 128 + (d & 7) * 2;
      const int hg = hbase + hl;
      const float sc = hg < 32 ? ATT_SCALE_LOG2E : 1.0f;
      const float2 cc = *reinterpret_cast<const float2*>(cs_s + j * 8 + c4 * 2);
      const float i0 = rs0.y * sc, i1 = rs1.y * sc;
      st_shared_b32(a0, pack_bf16(fmaf(-rs0.x, cc.x, acc[4 * j]) * i0, fmaf(-rs0.x, cc.y, acc[4 * j + 1]) * i0));
      st_shared_b32(a0 + 384, pack_bf16(fmaf(-rs1.x, cc.x, acc[4 * j + 2]) * i1, fmaf(-rs1.x, cc.y, acc[4 * j + 3]) * i1));
      if (d == 18) {
        const uint32_t pad0 = hg < 32 ? 0u : (hg < 64 ? 0x3f803f80u : 0x00003f80u);
        const uint32_t pad1 = (hg >= 32 && hg < 64) ? 0x00003f80u : 0u;
        st_shared_v2(a0 + 4, pad0, pad1);
        st_shared_v2(a0 + 388, pad0, pad1);
      }
      if (j % 10 == 9) {
        fence_proxy_async();
        named_bar_sync(1 + wg, 128);
        if ((tid & 127) < 4) {
          const int hs = (j / 10) * 4 + (tid & 127);
          bf16* dst = g_img + (size_t)(hbase + hs) * IMG_HEAD_ELEMS + (size_t)(m_blk * 16 + wg * 8) * 192;
          bulk_s2g(dst, sbase + wg * (12 * 3072) + hs * 3072, 3072);
          bulk_commit();
        }
      }
    }
    if ((tid & 127) < 4) bulk_wait_read();
  }
  __syncwarp();
  TS(0, 5);
  cluster_sync_relaxed();
  TS(0, 6);
}

constexpr int KC_NST1 = 5, KC_NST3 = 6;
constexpr int KC_STAGING = 160 * 1024;
constexpr int KC_BAR = KC_STAGING + 48 * 1024;
constexpr int KC_CS = KC_BAR + 512;
constexpr int KC_SMEM = KC_CS + 1536 + 1024;

__global__ void __launch_bounds__(GT, 1)
mlp_kernel(const __grid_constant__ CUtensorMap tmO, const __grid_constant__ CUtensorMap tmWo64, const __grid_constant__ CUtensorMap tmWo16,
           const __grid_constant__ CUtensorMap tmH, const __grid_constant__ CUtensorMap tmWg, const __grid_constant__ CUtensorMap tmWu,
           const __grid_constant__ CUtensorMap tmHHs, const __grid_constant__ CUtensorMap tmHH, const __grid_constant__ CUtensorMap tmWd64,
           const __grid_constant__ CUtensorMap tmWd16, const __grid_constant__ CUtensorMap tmHs, const __grid_constant__ CUtensorMap tmOut,
           const bf16* __restrict__ x) {
  extern __shared__ uint8_t smem_raw[];
  const uint32_t sbase = (smem_u32(smem_raw) + 1023u) & ~1023u;
  const uint32_t bar1 = sbase + KC_BAR;
  const uint32_t bar2 = bar1 + 128;
  const uint32_t bar3 = bar2 + 128;
  const uint32_t barD = bar3 + 128;
  const int tid = threadIdx.x, warp = tid >> 5, lane = tid & 31;
  const int rank = blockIdx.x & 1;
  const int pair = blockIdx.x >> 1;
  const int j_blk = pair & 7;
  const int m_blk = (pair >> 3) * 2 + rank;
  const int n0 = j_blk * 80;
  TS(2, 0);
  if (tid == 256) {
    prefetch_tmap(&tmO); prefetch_tmap(&tmWo64); prefetch_tmap(&tmWo16); prefetch_tmap(&tmH); prefetch_tmap(&tmWg);
    prefetch_tmap(&tmWu); prefetch_tmap(&tmHHs); prefetch_tmap(&tmHH); prefetch_tmap(&tmWd64); prefetch_tmap(&tmWd16);
    prefetch_tmap(&tmHs); prefetch_tmap(&tmOut);
  }
  if (tid == 0) {
    for (int s = 0; s < 5; s++) {
      mbar_init(bar1 + 8 * s, 1); mbar_init(bar1 + 8 * (5 + s), 4);
      mbar_init(bar2 + 8 * s, 1); mbar_init(bar2 + 8 * (5 + s), 4);
    }
    for (int s = 0; s < 6; s++) { mbar_init(bar3 + 8 * s, 1); mbar_init(bar3 + 8 * (6 + s), 4); }
    mbar_init(barD, 4); mbar_init(barD + 8, 4);
    fence_mbar_init();
  }
  cluster_sync_all();

  if (warp >= 8) {
    asm volatile("setmaxnreg.dec.sync.aligned.u32 40;");
    if (tid == 256) {
      auto issue_b80 = [&](const CUtensorMap* t64, const CUtensorMap* t16, uint32_t bars, int nst, int kb) {
        const int s = kb % nst;
        const uint32_t full = bars + 8 * s;
        const uint32_t st = sbase + s * RG_STAGE_BYTES;
        mbar_expect_tx(full, RG_STAGE_BYTES);
        tma_load_2d_mc(st + 16384 + rank * 4096, t64, n0, kb * 64 + rank * 32, full, (uint16_t)3);
        tma_load_2d_mc(st + 16384 + 8192 + rank * 1024, t16, n0 + 64, kb * 64 + rank * 32, full, (uint16_t)3);
      };
      for (int kb = 0; kb < KC_NST1; kb++) issue_b80(&tmWo64, &tmWo16, bar1, KC_NST1, kb);
      pdl_wait();
      for (int kb = 0; kb < 10; kb++) {
        const int s = kb % KC_NST1;
        if (kb >= KC_NST1) {
          mbar_wait(bar1 + 8 * (KC_NST1 + s), ((kb / KC_NST1) & 1) ^ 1);
          issue_b80(&tmWo64, &tmWo16, bar1, KC_NST1, kb);
        }
        tma_load_2d(sbase + s * RG_STAGE_BYTES, &tmO, kb * 64, m_blk * 128, bar1 + 8 * s);
      }
      auto issue_bglu = [&](int kb) {
        const int s = kb % LG_STAGES;
        const uint32_t full = bar2 + 8 * s;
        mbar_expect_tx(full, GLU_STAGE);
        const uint32_t dst = sbase + s * GLU_STAGE + 8192;
#pragma unroll
        for (int j = 0; j < 3; j++)
          tma_load_2d_mc(dst + (rank * 3 + j) * 4096, rank == 0 ? &tmWg : &tmWu, j_blk * 192 + j * 64, kb * 32, full, (uint16_t)3);
      };
      mbar_wait(barD, 0);
      for (int kb = 0; kb < LG_STAGES; kb++) issue_bglu(kb);
      flag_wait(&g_flag[16 + m_blk], 16);
      fence_proxy_async_all();
      for (int kb = 0; kb < 20; kb++) {
        const int s = kb % LG_STAGES;
        if (kb >= LG_STAGES) {
          mbar_wait(bar2 + 8 * (LG_STAGES + s), ((kb / LG_STAGES) & 1) ^ 1);
          issue_bglu(kb);
        }
        tma_load_2d(sbase + s * GLU_STAGE, &tmH, kb * 32, m_blk * 128, bar2 + 8 * s);
      }
      mbar_wait(barD + 8, 0);
      for (int kb = 0; kb < KC_NST3; kb++) issue_b80(&tmWd64, &tmWd16, bar3, KC_NST3, kb);
      flag_wait(&g_flag[32 + m_blk], 16);
      fence_proxy_async_all();
      for (int kb = 0; kb < 24; kb++) {
        const int s = kb % KC_NST3;
        if (kb >= KC_NST3) {
          mbar_wait(bar3 + 8 * (KC_NST3 + s), ((kb / KC_NST3) & 1) ^ 1);
          issue_b80(&tmWd64, &tmWd16, bar3, KC_NST3, kb);
        }
        tma_load_2d(sbase + s * RG_STAGE_BYTES, &tmHH, kb * 64, m_blk * 128, bar3 + 8 * s);
      }
    }
  } else {
    asm volatile("setmaxnreg.inc.sync.aligned.u32 232;");
    const int wg = __shfl_sync(0xffffffffu, warp >> 2, 0);
    const int wwarp = warp & 3;
    const int g = lane >> 2, c4 = lane & 3;
    const int row0 = m_blk * 128 + wg * 64 + wwarp * 16 + g;
    const bool leader = (tid & 127) == 0;
    const uint32_t stg80_base = sbase + KC_STAGING + wg * 24576;
    const uint32_t stg80 = stg80_base + (wwarp * 16 + g) * 160 + c4 * 4;
    {
      uint32_t res[20];
#pragma unroll
      for (int j = 0; j < 10; j++) {
        res[2 * j] = __ldg(reinterpret_cast<const uint32_t*>(x + (size_t)row0 * DM + n0 + j * 8 + c4 * 2));
        res[2 * j + 1] = __ldg(reinterpret_cast<const uint32_t*>(x + (size_t)(row0 + 8) * DM + n0 + j * 8 + c4 * 2));
      }
      float acc0[32], acc1[8];
#pragma unroll
      for (int i = 0; i < 32; i++) acc0[i] = 0.f;
#pragma unroll
      for (int i = 0; i < 8; i++) acc1[i] = 0.f;
      TS(2, 1);
      if (wg == 0) res_mainloop<10, KC_NST1, 0>(acc0, acc1, sbase, bar1, leader);
      else res_mainloop<10, KC_NST1, 1>(acc0, acc1, sbase, bar1, leader);
      wgmma_wait<0>();
      fence_regs(acc0); fence_regs(acc1);
      release_stage(barD, leader);
      TS(2, 4);
      float sum0 = 0.f, sum1 = 0.f;
#pragma unroll
      for (int j = 0; j < 10; j++) {
        const uint32_t a01 = j < 8 ? pack_bf16(acc0[4 * j], acc0[4 * j + 1]) : pack_bf16(acc1[4 * (j - 8)], acc1[4 * (j - 8) + 1]);
        const uint32_t a23 = j < 8 ? pack_bf16(acc0[4 * j + 2], acc0[4 * j + 3]) : pack_bf16(acc1[4 * (j - 8) + 2], acc1[4 * (j - 8) + 3]);
        res[2 * j] = pack_bf16(bf_lo(res[2 * j]) + bf_lo(a01), bf_hi(res[2 * j]) + bf_hi(a01));
        res[2 * j + 1] = pack_bf16(bf_lo(res[2 * j + 1]) + bf_lo(a23), bf_hi(res[2 * j + 1]) + bf_hi(a23));
        st_shared_b32(stg80 + j * 16, res[2 * j]);
        st_shared_b32(stg80 + 8 * 160 + j * 16, res[2 * j + 1]);
        sum0 += bf_lo(res[2 * j]) + bf_hi(res[2 * j]);
        sum1 += bf_lo(res[2 * j + 1]) + bf_hi(res[2 * j + 1]);
      }
      sum0 += __shfl_xor_sync(0xffffffffu, sum0, 1); sum1 += __shfl_xor_sync(0xffffffffu, sum1, 1);
      sum0 += __shfl_xor_sync(0xffffffffu, sum0, 2); sum1 += __shfl_xor_sync(0xffffffffu, sum1, 2);
      const float mu0 = sum0 * (1.0f / 80.0f), mu1 = sum1 * (1.0f / 80.0f);
      float q0 = 0.f, q1 = 0.f;
#pragma unroll
      for (int j = 0; j < 10; j++) {
        float d;
        d = bf_lo(res[2 * j]) - mu0; q0 = fmaf(d, d, q0);
        d = bf_hi(res[2 * j]) - mu0; q0 = fmaf(d, d, q0);
        d = bf_lo(res[2 * j + 1]) - mu1; q1 = fmaf(d, d, q1);
        d = bf_hi(res[2 * j + 1]) - mu1; q1 = fmaf(d, d, q1);
      }
      q0 += __shfl_xor_sync(0xffffffffu, q0, 1); q1 += __shfl_xor_sync(0xffffffffu, q1, 1);
      q0 += __shfl_xor_sync(0xffffffffu, q0, 2); q1 += __shfl_xor_sync(0xffffffffu, q1, 2);
      if (c4 == 0) {
        g_stats[row0 * 8 + j_blk] = make_float2(mu0, q0);
        g_stats[(row0 + 8) * 8 + j_blk] = make_float2(mu1, q1);
      }
      fence_proxy_async();
      named_bar_sync(1 + wg, 128);
      if (leader) {
        tma_store_2d(&tmHs, stg80_base, n0, m_blk * 128 + wg * 64);
        bulk_commit();
        bulk_wait_all();
        fence_proxy_async_all();
        flag_signal(&g_flag[16 + m_blk]);
      }
      TS(2, 5);
    }
    {
      pdl_wait();
      {
        float* cs_s = reinterpret_cast<float*>(smem_raw + (sbase - smem_u32(smem_raw)) + KC_CS);
        for (int i = tid; i < 384; i += 256) cs_s[i] = g_cs[(i >= 192 ? FF - 192 : 0) + j_blk * 192 + i];
        named_bar_sync(3, 256);
      }
      flag_wait(&g_flag[16 + m_blk], 16);
      float mb[2], iv[2];
#pragma unroll
      for (int h = 0; h < 2; h++) {
        const float4* sp = reinterpret_cast<const float4*>(g_stats + (row0 + 8 * h) * 8);
        const float4 p0 = sp[0], p1 = sp[1], p2 = sp[2], p3 = sp[3];
        const float mean = (((p0.x + p0.z) + (p1.x + p1.z)) + ((p2.x + p2.z) + (p3.x + p3.z))) * 0.125f;
        float m2 = ((p0.y + p0.w) + (p1.y + p1.w)) + ((p2.y + p2.w) + (p3.y + p3.w));
        float dd = 0.f, d;
        d = p0.x - mean; dd = fmaf(d, d, dd); d = p0.z - mean; dd = fmaf(d, d, dd);
        d = p1.x - mean; dd = fmaf(d, d, dd); d = p1.z - mean; dd = fmaf(d, d, dd);
        d = p2.x - mean; dd = fmaf(d, d, dd); d = p2.z - mean; dd = fmaf(d, d, dd);
        d = p3.x - mean; dd = fmaf(d, d, dd); d = p3.z - mean; dd = fmaf(d, d, dd);
        m2 = fmaf(dd, 80.0f, m2);
        const float var_b = bf16_round(m2 * (1.0f / DM));
        const float den = bf16_round(sqrtf(bf16_round(var_b + 1e-5f)));
        iv[h] = __frcp_rn(den);
        mb[h] = bf16_round(mean);
      }
      float accg[96], accu[96];
#pragma unroll
      for (int i = 0; i < 96; i++) { accg[i] = 0.f; accu[i] = 0.f; }
      TS(3, 3);
      if (wg == 0) glu_mainloop<0>(accg, accu, sbase, bar2, leader);
      else glu_mainloop<1>(accg, accu, sbase, bar2, leader);
      wgmma_wait<0>();
      fence_regs(accg); fence_regs(accu);
      release_stage(barD + 8, leader);
      TS(3, 4);
      const uint32_t stg = sbase + KC_STAGING + wg * 24576 + (wwarp * 16 + g) * 128 + c4 * 4;
      const float* csg = reinterpret_cast<const float*>(smem_raw + (sbase - smem_u32(smem_raw)) + KC_CS) + c4 * 2;
      const float nm0 = -mb[0] * iv[0], nm1 = -mb[1] * iv[1];
#pragma unroll
      for (int sl = 0; sl < 3; sl++) {
#pragma unroll
        for (int jj = 0; jj < 8; jj++) {
          const int j = sl * 8 + jj;
          const float2 cg = *reinterpret_cast<const float2*>(csg + j * 8);
          const float2 cu = *reinterpret_cast<const float2*>(csg + 192 + j * 8);
          const float r0 = fmaxf(fmaf(accg[4 * j], iv[0], nm0 * cg.x), 0.f) * fmaf(accu[4 * j], iv[0], nm0 * cu.x);
          const float r1 = fmaxf(fmaf(accg[4 * j + 1], iv[0], nm0 * cg.y), 0.f) * fmaf(accu[4 * j + 1], iv[0], nm0 * cu.y);
          const float r2 = fmaxf(fmaf(accg[4 * j + 2], iv[1], nm1 * cg.x), 0.f) * fmaf(accu[4 * j + 2], iv[1], nm1 * cu.x);
          const float r3 = fmaxf(fmaf(accg[4 * j + 3], iv[1], nm1 * cg.y), 0.f) * fmaf(accu[4 * j + 3], iv[1], nm1 * cu.y);
          const uint32_t a0 = stg + sl * 8192 + ((jj ^ g) << 4);
          st_shared_b32(a0, pack_bf16(r0, r1));
          st_shared_b32(a0 + 1024, pack_bf16(r2, r3));
        }
        fence_proxy_async();
        named_bar_sync(1 + wg, 128);
        if (leader) {
          tma_store_2d(&tmHHs, sbase + KC_STAGING + wg * 24576 + sl * 8192, j_blk * 192 + sl * 64, m_blk * 128 + wg * 64);
          bulk_commit();
        }
      }
      TS(3, 7);
      if (leader) {
        bulk_wait_all();
        TS(3, 8);
        fence_proxy_async_all();
        flag_signal(&g_flag[32 + m_blk]);
      }
      TS(3, 9);
    }
    {
      uint32_t res[20];
#pragma unroll
      for (int j = 0; j < 10; j++) {
        res[2 * j] = *reinterpret_cast<const uint32_t*>(g_h + (size_t)row0 * DM + n0 + j * 8 + c4 * 2);
        res[2 * j + 1] = *reinterpret_cast<const uint32_t*>(g_h + (size_t)(row0 + 8) * DM + n0 + j * 8 + c4 * 2);
      }
      float acc0[32], acc1[8];
#pragma unroll
      for (int i = 0; i < 32; i++) acc0[i] = 0.f;
#pragma unroll
      for (int i = 0; i < 8; i++) acc1[i] = 0.f;
      mbar_wait(bar3, 0);
      TS(4, 3);
      if (wg == 0) res_mainloop<24, KC_NST3, 0>(acc0, acc1, sbase, bar3, leader);
      else res_mainloop<24, KC_NST3, 1>(acc0, acc1, sbase, bar3, leader);
      wgmma_wait<0>();
      fence_regs(acc0); fence_regs(acc1);
      TS(4, 4);
#pragma unroll
      for (int j = 0; j < 10; j++) {
        const uint32_t a01 = j < 8 ? pack_bf16(acc0[4 * j], acc0[4 * j + 1]) : pack_bf16(acc1[4 * (j - 8)], acc1[4 * (j - 8) + 1]);
        const uint32_t a23 = j < 8 ? pack_bf16(acc0[4 * j + 2], acc0[4 * j + 3]) : pack_bf16(acc1[4 * (j - 8) + 2], acc1[4 * (j - 8) + 3]);
        st_shared_b32(stg80 + j * 16, pack_bf16(bf_lo(res[2 * j]) + bf_lo(a01), bf_hi(res[2 * j]) + bf_hi(a01)));
        st_shared_b32(stg80 + 8 * 160 + j * 16, pack_bf16(bf_lo(res[2 * j + 1]) + bf_lo(a23), bf_hi(res[2 * j + 1]) + bf_hi(a23)));
      }
      fence_proxy_async();
      named_bar_sync(1 + wg, 128);
      if (leader) {
        tma_store_2d(&tmOut, stg80_base, n0, m_blk * 128 + wg * 64);
        bulk_commit();
        bulk_wait_read();
      }
      TS(4, 5);
    }
  }
  __syncwarp();
  cluster_sync_relaxed();
  TS(4, 6);
}

constexpr int AT_THREADS = 512;
constexpr int AT_WGS = AT_THREADS / 128;
#define AT_CHUNK_MASK 3
#define AT_STAGGER 0
constexpr int AT_KV_BYTES = IMG_HEAD_ELEMS * 2;
constexpr int AT_SMEM = 2 * AT_KV_BYTES + 256 + 1024;
constexpr int AT_CHUNKS = 8;

__device__ __forceinline__ float exp2_poly(float x) {
  const float u = __saturatef(fmaf(x, 1.0f / 64.0f, 62.0f / 64.0f));
  const float MAGIC = 12582912.0f - 62.0f;
  const float r = fmaf(u, 64.0f, MAGIC);
  const float q = MAGIC - r;
  const float fr = fmaf(u, 64.0f, q);
  float p = fmaf(fr, 0.009570102207362652f, 0.05591785907745361f);
  p = fmaf(p, fr, 0.240247443318367f);
  p = fmaf(p, fr, 0.6931217908859253f);
  p = fmaf(p, fr, 0.9999992847442627f);
  return __uint_as_float(__float_as_uint(p) + (__float_as_uint(r) << 23));
}
#define AT_VARIANT 0
#define AT_POLY_MOD 8
__device__ __forceinline__ bool use_poly(int e) {
  return (e % AT_POLY_MOD) == 1;
}

struct AttnState {
  uint32_t qa0, qa1, qa2, qa3, qa4, qa5;
  float M0, M1;
};

__device__ __forceinline__ bool attn_exp_fast(const float (&s)[32], uint32_t (&p)[16]) {
#pragma unroll
  for (int j = 0; j < 16; j++) {
    const float e0 = use_poly(2 * j) ? exp2_poly(s[2 * j]) : ex2(s[2 * j]);
    const float e1 = use_poly(2 * j + 1) ? exp2_poly(s[2 * j + 1]) : ex2(s[2 * j + 1]);
    p[j] = pack_bf16(e0, e1);
  }
  uint32_t acc_or = 0;
#pragma unroll
  for (int j = 0; j < 16; j++) acc_or |= p[j];
  return __any_sync(0xffffffffu, (acc_or & 0x40004000u) != 0);
}
__device__ __forceinline__ void attn_exp_exact(const float (&s)[32], uint32_t (&p)[16], float (&o)[12], AttnState& st, bool first, int c4) {
  float mx0 = fmaxf(s[0], s[1]), mx1 = fmaxf(s[2], s[3]);
#pragma unroll
  for (int j = 1; j < 8; j++) {
    mx0 = fmaxf(mx0, fmaxf(s[4 * j], s[4 * j + 1]));
    mx1 = fmaxf(mx1, fmaxf(s[4 * j + 2], s[4 * j + 3]));
  }
  mx0 = fmaxf(mx0, __shfl_xor_sync(0xffffffffu, mx0, 1));
  mx1 = fmaxf(mx1, __shfl_xor_sync(0xffffffffu, mx1, 1));
  mx0 = fmaxf(mx0, __shfl_xor_sync(0xffffffffu, mx0, 2));
  mx1 = fmaxf(mx1, __shfl_xor_sync(0xffffffffu, mx1, 2));
  float d0 = mx0 + 7.0f, d1 = mx1 + 7.0f;
  if (!first) { d0 = fmaxf(d0, 0.f); d1 = fmaxf(d1, 0.f); }
  const float T0 = st.M0 + d0, T1 = st.M1 + d1;
  const float h0 = bf16_round(T0), h1 = bf16_round(T1);
  const float i0 = bf16_round(T0 - h0), i1 = bf16_round(T1 - h1);
  const float l0 = bf16_round((T0 - h0) - i0), l1 = bf16_round((T1 - h1) - i1);
  const float N0 = (h0 + i0) + l0, N1 = (h1 + i1) + l1;
  d0 = N0 - st.M0; d1 = N1 - st.M1;
  st.M0 = N0; st.M1 = N1;
  if (c4 == 2) { st.qa4 = pack_bf16(-h0, -i0); st.qa5 = pack_bf16(-h1, -i1); }
  if (c4 == 3) { st.qa4 = pack_bf16(-l0, 0.f); st.qa5 = pack_bf16(-l1, 0.f); }
  if (!first) {
    const float al0 = ex2(-d0), al1 = ex2(-d1);
#pragma unroll
    for (int j = 0; j < 3; j++) {
      o[4 * j] *= al0; o[4 * j + 1] *= al0;
      o[4 * j + 2] *= al1; o[4 * j + 3] *= al1;
    }
  }
#pragma unroll
  for (int j = 0; j < 8; j++) {
    p[2 * j] = pack_bf16(ex2(s[4 * j] - d0), ex2(s[4 * j + 1] - d0));
    p[2 * j + 1] = pack_bf16(ex2(s[4 * j + 2] - d1), ex2(s[4 * j + 3] - d1));
  }
}
__device__ __forceinline__ void attn_step(float (&s)[32], const uint32_t (&pp)[16], uint32_t (&pn)[16], float (&o)[12], AttnState& st,
                                          uint32_t k_addr, uint32_t v_addr_prev, int keep, int c4, int wgdbg = 0, int tdbg = 0) {
  PH(wgdbg, tdbg, 0);
  const uint64_t dk = make_desc(k_addr, 128, 384, 0);
  const uint64_t dv_prev = make_desc(v_addr_prev, 384, 128, 0);
  wgmma_fence();
  wgmma_rs_n64(s, st.qa0, st.qa1, st.qa2, st.qa3, dk, 0);
  wgmma_rs_n64(s, st.qa4, st.qa5, 0u, 0u, dk + 16, 1);
  wgmma_commit();
#pragma unroll
  for (int kk = 0; kk < 4; kk++) wgmma_rs_n24_tb(o, pp[4 * kk], pp[4 * kk + 1], pp[4 * kk + 2], pp[4 * kk + 3], dv_prev + kk * 48, kk == 0 ? keep : 1);
  wgmma_commit();
  wgmma_wait<1>();
  fence_regs(s);
  PH(wgdbg, tdbg, 1);
  const bool redo = attn_exp_fast(s, pn);
  PH(wgdbg, tdbg, 2);
  wgmma_wait<0>();
  fence_regs(o);
  if (redo) attn_exp_exact(s, pn, o, st, false, c4);
}

__global__ void __launch_bounds__(AT_THREADS, 1) attn_kernel(const bf16* __restrict__ wo, const bf16* __restrict__ wgt, const bf16* __restrict__ wup, const bf16* __restrict__ wdn) {
  extern __shared__ uint8_t smem_raw[];
  const uint32_t sbase = (smem_u32(smem_raw) + 1023u) & ~1023u;
  const uint32_t sK = sbase, sV = sbase + AT_KV_BYTES;
  const uint32_t sBar = sV + AT_KV_BYTES;
  const int tid = threadIdx.x, warp = tid >> 5, lane = tid & 31;
  const int head = blockIdx.x >> 2, quarter = blockIdx.x & 3;
  if (blockIdx.x >= 128) {
    pdl_launch();
    const int b = blockIdx.x - 128;
    const bf16* w = (b >> 1) ? wup : wgt;
    const int cgrp = tid % 96, rgrp = tid / 96;
    float acc[8];
#pragma unroll
    for (int i = 0; i < 8; i++) acc[i] = 0.f;
    float* red = reinterpret_cast<float*>(smem_raw);
    if (rgrp < 5) {
      const uint4* src = reinterpret_cast<const uint4*>(w + (size_t)(rgrp * 128) * FF + (b & 1) * 768 + cgrp * 8);
#pragma unroll 8
      for (int r = 0; r < 128; r++) {
        const uint4 v = __ldg(src + (size_t)r * (FF / 8));
        acc[0] += bf_lo(v.x); acc[1] += bf_hi(v.x); acc[2] += bf_lo(v.y); acc[3] += bf_hi(v.y);
        acc[4] += bf_lo(v.z); acc[5] += bf_hi(v.z); acc[6] += bf_lo(v.w); acc[7] += bf_hi(v.w);
      }
#pragma unroll
      for (int i = 0; i < 8; i++) red[rgrp * 768 + cgrp * 8 + i] = acc[i];
    }
    __syncthreads();
    pdl_wait();
    for (int c = tid; c < 768; c += AT_THREADS)
      g_cs[(b >> 1) * FF + (b & 1) * 768 + c] = ((red[c] + red[768 + c]) + (red[1536 + c] + red[2304 + c])) + red[3072 + c];
    if (b == 0 && tid < 16) g_flag[tid] = 0;
    if (b == 0 && tid < 8) g_flag[48 + tid] = 0;
    return;
  }
  TS(1, 0);
  if (tid == 0) {
    for (int i = 0; i < AT_CHUNKS; i++) mbar_init(sBar + 8 * i, 1);
    fence_mbar_init();
  }
  pdl_launch();
  if (tid == 32) {
    prefetch_l2(reinterpret_cast<const uint8_t*>(wo) + blockIdx.x * 6400, 6400);
    prefetch_l2(reinterpret_cast<const uint8_t*>(wgt) + blockIdx.x * 15360, 15360);
    prefetch_l2(reinterpret_cast<const uint8_t*>(wup) + blockIdx.x * 15360, 15360);
    prefetch_l2(reinterpret_cast<const uint8_t*>(wdn) + blockIdx.x * 15360, 15360);
  }
  __syncthreads();
  TS(1, 1);
  pdl_wait();
  TS(1, 2);
  if (tid == 0) {
    const uint8_t* kg = reinterpret_cast<const uint8_t*>(g_img + (size_t)(32 + head) * IMG_HEAD_ELEMS);
    const uint8_t* vg = reinterpret_cast<const uint8_t*>(g_img + (size_t)(64 + head) * IMG_HEAD_ELEMS);
    constexpr int CB = AT_KV_BYTES / AT_CHUNKS;
    for (int i = 0; i < AT_CHUNKS; i++) {
      mbar_expect_tx(sBar + 8 * i, 2 * CB);
      bulk_g2s(sK + i * CB, kg + i * CB, CB, sBar + 8 * i);
      bulk_g2s(sV + i * CB, vg + i * CB, CB, sBar + 8 * i);
    }
  }
  const int wg = warp >> 2, wwarp = warp & 3;
  const int g = lane >> 2, c4 = lane & 3;
  const uint64_t dk_base = make_desc(sK, 128, 384, 0);
  const uint64_t dv_base = make_desc(sV, 384, 128, 0);

#pragma unroll 1
  for (int rep = 0; rep < 8 / AT_WGS; rep++) {
    const int row0 = quarter * 512 + (rep * AT_WGS + wg) * 64 + wwarp * 16 + g;
    AttnState st;
    {
      const bf16* q0 = g_img + (size_t)head * IMG_HEAD_ELEMS + (size_t)(row0 >> 3) * 192 + g * 8 + c4 * 2;
      const bf16* q1 = q0 + 192;
      st.qa0 = *reinterpret_cast<const uint32_t*>(q0);
      st.qa1 = *reinterpret_cast<const uint32_t*>(q1);
      st.qa2 = *reinterpret_cast<const uint32_t*>(q0 + 64);
      st.qa3 = *reinterpret_cast<const uint32_t*>(q1 + 64);
      st.qa4 = *reinterpret_cast<const uint32_t*>(q0 + 128);
      st.qa5 = *reinterpret_cast<const uint32_t*>(q1 + 128);
    }
    float o[12];
    float s[32];
    uint32_t pa[16], pb[16];
    st.M0 = st.M1 = 0.f;
    if (rep == 0) mbar_wait(sBar, 0);
    wgmma_fence();
    wgmma_rs_n64(s, st.qa0, st.qa1, st.qa2, st.qa3, dk_base, 0);
    wgmma_rs_n64(s, st.qa4, st.qa5, 0u, 0u, dk_base + 16, 1);
    wgmma_commit();
    wgmma_wait<0>();
    fence_regs(s);
    attn_exp_exact(s, pa, o, st, true, c4);
    attn_step(s, pa, pb, o, st, sK + 3072, sV, 0, c4);
#pragma unroll 1
    for (int tt = 1; tt < 16; tt++) {
      if (rep == 0 && !(tt & 1)) mbar_wait(sBar + 8 * (tt >> 1), 0);
      attn_step(s, pb, pa, o, st, sK + tt * 6144, sV + tt * 6144 - 3072, 1, c4, wg, rep * 32 + tt * 2);
      attn_step(s, pa, pb, o, st, sK + tt * 6144 + 3072, sV + tt * 6144, 1, c4, wg, rep * 32 + tt * 2 + 1);
    }
    wgmma_fence();
#pragma unroll
    for (int kk = 0; kk < 4; kk++) wgmma_rs_n24_tb(o, pb[4 * kk], pb[4 * kk + 1], pb[4 * kk + 2], pb[4 * kk + 3], dv_base + 31 * 192 + kk * 48, 1);
    wgmma_commit();
    wgmma_wait<0>();
    fence_regs(o);
    TS(1, 3 + rep);
    const float l0 = __shfl_sync(0xffffffffu, o[8], (lane & ~3) | 2);
    const float l1 = __shfl_sync(0xffffffffu, o[10], (lane & ~3) | 2);
    const float i0 = 1.0f / l0, i1 = 1.0f / l1;
    bf16* o0 = g_o + (size_t)row0 * DM + head * DH;
    bf16* o1 = o0 + 8 * DM;
#pragma unroll
    for (int j = 0; j < 3; j++) {
      if (j < 2 || c4 < 2) {
        *reinterpret_cast<uint32_t*>(o0 + j * 8 + c4 * 2) = pack_bf16(o[4 * j] * i0, o[4 * j + 1] * i0);
        *reinterpret_cast<uint32_t*>(o1 + j * 8 + c4 * 2) = pack_bf16(o[4 * j + 2] * i1, o[4 * j + 3] * i1);
      }
    }
  }
}

typedef CUresult (*EncodeTiledFn)(CUtensorMap*, CUtensorMapDataType, cuuint32_t, void*, const cuuint64_t*, const cuuint64_t*,
                                  const cuuint32_t*, const cuuint32_t*, CUtensorMapInterleave, CUtensorMapSwizzle,
                                  CUtensorMapL2promotion, CUtensorMapFloatOOBfill);

static void make_map(EncodeTiledFn fn, CUtensorMap* tm, const void* ptr, uint64_t rows, uint64_t cols, uint32_t box_rows,
                     uint32_t box_cols, CUtensorMapSwizzle sw) {
  cuuint64_t dims[2] = {cols, rows};
  cuuint64_t strides[1] = {cols * 2};
  cuuint32_t box[2] = {box_cols, box_rows};
  cuuint32_t es[2] = {1, 1};
  fn(tm, CU_TENSOR_MAP_DATA_TYPE_BFLOAT16, 2, const_cast<void*>(ptr), dims, strides, box, es, CU_TENSOR_MAP_INTERLEAVE_NONE, sw,
     CU_TENSOR_MAP_L2_PROMOTION_L2_256B, CU_TENSOR_MAP_FLOAT_OOB_FILL_NONE);
}

template <typename... KArgs, typename... Args>
static void launch(void (*kern)(KArgs...), int grid, int block, int smem, int cluster, bool pdl, Args... args) {
  cudaLaunchConfig_t cfg = {};
  cfg.gridDim = dim3(grid);
  cfg.blockDim = dim3(block);
  cfg.dynamicSmemBytes = smem;
  cfg.stream = cudaStreamPerThread;
  cudaLaunchAttribute at[2];
  int n = 0;
  if (cluster > 1) {
    at[n].id = cudaLaunchAttributeClusterDimension;
    at[n].val.clusterDim.x = cluster; at[n].val.clusterDim.y = 1; at[n].val.clusterDim.z = 1;
    n++;
  }
  if (pdl) {
    at[n].id = cudaLaunchAttributeProgrammaticStreamSerialization;
    at[n].val.programmaticStreamSerializationAllowed = 1;
    n++;
  }
  cfg.attrs = at;
  cfg.numAttrs = n;
  cudaLaunchKernelEx(&cfg, kern, KArgs(args)...);
}

extern "C" void kernel_launch(void* const* d_in, const int* in_sizes, int n_in, void* d_out, int out_size) {
  const bf16* x = (const bf16*)d_in[0];
  const bf16* wqkv = (const bf16*)d_in[1];
  const bf16* wo = (const bf16*)d_in[2];
  const bf16* wg = (const bf16*)d_in[4];
  const bf16* wu = (const bf16*)d_in[5];
  const bf16* wd = (const bf16*)d_in[6];
  bf16* out = (bf16*)d_out;

  static EncodeTiledFn enc = nullptr;
  static void *p_o = nullptr, *p_h = nullptr, *p_hh = nullptr;
  if (!enc) {
    void* fn = nullptr;
    cudaDriverEntryPointQueryResult qr;
    cudaGetDriverEntryPoint("cuTensorMapEncodeTiled", &fn, cudaEnableDefault, &qr);
    enc = (EncodeTiledFn)fn;
    cudaGetSymbolAddress(&p_o, g_o);
    cudaGetSymbolAddress(&p_h, g_h);
    cudaGetSymbolAddress(&p_hh, g_hh);
    cudaFuncSetAttribute(qkv_kernel, cudaFuncAttributeMaxDynamicSharedMemorySize, KA_SMEM);
    cudaFuncSetAttribute(mlp_kernel, cudaFuncAttributeMaxDynamicSharedMemorySize, KC_SMEM);
    cudaFuncSetAttribute(attn_kernel, cudaFuncAttributeMaxDynamicSharedMemorySize, AT_SMEM);
  }
  CUtensorMap tm_wqkv, tm_wg, tm_wu, tm_wo64, tm_wo16, tm_wd64, tm_wd16, tm_o, tm_h, tm_hh, tm_hhs, tm_xn, tm_hs, tm_out;
  make_map(enc, &tm_wqkv, wqkv, DM, 3 * DM, 32, 64, CU_TENSOR_MAP_SWIZZLE_128B);
  make_map(enc, &tm_wg, wg, DM, FF, 32, 64, CU_TENSOR_MAP_SWIZZLE_128B);
  make_map(enc, &tm_wu, wu, DM, FF, 32, 64, CU_TENSOR_MAP_SWIZZLE_128B);
  make_map(enc, &tm_wo64, wo, DM, DM, 32, 64, CU_TENSOR_MAP_SWIZZLE_128B);
  make_map(enc, &tm_wo16, wo, DM, DM, 32, 16, CU_TENSOR_MAP_SWIZZLE_32B);
  make_map(enc, &tm_wd64, wd, FF, DM, 32, 64, CU_TENSOR_MAP_SWIZZLE_128B);
  make_map(enc, &tm_wd16, wd, FF, DM, 32, 16, CU_TENSOR_MAP_SWIZZLE_32B);
  make_map(enc, &tm_o, p_o, SEQ, DM, 128, 64, CU_TENSOR_MAP_SWIZZLE_128B);
  make_map(enc, &tm_h, p_h, SEQ, DM, 128, 32, CU_TENSOR_MAP_SWIZZLE_64B);
  make_map(enc, &tm_hh, p_hh, SEQ, FF, 128, 64, CU_TENSOR_MAP_SWIZZLE_128B);
  make_map(enc, &tm_hhs, p_hh, SEQ, FF, 64, 64, CU_TENSOR_MAP_SWIZZLE_128B);
  make_map(enc, &tm_xn, x, SEQ, DM, 128, 32, CU_TENSOR_MAP_SWIZZLE_64B);
  make_map(enc, &tm_hs, p_h, SEQ, DM, 64, 80, CU_TENSOR_MAP_SWIZZLE_NONE);
  make_map(enc, &tm_out, out, SEQ, DM, 64, 80, CU_TENSOR_MAP_SWIZZLE_NONE);

  launch(qkv_kernel, 128, GT, KA_SMEM, 2, false, tm_xn, tm_wqkv, x, wqkv);
  launch(attn_kernel, 132, AT_THREADS, AT_SMEM, 1, true, wo, wg, wu, wd);
  launch(mlp_kernel, 128, GT, KC_SMEM, 2, true, tm_o, tm_wo64, tm_wo16, tm_h, tm_wg, tm_wu, tm_hhs, tm_hh, tm_wd64, tm_wd16, tm_hs, tm_out, x);
}
```

```cpp
#include <cuda_runtime.h>
#include <cuda_bf16.h>
#include <cuda.h>
#include <stdint.h>

typedef __nv_bfloat16 bf16;
#define FLAGV 0

constexpr int SEQ = 2048, DM = 640, NH = 32, DH = 20, FF = 1536;
constexpr float ATT_SCALE_LOG2E = 0.22360679774997896f * 1.4426950408889634f;
constexpr int IMG_HEAD_ELEMS = (SEQ / 8) * 192;

__device__ __align__(1024) bf16 g_img[3 * NH * IMG_HEAD_ELEMS];
__device__ __align__(1024) bf16 g_o[SEQ * DM];
__device__ __align__(1024) bf16 g_h[SEQ * DM];
__device__ float2 g_stats[SEQ * 8];
__device__ float g_cs[2 * FF];
__device__ int g_flag[4 * 16];
__device__ float2 g_rs[SEQ];
__device__ float g_csp[16 * 3 * DM];
__device__ __align__(1024) bf16 g_hh[SEQ * FF];

#define TS(k, i)
#define PH(w, t, i)
__device__ __forceinline__ uint32_t smem_u32(const void* p) { return (uint32_t)__cvta_generic_to_shared(p); }
__device__ __forceinline__ void mbar_init(uint32_t bar, uint32_t cnt) {
  asm volatile("mbarrier.init.shared::cta.b64 [%0], %1;" ::"r"(bar), "r"(cnt) : "memory");
}
__device__ __forceinline__ void mbar_expect_tx(uint32_t bar, uint32_t bytes) {
  asm volatile("mbarrier.arrive.expect_tx.shared::cta.b64 _, [%0], %1;" ::"r"(bar), "r"(bytes) : "memory");
}
__device__ __forceinline__ void mbar_arrive(uint32_t bar) {
  asm volatile("mbarrier.arrive.shared::cta.b64 _, [%0];" ::"r"(bar) : "memory");
}
__device__ __forceinline__ void mbar_arrive_cluster(uint32_t bar, uint32_t cta) {
  asm volatile(
      "{\n.reg .b32 r;\nmapa.shared::cluster.u32 r, %0, %1;\n"
      "mbarrier.arrive.shared::cluster.b64 _, [r];\n}\n" ::"r"(bar), "r"(cta)
      : "memory");
}
__device__ __forceinline__ void mbar_wait(uint32_t bar, uint32_t parity) {
  asm volatile(
      "{\n.reg .pred p;\nLAB_WAIT:\n"
      "mbarrier.try_wait.parity.shared::cta.b64 p, [%0], %1;\n"
      "@p bra DONE;\nbra LAB_WAIT;\nDONE:\n}\n" ::"r"(bar), "r"(parity)
      : "memory");
}
__device__ __forceinline__ void mbar_wait_cluster(uint32_t bar, uint32_t parity) {
  asm volatile(
      "{\n.reg .pred p;\nLAB_WAIT:\n"
      "mbarrier.try_wait.parity.acquire.cluster.shared::cta.b64 p, [%0], %1;\n"
      "@p bra DONE;\nbra LAB_WAIT;\nDONE:\n}\n" ::"r"(bar), "r"(parity)
      : "memory");
}
__device__ __forceinline__ void fence_mbar_init() { asm volatile("fence.mbarrier_init.release.cluster;" ::: "memory"); }
__device__ __forceinline__ void fence_proxy_async() { asm volatile("fence.proxy.async.shared::cta;" ::: "memory"); }
__device__ __forceinline__ void cluster_sync_all() {
  asm volatile("barrier.cluster.arrive.release.aligned;\nbarrier.cluster.wait.acquire.aligned;" ::: "memory");
}
__device__ __forceinline__ void cluster_sync_relaxed() {
  asm volatile("barrier.cluster.arrive.relaxed.aligned;\nbarrier.cluster.wait.aligned;" ::: "memory");
}
__device__ __forceinline__ void named_bar_sync(int id, int n) { asm volatile("bar.sync %0, %1;" ::"r"(id), "r"(n) : "memory"); }
__device__ __forceinline__ bool wg_any(bool pred, int id) {
  uint32_t r;
  asm volatile("{\n.reg .pred p, q;\nsetp.ne.u32 p, %1, 0;\nbar.red.or.pred q, %2, 128, p;\nselp.u32 %0, 1, 0, q;\n}\n" : "=r"(r) : "r"((uint32_t)pred), "r"(id) : "memory");
  return r != 0;
}
__device__ __forceinline__ void fence_proxy_async_all() { asm volatile("fence.proxy.async;" ::: "memory"); }
__device__ __forceinline__ void flag_signal(int* f) {
  __threadfence();
  atomicAdd(f, 1);
}
__device__ __forceinline__ void flag_wait(const int* f, int target) {
  int v;
  unsigned spins = 0;
  do {
    asm volatile("ld.acquire.gpu.global.s32 %0, [%1];" : "=r"(v) : "l"(f) : "memory");
    if (++spins > (1u << 24)) __trap();
  } while (v < target);
}
__device__ __forceinline__ void pdl_launch() { asm volatile("griddepcontrol.launch_dependents;" ::: "memory"); }
__device__ __forceinline__ void pdl_wait() { asm volatile("griddepcontrol.wait;" ::: "memory"); }

__device__ __forceinline__ void tma_load_2d(uint32_t dst, const CUtensorMap* tm, int c0, int c1, uint32_t bar) {
  asm volatile(
      "cp.async.bulk.tensor.2d.shared::cluster.global.mbarrier::complete_tx::bytes [%0], [%1, {%3, %4}], [%2];" ::"r"(dst),
      "l"((uint64_t)tm), "r"(bar), "r"(c0), "r"(c1)
      : "memory");
}
__device__ __forceinline__ void tma_load_2d_mc(uint32_t dst, const CUtensorMap* tm, int c0, int c1, uint32_t bar, uint16_t mask) {
  asm volatile(
      "cp.async.bulk.tensor.2d.shared::cluster.global.mbarrier::complete_tx::bytes.multicast::cluster [%0], [%1, {%3, %4}], [%2], %5;" ::"r"(dst),
      "l"((uint64_t)tm), "r"(bar), "r"(c0), "r"(c1), "h"(mask)
      : "memory");
}
__device__ __forceinline__ void bulk_g2s(uint32_t dst, const void* src, uint32_t bytes, uint32_t bar) {
  asm volatile("cp.async.bulk.shared::cluster.global.mbarrier::complete_tx::bytes [%0], [%1], %2, [%3];" ::"r"(dst), "l"(src),
               "r"(bytes), "r"(bar)
               : "memory");
}
__device__ __forceinline__ void bulk_s2g(void* dst, uint32_t src, uint32_t bytes) {
  asm volatile("cp.async.bulk.global.shared::cta.bulk_group [%0], [%1], %2;" ::"l"(dst), "r"(src), "r"(bytes) : "memory");
}
__device__ __forceinline__ void tma_store_2d(const CUtensorMap* tm, uint32_t src, int c0, int c1) {
  asm volatile("cp.async.bulk.tensor.2d.global.shared::cta.bulk_group [%0, {%2, %3}], [%1];" ::"l"((uint64_t)tm), "r"(src), "r"(c0), "r"(c1) : "memory");
}
__device__ __forceinline__ void bulk_commit() { asm volatile("cp.async.bulk.commit_group;" ::: "memory"); }
__device__ __forceinline__ void bulk_wait_read() { asm volatile("cp.async.bulk.wait_group.read 0;" ::: "memory"); }
__device__ __forceinline__ void prefetch_l2(const void* p, uint32_t bytes) {
  asm volatile("cp.async.bulk.prefetch.L2.global [%0], %1;" ::"l"(p), "r"(bytes) : "memory");
}
__device__ __forceinline__ void bulk_wait_all() { asm volatile("cp.async.bulk.wait_group 0;" ::: "memory"); }
__device__ __forceinline__ void st_shared_b32(uint32_t addr, uint32_t v) { asm volatile("st.shared.b32 [%0], %1;" ::"r"(addr), "r"(v) : "memory"); }
__device__ __forceinline__ void st_shared_v2(uint32_t addr, uint32_t a, uint32_t b) { asm volatile("st.shared.v2.b32 [%0], {%1, %2};" ::"r"(addr), "r"(a), "r"(b) : "memory"); }
__device__ __forceinline__ void prefetch_tmap(const CUtensorMap* tm) {
  asm volatile("prefetch.tensormap [%0];" ::"l"((uint64_t)tm) : "memory");
}
__device__ __forceinline__ void wgmma_fence() { asm volatile("wgmma.fence.sync.aligned;" ::: "memory"); }
__device__ __forceinline__ void wgmma_commit() { asm volatile("wgmma.commit_group.sync.aligned;" ::: "memory"); }
template <int N>
__device__ __forceinline__ void wgmma_wait() { asm volatile("wgmma.wait_group.sync.aligned %0;" ::"n"(N) : "memory"); }

template <int N>
__device__ __forceinline__ void fence_regs(float (&r)[N]) {
#pragma unroll
  for (int i = 0; i < N; i++) asm volatile("" : "+f"(r[i])::"memory");
}
template <int N>
__device__ __forceinline__ void fence_regs(uint32_t (&r)[N]) {
#pragma unroll
  for (int i = 0; i < N; i++) asm volatile("" : "+r"(r[i])::"memory");
}
__device__ __forceinline__ uint64_t make_desc(uint32_t addr, uint32_t lbo, uint32_t sbo, uint32_t layout) {
  return (uint64_t)((addr & 0x3FFFF) >> 4) | ((uint64_t)((lbo & 0x3FFFF) >> 4) << 16) | ((uint64_t)((sbo & 0x3FFFF) >> 4) << 32) |
         ((uint64_t)layout << 62);
}
__device__ __forceinline__ uint32_t pack_bf16(float lo, float hi) {
  uint32_t r;
  asm("cvt.rn.bf16x2.f32 %0, %1, %2;" : "=r"(r) : "f"(hi), "f"(lo));
  return r;
}
__device__ __forceinline__ float bf16_round(float x) { return __bfloat162float(__float2bfloat16_rn(x)); }
__device__ __forceinline__ float bf_lo(uint32_t u) { return __uint_as_float(u << 16); }
__device__ __forceinline__ float bf_hi(uint32_t u) { return __uint_as_float(u & 0xffff0000u); }
__device__ __forceinline__ float ex2(float x) {
  float y;
  asm("ex2.approx.ftz.f32 %0, %1;" : "=f"(y) : "f"(x));
  return y;
}

__device__ __forceinline__ void wgmma_ss_n240_tb(float (&d)[120], uint64_t descA, uint64_t descB, int scaleD) {
  asm volatile("{\n.reg .pred p;\nsetp.ne.b32 p, %122, 0;\n"
    "wgmma.mma_async.sync.aligned.m64n240k16.f32.bf16.bf16 {%0, %1, %2, %3, %4, %5, %6, %7, %8, %9, %10, %11, %12, %13, %14, %15, %16, %17, %18, %19, %20, %21, %22, %23, %24, %25, %26, %27, %28, %29, %30, %31, %32, %33, %34, %35, %36, %37, %38, %39, %40, %41, %42, %43, %44, %45, %46, %47, %48, %49, %50, %51, %52, %53, %54, %55, %56, %57, %58, %59, %60, %61, %62, %63, %64, %65, %66, %67, %68, %69, %70, %71, %72, %73, %74, %75, %76, %77, %78, %79, %80, %81, %82, %83, %84, %85, %86, %87, %88, %89, %90, %91, %92, %93, %94, %95, %96, %97, %98, %99, %100, %101, %102, %103, %104, %105, %106, %107, %108, %109, %110, %111, %112, %113, %114, %115, %116, %117, %118, %119}, %120, %121, p, 1, 1, 0, 1;\n}\n"
    : "+f"(d[0]), "+f"(d[1]), "+f"(d[2]), "+f"(d[3]), "+f"(d[4]), "+f"(d[5]), "+f"(d[6]), "+f"(d[7]), "+f"(d[8]), "+f"(d[9]), "+f"(d[10]), "+f"(d[11]), "+f"(d[12]), "+f"(d[13]), "+f"(d[14]), "+f"(d[15]), "+f"(d[16]), "+f"(d[17]), "+f"(d[18]), "+f"(d[19]), "+f"(d[20]), "+f"(d[21]), "+f"(d[22]), "+f"(d[23]), "+f"(d[24]), "+f"(d[25]), "+f"(d[26]), "+f"(d[27]), "+f"(d[28]), "+f"(d[29]), "+f"(d[30]), "+f"(d[31]), "+f"(d[32]), "+f"(d[33]), "+f"(d[34]), "+f"(d[35]), "+f"(d[36]), "+f"(d[37]), "+f"(d[38]), "+f"(d[39]), "+f"(d[40]), "+f"(d[41]), "+f"(d[42]), "+f"(d[43]), "+f"(d[44]), "+f"(d[45]), "+f"(d[46]), "+f"(d[47]), "+f"(d[48]), "+f"(d[49]), "+f"(d[50]), "+f"(d[51]), "+f"(d[52]), "+f"(d[53]), "+f"(d[54]), "+f"(d[55]), "+f"(d[56]), "+f"(d[57]), "+f"(d[58]), "+f"(d[59]), "+f"(d[60]), "+f"(d[61]), "+f"(d[62]), "+f"(d[63]), "+f"(d[64]), "+f"(d[65]), "+f"(d[66]), "+f"(d[67]), "+f"(d[68]), "+f"(d[69]), "+f"(d[70]), "+f"(d[71]), "+f"(d[72]), "+f"(d[73]), "+f"(d[74]), "+f"(d[75]), "+f"(d[76]), "+f"(d[77]), "+f"(d[78]), "+f"(d[79]), "+f"(d[80]), "+f"(d[81]), "+f"(d[82]), "+f"(d[83]), "+f"(d[84]), "+f"(d[85]), "+f"(d[86]), "+f"(d[87]), "+f"(d[88]), "+f"(d[89]), "+f"(d[90]), "+f"(d[91]), "+f"(d[92]), "+f"(d[93]), "+f"(d[94]), "+f"(d[95]), "+f"(d[96]), "+f"(d[97]), "+f"(d[98]), "+f"(d[99]), "+f"(d[100]), "+f"(d[101]), "+f"(d[102]), "+f"(d[103]), "+f"(d[104]), "+f"(d[105]), "+f"(d[106]), "+f"(d[107]), "+f"(d[108]), "+f"(d[109]), "+f"(d[110]), "+f"(d[111]), "+f"(d[112]), "+f"(d[113]), "+f"(d[114]), "+f"(d[115]), "+f"(d[116]), "+f"(d[117]), "+f"(d[118]), "+f"(d[119])
    : "l"(descA), "l"(descB), "r"(scaleD));
}
__device__ __forceinline__ void wgmma_ss_n192_tb(float (&d)[96], uint64_t descA, uint64_t descB, int scaleD) {
  asm volatile("{\n.reg .pred p;\nsetp.ne.b32 p, %98, 0;\n"
    "wgmma.mma_async.sync.aligned.m64n192k16.f32.bf16.bf16 {%0, %1, %2, %3, %4, %5, %6, %7, %8, %9, %10, %11, %12, %13, %14, %15, %16, %17, %18, %19, %20, %21, %22, %23, %24, %25, %26, %27, %28, %29, %30, %31, %32, %33, %34, %35, %36, %37, %38, %39, %40, %41, %42, %43, %44, %45, %46, %47, %48, %49, %50, %51, %52, %53, %54, %55, %56, %57, %58, %59, %60, %61, %62, %63, %64, %65, %66, %67, %68, %69, %70, %71, %72, %73, %74, %75, %76, %77, %78, %79, %80, %81, %82, %83, %84, %85, %86, %87, %88, %89, %90, %91, %92, %93, %94, %95}, %96, %97, p, 1, 1, 0, 1;\n}\n"
    : "+f"(d[0]), "+f"(d[1]), "+f"(d[2]), "+f"(d[3]), "+f"(d[4]), "+f"(d[5]), "+f"(d[6]), "+f"(d[7]), "+f"(d[8]), "+f"(d[9]), "+f"(d[10]), "+f"(d[11]), "+f"(d[12]), "+f"(d[13]), "+f"(d[14]), "+f"(d[15]), "+f"(d[16]), "+f"(d[17]), "+f"(d[18]), "+f"(d[19]), "+f"(d[20]), "+f"(d[21]), "+f"(d[22]), "+f"(d[23]), "+f"(d[24]), "+f"(d[25]), "+f"(d[26]), "+f"(d[27]), "+f"(d[28]), "+f"(d[29]), "+f"(d[30]), "+f"(d[31]), "+f"(d[32]), "+f"(d[33]), "+f"(d[34]), "+f"(d[35]), "+f"(d[36]), "+f"(d[37]), "+f"(d[38]), "+f"(d[39]), "+f"(d[40]), "+f"(d[41]), "+f"(d[42]), "+f"(d[43]), "+f"(d[44]), "+f"(d[45]), "+f"(d[46]), "+f"(d[47]), "+f"(d[48]), "+f"(d[49]), "+f"(d[50]), "+f"(d[51]), "+f"(d[52]), "+f"(d[53]), "+f"(d[54]), "+f"(d[55]), "+f"(d[56]), "+f"(d[57]), "+f"(d[58]), "+f"(d[59]), "+f"(d[60]), "+f"(d[61]), "+f"(d[62]), "+f"(d[63]), "+f"(d[64]), "+f"(d[65]), "+f"(d[66]), "+f"(d[67]), "+f"(d[68]), "+f"(d[69]), "+f"(d[70]), "+f"(d[71]), "+f"(d[72]), "+f"(d[73]), "+f"(d[74]), "+f"(d[75]), "+f"(d[76]), "+f"(d[77]), "+f"(d[78]), "+f"(d[79]), "+f"(d[80]), "+f"(d[81]), "+f"(d[82]), "+f"(d[83]), "+f"(d[84]), "+f"(d[85]), "+f"(d[86]), "+f"(d[87]), "+f"(d[88]), "+f"(d[89]), "+f"(d[90]), "+f"(d[91]), "+f"(d[92]), "+f"(d[93]), "+f"(d[94]), "+f"(d[95])
    : "l"(descA), "l"(descB), "r"(scaleD));
}
__device__ __forceinline__ void wgmma_ss_n64_tb(float (&d)[32], uint64_t descA, uint64_t descB, int scaleD) {
  asm volatile("{\n.reg .pred p;\nsetp.ne.b32 p, %34, 0;\n"
    "wgmma.mma_async.sync.aligned.m64n64k16.f32.bf16.bf16 {%0, %1, %2, %3, %4, %5, %6, %7, %8, %9, %10, %11, %12, %13, %14, %15, %16, %17, %18, %19, %20, %21, %22, %23, %24, %25, %26, %27, %28, %29, %30, %31}, %32, %33, p, 1, 1, 0, 1;\n}\n"
    : "+f"(d[0]), "+f"(d[1]), "+f"(d[2]), "+f"(d[3]), "+f"(d[4]), "+f"(d[5]), "+f"(d[6]), "+f"(d[7]), "+f"(d[8]), "+f"(d[9]), "+f"(d[10]), "+f"(d[11]), "+f"(d[12]), "+f"(d[13]), "+f"(d[14]), "+f"(d[15]), "+f"(d[16]), "+f"(d[17]), "+f"(d[18]), "+f"(d[19]), "+f"(d[20]), "+f"(d[21]), "+f"(d[22]), "+f"(d[23]), "+f"(d[24]), "+f"(d[25]), "+f"(d[26]), "+f"(d[27]), "+f"(d[28]), "+f"(d[29]), "+f"(d[30]), "+f"(d[31])
    : "l"(descA), "l"(descB), "r"(scaleD));
}
__device__ __forceinline__ void wgmma_ss_n16_tb(float (&d)[8], uint64_t descA, uint64_t descB, int scaleD) {
  asm volatile("{\n.reg .pred p;\nsetp.ne.b32 p, %10, 0;\n"
    "wgmma.mma_async.sync.aligned.m64n16k16.f32.bf16.bf16 {%0, %1, %2, %3, %4, %5, %6, %7}, %8, %9, p, 1, 1, 0, 1;\n}\n"
    : "+f"(d[0]), "+f"(d[1]), "+f"(d[2]), "+f"(d[3]), "+f"(d[4]), "+f"(d[5]), "+f"(d[6]), "+f"(d[7])
    : "l"(descA), "l"(descB), "r"(scaleD));
}
__device__ __forceinline__ void wgmma_rs_n128(float (&d)[64], uint32_t a0, uint32_t a1, uint32_t a2, uint32_t a3, uint64_t descB, int scaleD) {
  asm volatile("{\n.reg .pred p;\nsetp.ne.b32 p, %69, 0;\n"
    "wgmma.mma_async.sync.aligned.m64n128k16.f32.bf16.bf16 {%0, %1, %2, %3, %4, %5, %6, %7, %8, %9, %10, %11, %12, %13, %14, %15, %16, %17, %18, %19, %20, %21, %22, %23, %24, %25, %26, %27, %28, %29, %30, %31, %32, %33, %34, %35, %36, %37, %38, %39, %40, %41, %42, %43, %44, %45, %46, %47, %48, %49, %50, %51, %52, %53, %54, %55, %56, %57, %58, %59, %60, %61, %62, %63}, {%64, %65, %66, %67}, %68, p, 1, 1, 0;\n}\n"
    : "+f"(d[0]), "+f"(d[1]), "+f"(d[2]), "+f"(d[3]), "+f"(d[4]), "+f"(d[5]), "+f"(d[6]), "+f"(d[7]), "+f"(d[8]), "+f"(d[9]), "+f"(d[10]), "+f"(d[11]), "+f"(d[12]), "+f"(d[13]), "+f"(d[14]), "+f"(d[15]), "+f"(d[16]), "+f"(d[17]), "+f"(d[18]), "+f"(d[19]), "+f"(d[20]), "+f"(d[21]), "+f"(d[22]), "+f"(d[23]), "+f"(d[24]), "+f"(d[25]), "+f"(d[26]), "+f"(d[27]), "+f"(d[28]), "+f"(d[29]), "+f"(d[30]), "+f"(d[31]), "+f"(d[32]), "+f"(d[33]), "+f"(d[34]), "+f"(d[35]), "+f"(d[36]), "+f"(d[37]), "+f"(d[38]), "+f"(d[39]), "+f"(d[40]), "+f"(d[41]), "+f"(d[42]), "+f"(d[43]), "+f"(d[44]), "+f"(d[45]), "+f"(d[46]), "+f"(d[47]), "+f"(d[48]), "+f"(d[49]), "+f"(d[50]), "+f"(d[51]), "+f"(d[52]), "+f"(d[53]), "+f"(d[54]), "+f"(d[55]), "+f"(d[56]), "+f"(d[57]), "+f"(d[58]), "+f"(d[59]), "+f"(d[60]), "+f"(d[61]), "+f"(d[62]), "+f"(d[63])
    : "r"(a0), "r"(a1), "r"(a2), "r"(a3), "l"(descB), "r"(scaleD));
}
__device__ __forceinline__ void wgmma_rs_n64(float (&d)[32], uint32_t a0, uint32_t a1, uint32_t a2, uint32_t a3, uint64_t descB, int scaleD) {
  asm volatile("{\n.reg .pred p;\nsetp.ne.b32 p, %37, 0;\n"
    "wgmma.mma_async.sync.aligned.m64n64k16.f32.bf16.bf16 {%0, %1, %2, %3, %4, %5, %6, %7, %8, %9, %10, %11, %12, %13, %14, %15, %16, %17, %18, %19, %20, %21, %22, %23, %24, %25, %26, %27, %28, %29, %30, %31}, {%32, %33, %34, %35}, %36, p, 1, 1, 0;\n}\n"
    : "+f"(d[0]), "+f"(d[1]), "+f"(d[2]), "+f"(d[3]), "+f"(d[4]), "+f"(d[5]), "+f"(d[6]), "+f"(d[7]), "+f"(d[8]), "+f"(d[9]), "+f"(d[10]), "+f"(d[11]), "+f"(d[12]), "+f"(d[13]), "+f"(d[14]), "+f"(d[15]), "+f"(d[16]), "+f"(d[17]), "+f"(d[18]), "+f"(d[19]), "+f"(d[20]), "+f"(d[21]), "+f"(d[22]), "+f"(d[23]), "+f"(d[24]), "+f"(d[25]), "+f"(d[26]), "+f"(d[27]), "+f"(d[28]), "+f"(d[29]), "+f"(d[30]), "+f"(d[31])
    : "r"(a0), "r"(a1), "r"(a2), "r"(a3), "l"(descB), "r"(scaleD));
}
__device__ __forceinline__ void wgmma_rs_n24_tb(float (&d)[12], uint32_t a0, uint32_t a1, uint32_t a2, uint32_t a3, uint64_t descB, int scaleD) {
  asm volatile("{\n.reg .pred p;\nsetp.ne.b32 p, %17, 0;\n"
    "wgmma.mma_async.sync.aligned.m64n24k16.f32.bf16.bf16 {%0, %1, %2, %3, %4, %5, %6, %7, %8, %9, %10, %11}, {%12, %13, %14, %15}, %16, p, 1, 1, 1;\n}\n"
    : "+f"(d[0]), "+f"(d[1]), "+f"(d[2]), "+f"(d[3]), "+f"(d[4]), "+f"(d[5]), "+f"(d[6]), "+f"(d[7]), "+f"(d[8]), "+f"(d[9]), "+f"(d[10]), "+f"(d[11])
    : "r"(a0), "r"(a1), "r"(a2), "r"(a3), "l"(descB), "r"(scaleD));
}

constexpr int GT = 384;

__device__ __forceinline__ void release_stage(uint32_t bar, bool leader) {
  if (leader) {
    mbar_arrive_cluster(bar, 0);
    mbar_arrive_cluster(bar, 1);
  }
}

__device__ __forceinline__ float2 ln_row_stats(const bf16* __restrict__ xin, int l16) {
  const uint4* src = reinterpret_cast<const uint4*>(xin);
  uint4 v[5];
#pragma unroll
  for (int j = 0; j < 5; j++) v[j] = __ldg(src + j * 16 + l16);
  float s0 = 0.f, s1 = 0.f, s2 = 0.f, s3 = 0.f;
#pragma unroll
  for (int j = 0; j < 5; j++) {
    s0 += bf_lo(v[j].x) + bf_hi(v[j].x);
    s1 += bf_lo(v[j].y) + bf_hi(v[j].y);
    s2 += bf_lo(v[j].z) + bf_hi(v[j].z);
    s3 += bf_lo(v[j].w) + bf_hi(v[j].w);
  }
  float mean = (s0 + s1) + (s2 + s3);
#pragma unroll
  for (int o = 1; o < 16; o <<= 1) mean += __shfl_xor_sync(0xffffffffu, mean, o);
  mean *= (1.0f / DM);
  s0 = s1 = s2 = s3 = 0.f;
#pragma unroll
  for (int j = 0; j < 5; j++) {
    float d;
    d = bf_lo(v[j].x) - mean; s0 = fmaf(d, d, s0);
    d = bf_hi(v[j].x) - mean; s1 = fmaf(d, d, s1);
    d = bf_lo(v[j].y) - mean; s2 = fmaf(d, d, s2);
    d = bf_hi(v[j].y) - mean; s3 = fmaf(d, d, s3);
    d = bf_lo(v[j].z) - mean; s0 = fmaf(d, d, s0);
    d = bf_hi(v[j].z) - mean; s1 = fmaf(d, d, s1);
    d = bf_lo(v[j].w) - mean; s2 = fmaf(d, d, s2);
    d = bf_hi(v[j].w) - mean; s3 = fmaf(d, d, s3);
  }
  float sq = (s0 + s1) + (s2 + s3);
#pragma unroll
  for (int o = 1; o < 16; o <<= 1) sq += __shfl_xor_sync(0xffffffffu, sq, o);
  const float var_b = bf16_round(sq * (1.0f / DM));
  const float den = bf16_round(sqrtf(bf16_round(var_b + 1e-5f)));
  return make_float2(bf16_round(mean), __frcp_rn(den));
}

constexpr int LG_STAGES = 5;
constexpr int QKV_STAGE = 8192 + 4 * 4096;
constexpr int GLU_STAGE = 8192 + 6 * 4096;

template <int WG>
__device__ __forceinline__ void qkv_mainloop(float (&acc)[120], uint32_t sbase, uint32_t sBar, bool leader) {
  constexpr int STAGE_BYTES = QKV_STAGE, NST = LG_STAGES;
  const uint64_t da_base = make_desc(sbase + WG * 4096, 16, 512, 2);
  const uint64_t db_base = make_desc(sbase + 8192, 4096, 1024, 1);
#pragma unroll 1
  for (int r = 0; r < 20 / NST; r++) {
#pragma unroll
    for (int s = 0; s < NST; s++) {
      mbar_wait(sBar + 8 * s, r & 1);
      wgmma_fence();
#pragma unroll
      for (int ks = 0; ks < 2; ks++)
        wgmma_ss_n240_tb(acc, da_base + (uint64_t)((s * STAGE_BYTES + ks * 32) >> 4), db_base + (uint64_t)((s * STAGE_BYTES + ks * 2048) >> 4), 1);
      wgmma_commit();
      wgmma_wait<1>();
      release_stage(sBar + 8 * (NST + (s + NST - 1) % NST), leader && (s > 0 || r > 0));
    }
  }
}
template <int WG>
__device__ __forceinline__ void glu_mainloop(float (&accg)[96], float (&accu)[96], uint32_t sbase, uint32_t sBar, bool leader) {
  constexpr int STAGE_BYTES = GLU_STAGE, NST = LG_STAGES;
  const uint64_t da_base = make_desc(sbase + WG * 4096, 16, 512, 2);
  const uint64_t db_base = make_desc(sbase + 8192, 4096, 1024, 1);
#pragma unroll 1
  for (int r = 0; r < 20 / NST; r++) {
#pragma unroll
    for (int s = 0; s < NST; s++) {
      mbar_wait(sBar + 8 * s, r & 1);
      wgmma_fence();
#pragma unroll
      for (int ks = 0; ks < 2; ks++) {
        const uint64_t da = da_base + (uint64_t)((s * STAGE_BYTES + ks * 32) >> 4);
        wgmma_ss_n192_tb(accg, da, db_base + (uint64_t)((s * STAGE_BYTES + ks * 2048) >> 4), 1);
        wgmma_ss_n192_tb(accu, da, db_base + (uint64_t)((s * STAGE_BYTES + 3 * 4096 + ks * 2048) >> 4), 1);
      }
      wgmma_commit();
      wgmma_wait<1>();
      release_stage(sBar + 8 * (NST + (s + NST - 1) % NST), leader && (s > 0 || r > 0));
    }
  }
}
constexpr int RG_STAGE_BYTES = 16384 + 8192 + 2048;
template <int NKB, int NST, int WG>
__device__ __forceinline__ void res_mainloop(float (&acc0)[32], float (&acc1)[8], uint32_t sbase, uint32_t sBar, bool leader) {
  const uint64_t da_base = make_desc(sbase + WG * 8192, 16, 1024, 1);
  const uint64_t db0_base = make_desc(sbase + 16384, 8192, 1024, 1);
  const uint64_t db1_base = make_desc(sbase + 16384 + 8192, 2048, 256, 3);
#pragma unroll 1
  for (int r = 0; r < NKB / NST; r++) {
#pragma unroll
    for (int s = 0; s < NST; s++) {
      const uint64_t so = (uint64_t)(s * (RG_STAGE_BYTES >> 4));
      mbar_wait(sBar + 8 * s, r & 1);
      wgmma_fence();
#pragma unroll
      for (int ks = 0; ks < 4; ks++) {
        wgmma_ss_n64_tb(acc0, da_base + so + ks * 2, db0_base + so + ks * 128, 1);
        wgmma_ss_n16_tb(acc1, da_base + so + ks * 2, db1_base + so + ks * 32, 1);
      }
      wgmma_commit();
      wgmma_wait<1>();
      release_stage(sBar + 8 * (NST + (s + NST - 1) % NST), leader && (s > 0 || r > 0));
    }
  }
}

constexpr int KA_CS = LG_STAGES * QKV_STAGE + 128;
constexpr int KA_SMEM = KA_CS + 1024 + 3072 + 1024;

__global__ void __launch_bounds__(GT, 1)
qkv_kernel(const __grid_constant__ CUtensorMap tmA, const __grid_constant__ CUtensorMap tmB, const bf16* __restrict__ x,
           const bf16* __restrict__ wqkv) {
  constexpr int STAGE_BYTES = QKV_STAGE, NST = LG_STAGES, NKB = 20;
  extern __shared__ uint8_t smem_raw[];
  const uint32_t sbase = (smem_u32(smem_raw) + 1023u) & ~1023u;
  const uint32_t sBar = sbase + NST * STAGE_BYTES;
  const int tid = threadIdx.x, warp = tid >> 5, lane = tid & 31;
  const int rank = blockIdx.x & 1;
  const int pair = blockIdx.x >> 1;
  const int n_blk = pair & 7;
  const int m_blk = (pair >> 3) * 2 + rank;
  TS(0, 0);
  if (tid == 256) {
    prefetch_tmap(&tmA);
    prefetch_tmap(&tmB);
  }
  if (tid == 0) {
    for (int s = 0; s < NST; s++) {
      mbar_init(sBar + 8 * s, 1);
      mbar_init(sBar + 8 * (NST + s), 4);
    }
    fence_mbar_init();
    if (blockIdx.x < 32) g_flag[16 + blockIdx.x] = 0;
  }
  pdl_launch();
  cluster_sync_all();

  if (warp >= 8) {
    asm volatile("setmaxnreg.dec.sync.aligned.u32 56;");
    if (warp >= 9) {
      const int w3 = warp - 9;
      float* red = reinterpret_cast<float*>(smem_raw + (sbase - smem_u32(smem_raw)) + KA_CS + 1024);
      if (lane < 30) {
        float a[8];
#pragma unroll
        for (int i = 0; i < 8; i++) a[i] = 0.f;
        const uint4* w = reinterpret_cast<const uint4*>(wqkv + (size_t)(m_blk * 40) * (3 * DM) + n_blk * 240) + lane;
#pragma unroll
        for (int r = w3; r < 42; r += 3) {
          if (r >= 40) break;
          const uint4 v = __ldg(w + (size_t)r * (3 * DM / 8));
          a[0] += bf_lo(v.x); a[1] += bf_hi(v.x); a[2] += bf_lo(v.y); a[3] += bf_hi(v.y);
          a[4] += bf_lo(v.z); a[5] += bf_hi(v.z); a[6] += bf_lo(v.w); a[7] += bf_hi(v.w);
        }
#pragma unroll
        for (int i = 0; i < 8; i++) red[w3 * 240 + lane * 8 + i] = a[i];
      }
      named_bar_sync(4, 96);
      for (int c = tid - 288; c < 240; c += 96) g_csp[m_blk * (3 * DM) + n_blk * 240 + c] = (red[c] + red[240 + c]) + red[480 + c];
      named_bar_sync(4, 96);
      if (tid == 288) flag_signal(&g_flag[48 + n_blk]);
      if (warp == 9) {
        named_bar_sync(5, 288);
        if (lane == 0) flag_signal(&g_flag[m_blk]);
      }
      if (lane == 0) {
        flag_wait(&g_flag[m_blk], 8);
        flag_wait(&g_flag[48 + n_blk], 16);
      }
      __syncwarp();
      float* cs_s = reinterpret_cast<float*>(smem_raw + (sbase - smem_u32(smem_raw)) + KA_CS);
      for (int c = tid - 288; c < 240; c += 96) {
        float t = 0.f;
#pragma unroll
        for (int mm = 0; mm < 16; mm++) t += g_csp[mm * (3 * DM) + n_blk * 240 + c];
        cs_s[c] = t;
      }
      named_bar_sync(6, 352);
    }
    if (tid == 256) {
      auto issue_b = [&](int kb) {
        const int s = kb % NST;
        const uint32_t full = sBar + 8 * s;
        mbar_expect_tx(full, STAGE_BYTES);
        const uint32_t dst = sbase + s * STAGE_BYTES + 8192;
#pragma unroll
        for (int j = 0; j < 2; j++) {
          const int sl = rank * 2 + j;
          tma_load_2d_mc(dst + sl * 4096, &tmB, n_blk * 240 + sl * 64, kb * 32, full, (uint16_t)3);
        }
      };
      for (int kb = 0; kb < NKB; kb++) {
        const int s = kb % NST;
        if (kb >= NST) mbar_wait(sBar + 8 * (NST + s), ((kb / NST) & 1) ^ 1);
        issue_b(kb);
        tma_load_2d(sbase + s * STAGE_BYTES, &tmA, kb * 32, m_blk * 128, sBar + 8 * s);
      }
    }
  } else {
    asm volatile("setmaxnreg.inc.sync.aligned.u32 224;");
    const int wg = __shfl_sync(0xffffffffu, warp >> 2, 0);
    const int wwarp = warp & 3;
    {
      const int row = m_blk * 128 + n_blk * 16 + warp * 2 + (lane >> 4);
      const float2 rs = ln_row_stats(x + (size_t)row * DM, lane & 15);
      if ((lane & 15) == 0) g_rs[row] = rs;
      asm volatile("bar.arrive 5, 288;" ::: "memory");
    }
    TS(0, 1);
    mbar_wait(sBar, 0);
    TS(0, 3);
    float acc[120];
#pragma unroll
    for (int i = 0; i < 120; i++) acc[i] = 0.f;
    if (wg == 0) qkv_mainloop<0>(acc, sbase, sBar, (tid & 127) == 0);
    else qkv_mainloop<1>(acc, sbase, sBar, (tid & 127) == 0);
    wgmma_wait<0>();
    fence_regs(acc);
    TS(0, 4);
    const int g = lane >> 2, c4 = lane & 3;
    float* cs_s = reinterpret_cast<float*>(smem_raw + (sbase - smem_u32(smem_raw)) + KA_CS);
    named_bar_sync(6, 352);
    const float2 rs0 = g_rs[m_blk * 128 + wg * 64 + wwarp * 16 + g], rs1 = g_rs[m_blk * 128 + wg * 64 + wwarp * 16 + g + 8];
    const uint32_t stg = sbase + wg * (12 * 3072) + (wwarp * 2) * 384 + g * 16;
    const int hbase = n_blk * 12;
#pragma unroll
    for (int j = 0; j < 30; j++) {
      const int cb = (j * 8) % 20;
      const int hb = (j * 8) / 20;
      int d = cb + c4 * 2;
      int hl = hb;
      if (cb == 16 && c4 >= 2) { d -= 20; hl += 1; }
      const uint32_t a0 = stg + hl * 3072 + (d >> 3) * 128 + (d & 7) * 2;
      const int hg = hbase + hl;
      const float sc = hg < 32 ? ATT_SCALE_LOG2E : 1.0f;
      const float2 cc = *reinterpret_cast<const float2*>(cs_s + j * 8 + c4 * 2);
      const float i0 = rs0.y * sc, i1 = rs1.y * sc;
      st_shared_b32(a0, pack_bf16(fmaf(-rs0.x, cc.x, acc[4 * j]) * i0, fmaf(-rs0.x, cc.y, acc[4 * j + 1]) * i0));
      st_shared_b32(a0 + 384, pack_bf16(fmaf(-rs1.x, cc.x, acc[4 * j + 2]) * i1, fmaf(-rs1.x, cc.y, acc[4 * j + 3]) * i1));
      if (d == 18) {
        const uint32_t pad0 = hg < 32 ? 0u : (hg < 64 ? 0x3f803f80u : 0x00003f80u);
        const uint32_t pad1 = (hg >= 32 && hg < 64) ? 0x00003f80u : 0u;
        st_shared_v2(a0 + 4, pad0, pad1);
        st_shared_v2(a0 + 388, pad0, pad1);
      }
      if (j % 10 == 9) {
        fence_proxy_async();
        named_bar_sync(1 + wg, 128);
        if ((tid & 127) < 4) {
          const int hs = (j / 10) * 4 + (tid & 127);
          bf16* dst = g_img + (size_t)(hbase + hs) * IMG_HEAD_ELEMS + (size_t)(m_blk * 16 + wg * 8) * 192;
          bulk_s2g(dst, sbase + wg * (12 * 3072) + hs * 3072, 3072);
          bulk_commit();
        }
      }
    }
    if ((tid & 127) < 4) bulk_wait_read();
  }
  __syncwarp();
  TS(0, 5);
  cluster_sync_relaxed();
  TS(0, 6);
}

constexpr int KC_NST1 = 5, KC_NST3 = 6;
constexpr int KC_STAGING = 160 * 1024;
constexpr int KC_BAR = KC_STAGING + 48 * 1024;
constexpr int KC_CS = KC_BAR + 512;
constexpr int KC_SMEM = KC_CS + 1536 + 1024;

__global__ void __launch_bounds__(GT, 1)
mlp_kernel(const __grid_constant__ CUtensorMap tmO, const __grid_constant__ CUtensorMap tmWo64, const __grid_constant__ CUtensorMap tmWo16,
           const __grid_constant__ CUtensorMap tmH, const __grid_constant__ CUtensorMap tmWg, const __grid_constant__ CUtensorMap tmWu,
           const __grid_constant__ CUtensorMap tmHHs, const __grid_constant__ CUtensorMap tmHH, const __grid_constant__ CUtensorMap tmWd64,
           const __grid_constant__ CUtensorMap tmWd16, const __grid_constant__ CUtensorMap tmHs, const __grid_constant__ CUtensorMap tmOut,
           const bf16* __restrict__ x) {
  extern __shared__ uint8_t smem_raw[];
  const uint32_t sbase = (smem_u32(smem_raw) + 1023u) & ~1023u;
  const uint32_t bar1 = sbase + KC_BAR;
  const uint32_t bar2 = bar1 + 128;
  const uint32_t bar3 = bar2 + 128;
  const uint32_t barD = bar3 + 128;
  const int tid = threadIdx.x, warp = tid >> 5, lane = tid & 31;
  const int rank = blockIdx.x & 1;
  const int pair = blockIdx.x >> 1;
  const int j_blk = pair & 7;
  const int m_blk = (pair >> 3) * 2 + rank;
  const int n0 = j_blk * 80;
  TS(2, 0);
  if (tid == 256) {
    prefetch_tmap(&tmO); prefetch_tmap(&tmWo64); prefetch_tmap(&tmWo16); prefetch_tmap(&tmH); prefetch_tmap(&tmWg);
    prefetch_tmap(&tmWu); prefetch_tmap(&tmHHs); prefetch_tmap(&tmHH); prefetch_tmap(&tmWd64); prefetch_tmap(&tmWd16);
    prefetch_tmap(&tmHs); prefetch_tmap(&tmOut);
  }
  if (tid == 0) {
    for (int s = 0; s < 5; s++) {
      mbar_init(bar1 + 8 * s, 1); mbar_init(bar1 + 8 * (5 + s), 4);
      mbar_init(bar2 + 8 * s, 1); mbar_init(bar2 + 8 * (5 + s), 4);
    }
    for (int s = 0; s < 6; s++) { mbar_init(bar3 + 8 * s, 1); mbar_init(bar3 + 8 * (6 + s), 4); }
    mbar_init(barD, 4); mbar_init(barD + 8, 4);
    fence_mbar_init();
  }
  cluster_sync_all();

  if (warp >= 8) {
    asm volatile("setmaxnreg.dec.sync.aligned.u32 40;");
    if (tid == 256) {
      auto issue_b80 = [&](const CUtensorMap* t64, const CUtensorMap* t16, uint32_t bars, int nst, int kb) {
        const int s = kb % nst;
        const uint32_t full = bars + 8 * s;
        const uint32_t st = sbase + s * RG_STAGE_BYTES;
        mbar_expect_tx(full, RG_STAGE_BYTES);
        tma_load_2d_mc(st + 16384 + rank * 4096, t64, n0, kb * 64 + rank * 32, full, (uint16_t)3);
        tma_load_2d_mc(st + 16384 + 8192 + rank * 1024, t16, n0 + 64, kb * 64 + rank * 32, full, (uint16_t)3);
      };
      for (int kb = 0; kb < KC_NST1; kb++) issue_b80(&tmWo64, &tmWo16, bar1, KC_NST1, kb);
      pdl_wait();
      for (int kb = 0; kb < 10; kb++) {
        const int s = kb % KC_NST1;
        if (kb >= KC_NST1) {
          mbar_wait(bar1 + 8 * (KC_NST1 + s), ((kb / KC_NST1) & 1) ^ 1);
          issue_b80(&tmWo64, &tmWo16, bar1, KC_NST1, kb);
        }
        tma_load_2d(sbase + s * RG_STAGE_BYTES, &tmO, kb * 64, m_blk * 128, bar1 + 8 * s);
      }
      auto issue_bglu = [&](int kb) {
        const int s = kb % LG_STAGES;
        const uint32_t full = bar2 + 8 * s;
        mbar_expect_tx(full, GLU_STAGE);
        const uint32_t dst = sbase + s * GLU_STAGE + 8192;
#pragma unroll
        for (int j = 0; j < 3; j++)
          tma_load_2d_mc(dst + (rank * 3 + j) * 4096, rank == 0 ? &tmWg : &tmWu, j_blk * 192 + j * 64, kb * 32, full, (uint16_t)3);
      };
      mbar_wait(barD, 0);
      for (int kb = 0; kb < LG_STAGES; kb++) issue_bglu(kb);
      flag_wait(&g_flag[16 + m_blk], 16);
      fence_proxy_async_all();
      for (int kb = 0; kb < 20; kb++) {
        const int s = kb % LG_STAGES;
        if (kb >= LG_STAGES) {
          mbar_wait(bar2 + 8 * (LG_STAGES + s), ((kb / LG_STAGES) & 1) ^ 1);
          issue_bglu(kb);
        }
        tma_load_2d(sbase + s * GLU_STAGE, &tmH, kb * 32, m_blk * 128, bar2 + 8 * s);
      }
      mbar_wait(barD + 8, 0);
      for (int kb = 0; kb < KC_NST3; kb++) issue_b80(&tmWd64, &tmWd16, bar3, KC_NST3, kb);
      flag_wait(&g_flag[32 + m_blk], 16);
      fence_proxy_async_all();
      for (int kb = 0; kb < 24; kb++) {
        const int s = kb % KC_NST3;
        if (kb >= KC_NST3) {
          mbar_wait(bar3 + 8 * (KC_NST3 + s), ((kb / KC_NST3) & 1) ^ 1);
          issue_b80(&tmWd64, &tmWd16, bar3, KC_NST3, kb);
        }
        tma_load_2d(sbase + s * RG_STAGE_BYTES, &tmHH, kb * 64, m_blk * 128, bar3 + 8 * s);
      }
    }
  } else {
    asm volatile("setmaxnreg.inc.sync.aligned.u32 232;");
    const int wg = __shfl_sync(0xffffffffu, warp >> 2, 0);
    const int wwarp = warp & 3;
    const int g = lane >> 2, c4 = lane & 3;
    const int row0 = m_blk * 128 + wg * 64 + wwarp * 16 + g;
    const bool leader = (tid & 127) == 0;
    const uint32_t stg80_base = sbase + KC_STAGING + wg * 24576;
    const uint32_t stg80 = stg80_base + (wwarp * 16 + g) * 160 + c4 * 4;
    {
      uint32_t res[20];
#pragma unroll
      for (int j = 0; j < 10; j++) {
        res[2 * j] = __ldg(reinterpret_cast<const uint32_t*>(x + (size_t)row0 * DM + n0 + j * 8 + c4 * 2));
        res[2 * j + 1] = __ldg(reinterpret_cast<const uint32_t*>(x + (size_t)(row0 + 8) * DM + n0 + j * 8 + c4 * 2));
      }
      float acc0[32], acc1[8];
#pragma unroll
      for (int i = 0; i < 32; i++) acc0[i] = 0.f;
#pragma unroll
      for (int i = 0; i < 8; i++) acc1[i] = 0.f;
      TS(2, 1);
      if (wg == 0) res_mainloop<10, KC_NST1, 0>(acc0, acc1, sbase, bar1, leader);
      else res_mainloop<10, KC_NST1, 1>(acc0, acc1, sbase, bar1, leader);
      wgmma_wait<0>();
      fence_regs(acc0); fence_regs(acc1);
      release_stage(barD, leader);
      TS(2, 4);
      float sum0 = 0.f, sum1 = 0.f;
#pragma unroll
      for (int j = 0; j < 10; j++) {
        const uint32_t a01 = j < 8 ? pack_bf16(acc0[4 * j], acc0[4 * j + 1]) : pack_bf16(acc1[4 * (j - 8)], acc1[4 * (j - 8) + 1]);
        const uint32_t a23 = j < 8 ? pack_bf16(acc0[4 * j + 2], acc0[4 * j + 3]) : pack_bf16(acc1[4 * (j - 8) + 2], acc1[4 * (j - 8) + 3]);
        res[2 * j] = pack_bf16(bf_lo(res[2 * j]) + bf_lo(a01), bf_hi(res[2 * j]) + bf_hi(a01));
        res[2 * j + 1] = pack_bf16(bf_lo(res[2 * j + 1]) + bf_lo(a23), bf_hi(res[2 * j + 1]) + bf_hi(a23));
        st_shared_b32(stg80 + j * 16, res[2 * j]);
        st_shared_b32(stg80 + 8 * 160 + j * 16, res[2 * j + 1]);
        sum0 += bf_lo(res[2 * j]) + bf_hi(res[2 * j]);
        sum1 += bf_lo(res[2 * j + 1]) + bf_hi(res[2 * j + 1]);
      }
      sum0 += __shfl_xor_sync(0xffffffffu, sum0, 1); sum1 += __shfl_xor_sync(0xffffffffu, sum1, 1);
      sum0 += __shfl_xor_sync(0xffffffffu, sum0, 2); sum1 += __shfl_xor_sync(0xffffffffu, sum1, 2);
      const float mu0 = sum0 * (1.0f / 80.0f), mu1 = sum1 * (1.0f / 80.0f);
      float q0 = 0.f, q1 = 0.f;
#pragma unroll
      for (int j = 0; j < 10; j++) {
        float d;
        d = bf_lo(res[2 * j]) - mu0; q0 = fmaf(d, d, q0);
        d = bf_hi(res[2 * j]) - mu0; q0 = fmaf(d, d, q0);
        d = bf_lo(res[2 * j + 1]) - mu1; q1 = fmaf(d, d, q1);
        d = bf_hi(res[2 * j + 1]) - mu1; q1 = fmaf(d, d, q1);
      }
      q0 += __shfl_xor_sync(0xffffffffu, q0, 1); q1 += __shfl_xor_sync(0xffffffffu, q1, 1);
      q0 += __shfl_xor_sync(0xffffffffu, q0, 2); q1 += __shfl_xor_sync(0xffffffffu, q1, 2);
      if (c4 == 0) {
        g_stats[row0 * 8 + j_blk] = make_float2(mu0, q0);
        g_stats[(row0 + 8) * 8 + j_blk] = make_float2(mu1, q1);
      }
      fence_proxy_async();
      named_bar_sync(1 + wg, 128);
      if (leader) {
        tma_store_2d(&tmHs, stg80_base, n0, m_blk * 128 + wg * 64);
        bulk_commit();
        bulk_wait_all();
        fence_proxy_async_all();
        flag_signal(&g_flag[16 + m_blk]);
      }
      TS(2, 5);
    }
    {
      pdl_wait();
      {
        float* cs_s = reinterpret_cast<float*>(smem_raw + (sbase - smem_u32(smem_raw)) + KC_CS);
        for (int i = tid; i < 384; i += 256) cs_s[i] = g_cs[(i >= 192 ? FF - 192 : 0) + j_blk * 192 + i];
        named_bar_sync(3, 256);
      }
      flag_wait(&g_flag[16 + m_blk], 16);
      float mb[2], iv[2];
#pragma unroll
      for (int h = 0; h < 2; h++) {
        const float4* sp = reinterpret_cast<const float4*>(g_stats + (row0 + 8 * h) * 8);
        const float4 p0 = sp[0], p1 = sp[1], p2 = sp[2], p3 = sp[3];
        const float mean = (((p0.x + p0.z) + (p1.x + p1.z)) + ((p2.x + p2.z) + (p3.x + p3.z))) * 0.125f;
        float m2 = ((p0.y + p0.w) + (p1.y + p1.w)) + ((p2.y + p2.w) + (p3.y + p3.w));
        float dd = 0.f, d;
        d = p0.x - mean; dd = fmaf(d, d, dd); d = p0.z - mean; dd = fmaf(d, d, dd);
        d = p1.x - mean; dd = fmaf(d, d, dd); d = p1.z - mean; dd = fmaf(d, d, dd);
        d = p2.x - mean; dd = fmaf(d, d, dd); d = p2.z - mean; dd = fmaf(d, d, dd);
        d = p3.x - mean; dd = fmaf(d, d, dd); d = p3.z - mean; dd = fmaf(d, d, dd);
        m2 = fmaf(dd, 80.0f, m2);
        const float var_b = bf16_round(m2 * (1.0f / DM));
        const float den = bf16_round(sqrtf(bf16_round(var_b + 1e-5f)));
        iv[h] = __frcp_rn(den);
        mb[h] = bf16_round(mean);
      }
      float accg[96], accu[96];
#pragma unroll
      for (int i = 0; i < 96; i++) { accg[i] = 0.f; accu[i] = 0.f; }
      TS(3, 3);
      if (wg == 0) glu_mainloop<0>(accg, accu, sbase, bar2, leader);
      else glu_mainloop<1>(accg, accu, sbase, bar2, leader);
      wgmma_wait<0>();
      fence_regs(accg); fence_regs(accu);
      release_stage(barD + 8, leader);
      TS(3, 4);
      const uint32_t stg = sbase + KC_STAGING + wg * 24576 + (wwarp * 16 + g) * 128 + c4 * 4;
      const float* csg = reinterpret_cast<const float*>(smem_raw + (sbase - smem_u32(smem_raw)) + KC_CS) + c4 * 2;
      const float nm0 = -mb[0] * iv[0], nm1 = -mb[1] * iv[1];
#pragma unroll
      for (int sl = 0; sl < 3; sl++) {
#pragma unroll
        for (int jj = 0; jj < 8; jj++) {
          const int j = sl * 8 + jj;
          const float2 cg = *reinterpret_cast<const float2*>(csg + j * 8);
          const float2 cu = *reinterpret_cast<const float2*>(csg + 192 + j * 8);
          const float r0 = fmaxf(fmaf(accg[4 * j], iv[0], nm0 * cg.x), 0.f) * fmaf(accu[4 * j], iv[0], nm0 * cu.x);
          const float r1 = fmaxf(fmaf(accg[4 * j + 1], iv[0], nm0 * cg.y), 0.f) * fmaf(accu[4 * j + 1], iv[0], nm0 * cu.y);
          const float r2 = fmaxf(fmaf(accg[4 * j + 2], iv[1], nm1 * cg.x), 0.f) * fmaf(accu[4 * j + 2], iv[1], nm1 * cu.x);
          const float r3 = fmaxf(fmaf(accg[4 * j + 3], iv[1], nm1 * cg.y), 0.f) * fmaf(accu[4 * j + 3], iv[1], nm1 * cu.y);
          const uint32_t a0 = stg + sl * 8192 + ((jj ^ g) << 4);
          st_shared_b32(a0, pack_bf16(r0, r1));
          st_shared_b32(a0 + 1024, pack_bf16(r2, r3));
        }
        fence_proxy_async();
        named_bar_sync(1 + wg, 128);
        if (leader) {
          tma_store_2d(&tmHHs, sbase + KC_STAGING + wg * 24576 + sl * 8192, j_blk * 192 + sl * 64, m_blk * 128 + wg * 64);
          bulk_commit();
        }
      }
      TS(3, 7);
      if (leader) {
        bulk_wait_all();
        TS(3, 8);
        fence_proxy_async_all();
        flag_signal(&g_flag[32 + m_blk]);
      }
      TS(3, 9);
    }
    {
      uint32_t res[20];
#pragma unroll
      for (int j = 0; j < 10; j++) {
        res[2 * j] = *reinterpret_cast<const uint32_t*>(g_h + (size_t)row0 * DM + n0 + j * 8 + c4 * 2);
        res[2 * j + 1] = *reinterpret_cast<const uint32_t*>(g_h + (size_t)(row0 + 8) * DM + n0 + j * 8 + c4 * 2);
      }
      float acc0[32], acc1[8];
#pragma unroll
      for (int i = 0; i < 32; i++) acc0[i] = 0.f;
#pragma unroll
      for (int i = 0; i < 8; i++) acc1[i] = 0.f;
      mbar_wait(bar3, 0);
      TS(4, 3);
      if (wg == 0) res_mainloop<24, KC_NST3, 0>(acc0, acc1, sbase, bar3, leader);
      else res_mainloop<24, KC_NST3, 1>(acc0, acc1, sbase, bar3, leader);
      wgmma_wait<0>();
      fence_regs(acc0); fence_regs(acc1);
      TS(4, 4);
#pragma unroll
      for (int j = 0; j < 10; j++) {
        const uint32_t a01 = j < 8 ? pack_bf16(acc0[4 * j], acc0[4 * j + 1]) : pack_bf16(acc1[4 * (j - 8)], acc1[4 * (j - 8) + 1]);
        const uint32_t a23 = j < 8 ? pack_bf16(acc0[4 * j + 2], acc0[4 * j + 3]) : pack_bf16(acc1[4 * (j - 8) + 2], acc1[4 * (j - 8) + 3]);
        st_shared_b32(stg80 + j * 16, pack_bf16(bf_lo(res[2 * j]) + bf_lo(a01), bf_hi(res[2 * j]) + bf_hi(a01)));
        st_shared_b32(stg80 + 8 * 160 + j * 16, pack_bf16(bf_lo(res[2 * j + 1]) + bf_lo(a23), bf_hi(res[2 * j + 1]) + bf_hi(a23)));
      }
      fence_proxy_async();
      named_bar_sync(1 + wg, 128);
      if (leader) {
        tma_store_2d(&tmOut, stg80_base, n0, m_blk * 128 + wg * 64);
        bulk_commit();
        bulk_wait_read();
      }
      TS(4, 5);
    }
  }
  __syncwarp();
  cluster_sync_relaxed();
  TS(4, 6);
}

constexpr int AT_THREADS = 512;
constexpr int AT_WGS = AT_THREADS / 128;
#define AT_CHUNK_MASK 3
#define AT_STAGGER 0
constexpr int AT_KV_BYTES = IMG_HEAD_ELEMS * 2;
constexpr int AT_SMEM = 2 * AT_KV_BYTES + 256 + 1024;
constexpr int AT_CHUNKS = 8;

__device__ __forceinline__ float exp2_poly(float x) {
  const float u = __saturatef(fmaf(x, 1.0f / 64.0f, 62.0f / 64.0f));
  const float MAGIC = 12582912.0f - 62.0f;
  const float r = fmaf(u, 64.0f, MAGIC);
  const float q = MAGIC - r;
  const float fr = fmaf(u, 64.0f, q);
  float p = fmaf(fr, 0.009570102207362652f, 0.05591785907745361f);
  p = fmaf(p, fr, 0.240247443318367f);
  p = fmaf(p, fr, 0.6931217908859253f);
  p = fmaf(p, fr, 0.9999992847442627f);
  return __uint_as_float(__float_as_uint(p) + (__float_as_uint(r) << 23));
}
#define AT_VARIANT 0
#define AT_POLY_MOD 8
__device__ __forceinline__ bool use_poly(int e) {
  return (e % AT_POLY_MOD) == 1;
}

struct AttnState {
  uint32_t qa0, qa1, qa2, qa3, qa4, qa5;
  float M0, M1;
};

__device__ __forceinline__ bool attn_exp_fast(const float (&s)[32], uint32_t (&p)[16]) {
#pragma unroll
  for (int j = 0; j < 16; j++) {
    const float e0 = use_poly(2 * j) ? exp2_poly(s[2 * j]) : ex2(s[2 * j]);
    const float e1 = use_poly(2 * j + 1) ? exp2_poly(s[2 * j + 1]) : ex2(s[2 * j + 1]);
    p[j] = pack_bf16(e0, e1);
  }
  uint32_t acc_or = 0;
#pragma unroll
  for (int j = 0; j < 16; j++) acc_or |= p[j];
  return __any_sync(0xffffffffu, (acc_or & 0x40004000u) != 0);
}
__device__ __forceinline__ void attn_exp_exact(const float (&s)[32], uint32_t (&p)[16], float (&o)[12], AttnState& st, bool first, int c4) {
  float mx0 = fmaxf(s[0], s[1]), mx1 = fmaxf(s[2], s[3]);
#pragma unroll
  for (int j = 1; j < 8; j++) {
    mx0 = fmaxf(mx0, fmaxf(s[4 * j], s[4 * j + 1]));
    mx1 = fmaxf(mx1, fmaxf(s[4 * j + 2], s[4 * j + 3]));
  }
  mx0 = fmaxf(mx0, __shfl_xor_sync(0xffffffffu, mx0, 1));
  mx1 = fmaxf(mx1, __shfl_xor_sync(0xffffffffu, mx1, 1));
  mx0 = fmaxf(mx0, __shfl_xor_sync(0xffffffffu, mx0, 2));
  mx1 = fmaxf(mx1, __shfl_xor_sync(0xffffffffu, mx1, 2));
  float d0 = mx0 + 7.0f, d1 = mx1 + 7.0f;
  if (!first) { d0 = fmaxf(d0, 0.f); d1 = fmaxf(d1, 0.f); }
  const float T0 = st.M0 + d0, T1 = st.M1 + d1;
  const float h0 = bf16_round(T0), h1 = bf16_round(T1);
  const float i0 = bf16_round(T0 - h0), i1 = bf16_round(T1 - h1);
  const float l0 = bf16_round((T0 - h0) - i0), l1 = bf16_round((T1 - h1) - i1);
  const float N0 = (h0 + i0) + l0, N1 = (h1 + i1) + l1;
  d0 = N0 - st.M0; d1 = N1 - st.M1;
  st.M0 = N0; st.M1 = N1;
  if (c4 == 2) { st.qa4 = pack_bf16(-h0, -i0); st.qa5 = pack_bf16(-h1, -i1); }
  if (c4 == 3) { st.qa4 = pack_bf16(-l0, 0.f); st.qa5 = pack_bf16(-l1, 0.f); }
  if (!first) {
    const float al0 = ex2(-d0), al1 = ex2(-d1);
#pragma unroll
    for (int j = 0; j < 3; j++) {
      o[4 * j] *= al0; o[4 * j + 1] *= al0;
      o[4 * j + 2] *= al1; o[4 * j + 3] *= al1;
    }
  }
#pragma unroll
  for (int j = 0; j < 8; j++) {
    p[2 * j] = pack_bf16(ex2(s[4 * j] - d0), ex2(s[4 * j + 1] - d0));
    p[2 * j + 1] = pack_bf16(ex2(s[4 * j + 2] - d1), ex2(s[4 * j + 3] - d1));
  }
}
__device__ __forceinline__ void attn_step(float (&s)[32], const uint32_t (&pp)[16], uint32_t (&pn)[16], float (&o)[12], AttnState& st,
                                          uint32_t k_addr, uint32_t v_addr_prev, int keep, int c4, int wgdbg = 0, int tdbg = 0) {
  PH(wgdbg, tdbg, 0);
  const uint64_t dk = make_desc(k_addr, 128, 384, 0);
  const uint64_t dv_prev = make_desc(v_addr_prev, 384, 128, 0);
  wgmma_fence();
  wgmma_rs_n64(s, st.qa0, st.qa1, st.qa2, st.qa3, dk, 0);
  wgmma_rs_n64(s, st.qa4, st.qa5, 0u, 0u, dk + 16, 1);
  wgmma_commit();
#pragma unroll
  for (int kk = 0; kk < 4; kk++) wgmma_rs_n24_tb(o, pp[4 * kk], pp[4 * kk + 1], pp[4 * kk + 2], pp[4 * kk + 3], dv_prev + kk * 48, kk == 0 ? keep : 1);
  wgmma_commit();
  wgmma_wait<1>();
  fence_regs(s);
  PH(wgdbg, tdbg, 1);
  const bool redo = attn_exp_fast(s, pn);
  PH(wgdbg, tdbg, 2);
  wgmma_wait<0>();
  fence_regs(o);
  if (redo) attn_exp_exact(s, pn, o, st, false, c4);
}

__global__ void __launch_bounds__(AT_THREADS, 1) attn_kernel(const bf16* __restrict__ wo, const bf16* __restrict__ wgt, const bf16* __restrict__ wup, const bf16* __restrict__ wdn) {
  extern __shared__ uint8_t smem_raw[];
  const uint32_t sbase = (smem_u32(smem_raw) + 1023u) & ~1023u;
  const uint32_t sK = sbase, sV = sbase + AT_KV_BYTES;
  const uint32_t sBar = sV + AT_KV_BYTES;
  const int tid = threadIdx.x, warp = tid >> 5, lane = tid & 31;
  const int head = blockIdx.x >> 2, quarter = blockIdx.x & 3;
  if (blockIdx.x >= 128) {
    pdl_launch();
    const int b = blockIdx.x - 128;
    const bf16* w = (b >> 1) ? wup : wgt;
    const int cgrp = tid % 96, rgrp = tid / 96;
    float acc[8];
#pragma unroll
    for (int i = 0; i < 8; i++) acc[i] = 0.f;
    float* red = reinterpret_cast<float*>(smem_raw);
    if (rgrp < 5) {
      const uint4* src = reinterpret_cast<const uint4*>(w + (size_t)(rgrp * 128) * FF + (b & 1) * 768 + cgrp * 8);
#pragma unroll 8
      for (int r = 0; r < 128; r++) {
        const uint4 v = __ldg(src + (size_t)r * (FF / 8));
        acc[0] += bf_lo(v.x); acc[1] += bf_hi(v.x); acc[2] += bf_lo(v.y); acc[3] += bf_hi(v.y);
        acc[4] += bf_lo(v.z); acc[5] += bf_hi(v.z); acc[6] += bf_lo(v.w); acc[7] += bf_hi(v.w);
      }
#pragma unroll
      for (int i = 0; i < 8; i++) red[rgrp * 768 + cgrp * 8 + i] = acc[i];
    }
    __syncthreads();
    pdl_wait();
    for (int c = tid; c < 768; c += AT_THREADS)
      g_cs[(b >> 1) * FF + (b & 1) * 768 + c] = ((red[c] + red[768 + c]) + (red[1536 + c] + red[2304 + c])) + red[3072 + c];
    if (b == 0 && tid < 16) g_flag[tid] = 0;
    if (b == 0 && tid < 8) g_flag[48 + tid] = 0;
    return;
  }
  TS(1, 0);
  if (tid == 0) {
    for (int i = 0; i < AT_CHUNKS; i++) mbar_init(sBar + 8 * i, 1);
    fence_mbar_init();
  }
  pdl_launch();
  if (tid == 32) {
    prefetch_l2(reinterpret_cast<const uint8_t*>(wo) + blockIdx.x * 6400, 6400);
    prefetch_l2(reinterpret_cast<const uint8_t*>(wgt) + blockIdx.x * 15360, 15360);
    prefetch_l2(reinterpret_cast<const uint8_t*>(wup) + blockIdx.x * 15360, 15360);
    prefetch_l2(reinterpret_cast<const uint8_t*>(wdn) + blockIdx.x * 15360, 15360);
  }
  __syncthreads();
  TS(1, 1);
  pdl_wait();
  TS(1, 2);
  if (tid == 0) {
    const uint8_t* kg = reinterpret_cast<const uint8_t*>(g_img + (size_t)(32 + head) * IMG_HEAD_ELEMS);
    const uint8_t* vg = reinterpret_cast<const uint8_t*>(g_img + (size_t)(64 + head) * IMG_HEAD_ELEMS);
    constexpr int CB = AT_KV_BYTES / AT_CHUNKS;
    for (int i = 0; i < AT_CHUNKS; i++) {
      mbar_expect_tx(sBar + 8 * i, 2 * CB);
      bulk_g2s(sK + i * CB, kg + i * CB, CB, sBar + 8 * i);
      bulk_g2s(sV + i * CB, vg + i * CB, CB, sBar + 8 * i);
    }
  }
  const int wg = warp >> 2, wwarp = warp & 3;
  const int g = lane >> 2, c4 = lane & 3;
  const uint64_t dk_base = make_desc(sK, 128, 384, 0);
  const uint64_t dv_base = make_desc(sV, 384, 128, 0);

#pragma unroll 1
  for (int rep = 0; rep < 8 / AT_WGS; rep++) {
    const int row0 = quarter * 512 + (rep * AT_WGS + wg) * 64 + wwarp * 16 + g;
    AttnState st;
    {
      const bf16* q0 = g_img + (size_t)head * IMG_HEAD_ELEMS + (size_t)(row0 >> 3) * 192 + g * 8 + c4 * 2;
      const bf16* q1 = q0 + 192;
      st.qa0 = *reinterpret_cast<const uint32_t*>(q0);
      st.qa1 = *reinterpret_cast<const uint32_t*>(q1);
      st.qa2 = *reinterpret_cast<const uint32_t*>(q0 + 64);
      st.qa3 = *reinterpret_cast<const uint32_t*>(q1 + 64);
      st.qa4 = *reinterpret_cast<const uint32_t*>(q0 + 128);
      st.qa5 = *reinterpret_cast<const uint32_t*>(q1 + 128);
    }
    float o[12];
    float s[32];
    uint32_t pa[16], pb[16];
    st.M0 = st.M1 = 0.f;
    if (rep == 0) mbar_wait(sBar, 0);
    wgmma_fence();
    wgmma_rs_n64(s, st.qa0, st.qa1, st.qa2, st.qa3, dk_base, 0);
    wgmma_rs_n64(s, st.qa4, st.qa5, 0u, 0u, dk_base + 16, 1);
    wgmma_commit();
    wgmma_wait<0>();
    fence_regs(s);
    attn_exp_exact(s, pa, o, st, true, c4);
    attn_step(s, pa, pb, o, st, sK + 3072, sV, 0, c4);
#pragma unroll 1
    for (int tt = 1; tt < 16; tt++) {
      if (rep == 0 && !(tt & 1)) mbar_wait(sBar + 8 * (tt >> 1), 0);
      attn_step(s, pb, pa, o, st, sK + tt * 6144, sV + tt * 6144 - 3072, 1, c4, wg, rep * 32 + tt * 2);
      attn_step(s, pa, pb, o, st, sK + tt * 6144 + 3072, sV + tt * 6144, 1, c4, wg, rep * 32 + tt * 2 + 1);
    }
    wgmma_fence();
#pragma unroll
    for (int kk = 0; kk < 4; kk++) wgmma_rs_n24_tb(o, pb[4 * kk], pb[4 * kk + 1], pb[4 * kk + 2], pb[4 * kk + 3], dv_base + 31 * 192 + kk * 48, 1);
    wgmma_commit();
    wgmma_wait<0>();
    fence_regs(o);
    TS(1, 3 + rep);
    const float l0 = __shfl_sync(0xffffffffu, o[8], (lane & ~3) | 2);
    const float l1 = __shfl_sync(0xffffffffu, o[10], (lane & ~3) | 2);
    const float i0 = 1.0f / l0, i1 = 1.0f / l1;
    bf16* o0 = g_o + (size_t)row0 * DM + head * DH;
    bf16* o1 = o0 + 8 * DM;
#pragma unroll
    for (int j = 0; j < 3; j++) {
      if (j < 2 || c4 < 2) {
        *reinterpret_cast<uint32_t*>(o0 + j * 8 + c4 * 2) = pack_bf16(o[4 * j] * i0, o[4 * j + 1] * i0);
        *reinterpret_cast<uint32_t*>(o1 + j * 8 + c4 * 2) = pack_bf16(o[4 * j + 2] * i1, o[4 * j + 3] * i1);
      }
    }
  }
}

typedef CUresult (*EncodeTiledFn)(CUtensorMap*, CUtensorMapDataType, cuuint32_t, void*, const cuuint64_t*, const cuuint64_t*,
                                  const cuuint32_t*, const cuuint32_t*, CUtensorMapInterleave, CUtensorMapSwizzle,
                                  CUtensorMapL2promotion, CUtensorMapFloatOOBfill);

static void make_map(EncodeTiledFn fn, CUtensorMap* tm, const void* ptr, uint64_t rows, uint64_t cols, uint32_t box_rows,
                     uint32_t box_cols, CUtensorMapSwizzle sw) {
  cuuint64_t dims[2] = {cols, rows};
  cuuint64_t strides[1] = {cols * 2};
  cuuint32_t box[2] = {box_cols, box_rows};
  cuuint32_t es[2] = {1, 1};
  fn(tm, CU_TENSOR_MAP_DATA_TYPE_BFLOAT16, 2, const_cast<void*>(ptr), dims, strides, box, es, CU_TENSOR_MAP_INTERLEAVE_NONE, sw,
     CU_TENSOR_MAP_L2_PROMOTION_L2_256B, CU_TENSOR_MAP_FLOAT_OOB_FILL_NONE);
}

template <typename... KArgs, typename... Args>
static void launch(void (*kern)(KArgs...), int grid, int block, int smem, int cluster, bool pdl, Args... args) {
  cudaLaunchConfig_t cfg = {};
  cfg.gridDim = dim3(grid);
  cfg.blockDim = dim3(block);
  cfg.dynamicSmemBytes = smem;
  cfg.stream = cudaStreamPerThread;
  cudaLaunchAttribute at[2];
  int n = 0;
  if (cluster > 1) {
    at[n].id = cudaLaunchAttributeClusterDimension;
    at[n].val.clusterDim.x = cluster; at[n].val.clusterDim.y = 1; at[n].val.clusterDim.z = 1;
    n++;
  }
  if (pdl) {
    at[n].id = cudaLaunchAttributeProgrammaticStreamSerialization;
    at[n].val.programmaticStreamSerializationAllowed = 1;
    n++;
  }
  cfg.attrs = at;
  cfg.numAttrs = n;
  cudaLaunchKernelEx(&cfg, kern, KArgs(args)...);
}

extern "C" void kernel_launch(void* const* d_in, const int* in_sizes, int n_in, void* d_out, int out_size) {
  const bf16* x = (const bf16*)d_in[0];
  const bf16* wqkv = (const bf16*)d_in[1];
  const bf16* wo = (const bf16*)d_in[2];
  const bf16* wg = (const bf16*)d_in[4];
  const bf16* wu = (const bf16*)d_in[5];
  const bf16* wd = (const bf16*)d_in[6];
  bf16* out = (bf16*)d_out;

  static EncodeTiledFn enc = nullptr;
  static void *p_o = nullptr, *p_h = nullptr, *p_hh = nullptr;
  if (!enc) {
    void* fn = nullptr;
    cudaDriverEntryPointQueryResult qr;
    cudaGetDriverEntryPoint("cuTensorMapEncodeTiled", &fn, cudaEnableDefault, &qr);
    enc = (EncodeTiledFn)fn;
    cudaGetSymbolAddress(&p_o, g_o);
    cudaGetSymbolAddress(&p_h, g_h);
    cudaGetSymbolAddress(&p_hh, g_hh);
    cudaFuncSetAttribute(qkv_kernel, cudaFuncAttributeMaxDynamicSharedMemorySize, KA_SMEM);
    cudaFuncSetAttribute(mlp_kernel, cudaFuncAttributeMaxDynamicSharedMemorySize, KC_SMEM);
    cudaFuncSetAttribute(attn_kernel, cudaFuncAttributeMaxDynamicSharedMemorySize, AT_SMEM);
  }
  CUtensorMap tm_wqkv, tm_wg, tm_wu, tm_wo64, tm_wo16, tm_wd64, tm_wd16, tm_o, tm_h, tm_hh, tm_hhs, tm_xn, tm_hs, tm_out;
  make_map(enc, &tm_wqkv, wqkv, DM, 3 * DM, 32, 64, CU_TENSOR_MAP_SWIZZLE_128B);
  make_map(enc, &tm_wg, wg, DM, FF, 32, 64, CU_TENSOR_MAP_SWIZZLE_128B);
  make_map(enc, &tm_wu, wu, DM, FF, 32, 64, CU_TENSOR_MAP_SWIZZLE_128B);
  make_map(enc, &tm_wo64, wo, DM, DM, 32, 64, CU_TENSOR_MAP_SWIZZLE_128B);
  make_map(enc, &tm_wo16, wo, DM, DM, 32, 16, CU_TENSOR_MAP_SWIZZLE_32B);
  make_map(enc, &tm_wd64, wd, FF, DM, 32, 64, CU_TENSOR_MAP_SWIZZLE_128B);
  make_map(enc, &tm_wd16, wd, FF, DM, 32, 16, CU_TENSOR_MAP_SWIZZLE_32B);
  make_map(enc, &tm_o, p_o, SEQ, DM, 128, 64, CU_TENSOR_MAP_SWIZZLE_128B);
  make_map(enc, &tm_h, p_h, SEQ, DM, 128, 32, CU_TENSOR_MAP_SWIZZLE_64B);
  make_map(enc, &tm_hh, p_hh, SEQ, FF, 128, 64, CU_TENSOR_MAP_SWIZZLE_128B);
  make_map(enc, &tm_hhs, p_hh, SEQ, FF, 64, 64, CU_TENSOR_MAP_SWIZZLE_128B);
  make_map(enc, &tm_xn, x, SEQ, DM, 128, 32, CU_TENSOR_MAP_SWIZZLE_64B);
  make_map(enc, &tm_hs, p_h, SEQ, DM, 64, 80, CU_TENSOR_MAP_SWIZZLE_NONE);
  make_map(enc, &tm_out, out, SEQ, DM, 64, 80, CU_TENSOR_MAP_SWIZZLE_NONE);

  launch(qkv_kernel, 128, GT, KA_SMEM, 2, false, tm_xn, tm_wqkv, x, wqkv);
  launch(attn_kernel, 132, AT_THREADS, AT_SMEM, 1, true, wo, wg, wu, wd);
  launch(mlp_kernel, 128, GT, KC_SMEM, 2, true, tm_o, tm_wo64, tm_wo16, tm_h, tm_wg, tm_wu, tm_hhs, tm_hh, tm_wd64, tm_wd16, tm_hs, tm_out, x);
}
```

```cpp
#include <cuda_runtime.h>
#include <cuda_bf16.h>
#include <cuda.h>
#include <stdint.h>

typedef __nv_bfloat16 bf16;
#define FLAGV 0

constexpr int SEQ = 2048, DM = 640, NH = 32, DH = 20, FF = 1536;
constexpr float ATT_SCALE_LOG2E = 0.22360679774997896f * 1.4426950408889634f;
constexpr int IMG_HEAD_ELEMS = (SEQ / 8) * 192;

__device__ __align__(1024) bf16 g_img[3 * NH * IMG_HEAD_ELEMS];
__device__ __align__(1024) bf16 g_o[SEQ * DM];
__device__ __align__(1024) bf16 g_h[SEQ * DM];
__device__ float2 g_stats[SEQ * 8];
__device__ float g_cs[2 * FF];
__device__ int g_flag[4 * 16];
__device__ float2 g_rs[SEQ];
__device__ __align__(1024) bf16 g_hh[SEQ * FF];

#define TS(k, i)
#define PH(w, t, i)
__device__ __forceinline__ uint32_t smem_u32(const void* p) { return (uint32_t)__cvta_generic_to_shared(p); }
__device__ __forceinline__ void mbar_init(uint32_t bar, uint32_t cnt) {
  asm volatile("mbarrier.init.shared::cta.b64 [%0], %1;" ::"r"(bar), "r"(cnt) : "memory");
}
__device__ __forceinline__ void mbar_expect_tx(uint32_t bar, uint32_t bytes) {
  asm volatile("mbarrier.arrive.expect_tx.shared::cta.b64 _, [%0], %1;" ::"r"(bar), "r"(bytes) : "memory");
}
__device__ __forceinline__ void mbar_arrive(uint32_t bar) {
  asm volatile("mbarrier.arrive.shared::cta.b64 _, [%0];" ::"r"(bar) : "memory");
}
__device__ __forceinline__ void mbar_arrive_cluster(uint32_t bar, uint32_t cta) {
  asm volatile(
      "{\n.reg .b32 r;\nmapa.shared::cluster.u32 r, %0, %1;\n"
      "mbarrier.arrive.shared::cluster.b64 _, [r];\n}\n" ::"r"(bar), "r"(cta)
      : "memory");
}
__device__ __forceinline__ void mbar_wait(uint32_t bar, uint32_t parity) {
  asm volatile(
      "{\n.reg .pred p;\nLAB_WAIT:\n"
      "mbarrier.try_wait.parity.shared::cta.b64 p, [%0], %1;\n"
      "@p bra DONE;\nbra LAB_WAIT;\nDONE:\n}\n" ::"r"(bar), "r"(parity)
      : "memory");
}
__device__ __forceinline__ void mbar_wait_cluster(uint32_t bar, uint32_t parity) {
  asm volatile(
      "{\n.reg .pred p;\nLAB_WAIT:\n"
      "mbarrier.try_wait.parity.acquire.cluster.shared::cta.b64 p, [%0], %1;\n"
      "@p bra DONE;\nbra LAB_WAIT;\nDONE:\n}\n" ::"r"(bar), "r"(parity)
      : "memory");
}
__device__ __forceinline__ void fence_mbar_init() { asm volatile("fence.mbarrier_init.release.cluster;" ::: "memory"); }
__device__ __forceinline__ void fence_proxy_async() { asm volatile("fence.proxy.async.shared::cta;" ::: "memory"); }
__device__ __forceinline__ void cluster_sync_all() {
  asm volatile("barrier.cluster.arrive.release.aligned;\nbarrier.cluster.wait.acquire.aligned;" ::: "memory");
}
__device__ __forceinline__ void cluster_sync_relaxed() {
  asm volatile("barrier.cluster.arrive.relaxed.aligned;\nbarrier.cluster.wait.aligned;" ::: "memory");
}
__device__ __forceinline__ void named_bar_sync(int id, int n) { asm volatile("bar.sync %0, %1;" ::"r"(id), "r"(n) : "memory"); }
__device__ __forceinline__ bool wg_any(bool pred, int id) {
  uint32_t r;
  asm volatile("{\n.reg .pred p, q;\nsetp.ne.u32 p, %1, 0;\nbar.red.or.pred q, %2, 128, p;\nselp.u32 %0, 1, 0, q;\n}\n" : "=r"(r) : "r"((uint32_t)pred), "r"(id) : "memory");
  return r != 0;
}
__device__ __forceinline__ void fence_proxy_async_all() { asm volatile("fence.proxy.async;" ::: "memory"); }
__device__ __forceinline__ void flag_signal(int* f) {
  __threadfence();
  atomicAdd(f, 1);
}
__device__ __forceinline__ void flag_wait(const int* f, int target) {
  int v;
  unsigned spins = 0;
  do {
    asm volatile("ld.acquire.gpu.global.s32 %0, [%1];" : "=r"(v) : "l"(f) : "memory");
    if (++spins > (1u << 24)) __trap();
  } while (v < target);
}
__device__ __forceinline__ void pdl_launch() { asm volatile("griddepcontrol.launch_dependents;" ::: "memory"); }
__device__ __forceinline__ void pdl_wait() { asm volatile("griddepcontrol.wait;" ::: "memory"); }

__device__ __forceinline__ void tma_load_2d(uint32_t dst, const CUtensorMap* tm, int c0, int c1, uint32_t bar) {
  asm volatile(
      "cp.async.bulk.tensor.2d.shared::cluster.global.mbarrier::complete_tx::bytes [%0], [%1, {%3, %4}], [%2];" ::"r"(dst),
      "l"((uint64_t)tm), "r"(bar), "r"(c0), "r"(c1)
      : "memory");
}
__device__ __forceinline__ void tma_load_2d_mc(uint32_t dst, const CUtensorMap* tm, int c0, int c1, uint32_t bar, uint16_t mask) {
  asm volatile(
      "cp.async.bulk.tensor.2d.shared::cluster.global.mbarrier::complete_tx::bytes.multicast::cluster [%0], [%1, {%3, %4}], [%2], %5;" ::"r"(dst),
      "l"((uint64_t)tm), "r"(bar), "r"(c0), "r"(c1), "h"(mask)
      : "memory");
}
__device__ __forceinline__ void bulk_g2s(uint32_t dst, const void* src, uint32_t bytes, uint32_t bar) {
  asm volatile("cp.async.bulk.shared::cluster.global.mbarrier::complete_tx::bytes [%0], [%1], %2, [%3];" ::"r"(dst), "l"(src),
               "r"(bytes), "r"(bar)
               : "memory");
}
__device__ __forceinline__ void bulk_s2g(void* dst, uint32_t src, uint32_t bytes) {
  asm volatile("cp.async.bulk.global.shared::cta.bulk_group [%0], [%1], %2;" ::"l"(dst), "r"(src), "r"(bytes) : "memory");
}
__device__ __forceinline__ void tma_store_2d(const CUtensorMap* tm, uint32_t src, int c0, int c1) {
  asm volatile("cp.async.bulk.tensor.2d.global.shared::cta.bulk_group [%0, {%2, %3}], [%1];" ::"l"((uint64_t)tm), "r"(src), "r"(c0), "r"(c1) : "memory");
}
__device__ __forceinline__ void bulk_commit() { asm volatile("cp.async.bulk.commit_group;" ::: "memory"); }
__device__ __forceinline__ void bulk_wait_read() { asm volatile("cp.async.bulk.wait_group.read 0;" ::: "memory"); }
__device__ __forceinline__ void prefetch_l2(const void* p, uint32_t bytes) {
  asm volatile("cp.async.bulk.prefetch.L2.global [%0], %1;" ::"l"(p), "r"(bytes) : "memory");
}
__device__ __forceinline__ void bulk_wait_all() { asm volatile("cp.async.bulk.wait_group 0;" ::: "memory"); }
__device__ __forceinline__ void st_shared_b32(uint32_t addr, uint32_t v) { asm volatile("st.shared.b32 [%0], %1;" ::"r"(addr), "r"(v) : "memory"); }
__device__ __forceinline__ void st_shared_v2(uint32_t addr, uint32_t a, uint32_t b) { asm volatile("st.shared.v2.b32 [%0], {%1, %2};" ::"r"(addr), "r"(a), "r"(b) : "memory"); }
__device__ __forceinline__ void prefetch_tmap(const CUtensorMap* tm) {
  asm volatile("prefetch.tensormap [%0];" ::"l"((uint64_t)tm) : "memory");
}
__device__ __forceinline__ void wgmma_fence() { asm volatile("wgmma.fence.sync.aligned;" ::: "memory"); }
__device__ __forceinline__ void wgmma_commit() { asm volatile("wgmma.commit_group.sync.aligned;" ::: "memory"); }
template <int N>
__device__ __forceinline__ void wgmma_wait() { asm volatile("wgmma.wait_group.sync.aligned %0;" ::"n"(N) : "memory"); }

template <int N>
__device__ __forceinline__ void fence_regs(float (&r)[N]) {
#pragma unroll
  for (int i = 0; i < N; i++) asm volatile("" : "+f"(r[i])::"memory");
}
template <int N>
__device__ __forceinline__ void fence_regs(uint32_t (&r)[N]) {
#pragma unroll
  for (int i = 0; i < N; i++) asm volatile("" : "+r"(r[i])::"memory");
}
__device__ __forceinline__ uint64_t make_desc(uint32_t addr, uint32_t lbo, uint32_t sbo, uint32_t layout) {
  return (uint64_t)((addr & 0x3FFFF) >> 4) | ((uint64_t)((lbo & 0x3FFFF) >> 4) << 16) | ((uint64_t)((sbo & 0x3FFFF) >> 4) << 32) |
         ((uint64_t)layout << 62);
}
__device__ __forceinline__ uint32_t pack_bf16(float lo, float hi) {
  uint32_t r;
  asm("cvt.rn.bf16x2.f32 %0, %1, %2;" : "=r"(r) : "f"(hi), "f"(lo));
  return r;
}
__device__ __forceinline__ float bf16_round(float x) { return __bfloat162float(__float2bfloat16_rn(x)); }
__device__ __forceinline__ float bf_lo(uint32_t u) { return __uint_as_float(u << 16); }
__device__ __forceinline__ float bf_hi(uint32_t u) { return __uint_as_float(u & 0xffff0000u); }
__device__ __forceinline__ float ex2(float x) {
  float y;
  asm("ex2.approx.ftz.f32 %0, %1;" : "=f"(y) : "f"(x));
  return y;
}

__device__ __forceinline__ void wgmma_ss_n240_tb(float (&d)[120], uint64_t descA, uint64_t descB, int scaleD) {
  asm volatile("{\n.reg .pred p;\nsetp.ne.b32 p, %122, 0;\n"
    "wgmma.mma_async.sync.aligned.m64n240k16.f32.bf16.bf16 {%0, %1, %2, %3, %4, %5, %6, %7, %8, %9, %10, %11, %12, %13, %14, %15, %16, %17, %18, %19, %20, %21, %22, %23, %24, %25, %26, %27, %28, %29, %30, %31, %32, %33, %34, %35, %36, %37, %38, %39, %40, %41, %42, %43, %44, %45, %46, %47, %48, %49, %50, %51, %52, %53, %54, %55, %56, %57, %58, %59, %60, %61, %62, %63, %64, %65, %66, %67, %68, %69, %70, %71, %72, %73, %74, %75, %76, %77, %78, %79, %80, %81, %82, %83, %84, %85, %86, %87, %88, %89, %90, %91, %92, %93, %94, %95, %96, %97, %98, %99, %100, %101, %102, %103, %104, %105, %106, %107, %108, %109, %110, %111, %112, %113, %114, %115, %116, %117, %118, %119}, %120, %121, p, 1, 1, 0, 1;\n}\n"
    : "+f"(d[0]), "+f"(d[1]), "+f"(d[2]), "+f"(d[3]), "+f"(d[4]), "+f"(d[5]), "+f"(d[6]), "+f"(d[7]), "+f"(d[8]), "+f"(d[9]), "+f"(d[10]), "+f"(d[11]), "+f"(d[12]), "+f"(d[13]), "+f"(d[14]), "+f"(d[15]), "+f"(d[16]), "+f"(d[17]), "+f"(d[18]), "+f"(d[19]), "+f"(d[20]), "+f"(d[21]), "+f"(d[22]), "+f"(d[23]), "+f"(d[24]), "+f"(d[25]), "+f"(d[26]), "+f"(d[27]), "+f"(d[28]), "+f"(d[29]), "+f"(d[30]), "+f"(d[31]), "+f"(d[32]), "+f"(d[33]), "+f"(d[34]), "+f"(d[35]), "+f"(d[36]), "+f"(d[37]), "+f"(d[38]), "+f"(d[39]), "+f"(d[40]), "+f"(d[41]), "+f"(d[42]), "+f"(d[43]), "+f"(d[44]), "+f"(d[45]), "+f"(d[46]), "+f"(d[47]), "+f"(d[48]), "+f"(d[49]), "+f"(d[50]), "+f"(d[51]), "+f"(d[52]), "+f"(d[53]), "+f"(d[54]), "+f"(d[55]), "+f"(d[56]), "+f"(d[57]), "+f"(d[58]), "+f"(d[59]), "+f"(d[60]), "+f"(d[61]), "+f"(d[62]), "+f"(d[63]), "+f"(d[64]), "+f"(d[65]), "+f"(d[66]), "+f"(d[67]), "+f"(d[68]), "+f"(d[69]), "+f"(d[70]), "+f"(d[71]), "+f"(d[72]), "+f"(d[73]), "+f"(d[74]), "+f"(d[75]), "+f"(d[76]), "+f"(d[77]), "+f"(d[78]), "+f"(d[79]), "+f"(d[80]), "+f"(d[81]), "+f"(d[82]), "+f"(d[83]), "+f"(d[84]), "+f"(d[85]), "+f"(d[86]), "+f"(d[87]), "+f"(d[88]), "+f"(d[89]), "+f"(d[90]), "+f"(d[91]), "+f"(d[92]), "+f"(d[93]), "+f"(d[94]), "+f"(d[95]), "+f"(d[96]), "+f"(d[97]), "+f"(d[98]), "+f"(d[99]), "+f"(d[100]), "+f"(d[101]), "+f"(d[102]), "+f"(d[103]), "+f"(d[104]), "+f"(d[105]), "+f"(d[106]), "+f"(d[107]), "+f"(d[108]), "+f"(d[109]), "+f"(d[110]), "+f"(d[111]), "+f"(d[112]), "+f"(d[113]), "+f"(d[114]), "+f"(d[115]), "+f"(d[116]), "+f"(d[117]), "+f"(d[118]), "+f"(d[119])
    : "l"(descA), "l"(descB), "r"(scaleD));
}
__device__ __forceinline__ void wgmma_ss_n192_tb(float (&d)[96], uint64_t descA, uint64_t descB, int scaleD) {
  asm volatile("{\n.reg .pred p;\nsetp.ne.b32 p, %98, 0;\n"
    "wgmma.mma_async.sync.aligned.m64n192k16.f32.bf16.bf16 {%0, %1, %2, %3, %4, %5, %6, %7, %8, %9, %10, %11, %12, %13, %14, %15, %16, %17, %18, %19, %20, %21, %22, %23, %24, %25, %26, %27, %28, %29, %30, %31, %32, %33, %34, %35, %36, %37, %38, %39, %40, %41, %42, %43, %44, %45, %46, %47, %48, %49, %50, %51, %52, %53, %54, %55, %56, %57, %58, %59, %60, %61, %62, %63, %64, %65, %66, %67, %68, %69, %70, %71, %72, %73, %74, %75, %76, %77, %78, %79, %80, %81, %82, %83, %84, %85, %86, %87, %88, %89, %90, %91, %92, %93, %94, %95}, %96, %97, p, 1, 1, 0, 1;\n}\n"
    : "+f"(d[0]), "+f"(d[1]), "+f"(d[2]), "+f"(d[3]), "+f"(d[4]), "+f"(d[5]), "+f"(d[6]), "+f"(d[7]), "+f"(d[8]), "+f"(d[9]), "+f"(d[10]), "+f"(d[11]), "+f"(d[12]), "+f"(d[13]), "+f"(d[14]), "+f"(d[15]), "+f"(d[16]), "+f"(d[17]), "+f"(d[18]), "+f"(d[19]), "+f"(d[20]), "+f"(d[21]), "+f"(d[22]), "+f"(d[23]), "+f"(d[24]), "+f"(d[25]), "+f"(d[26]), "+f"(d[27]), "+f"(d[28]), "+f"(d[29]), "+f"(d[30]), "+f"(d[31]), "+f"(d[32]), "+f"(d[33]), "+f"(d[34]), "+f"(d[35]), "+f"(d[36]), "+f"(d[37]), "+f"(d[38]), "+f"(d[39]), "+f"(d[40]), "+f"(d[41]), "+f"(d[42]), "+f"(d[43]), "+f"(d[44]), "+f"(d[45]), "+f"(d[46]), "+f"(d[47]), "+f"(d[48]), "+f"(d[49]), "+f"(d[50]), "+f"(d[51]), "+f"(d[52]), "+f"(d[53]), "+f"(d[54]), "+f"(d[55]), "+f"(d[56]), "+f"(d[57]), "+f"(d[58]), "+f"(d[59]), "+f"(d[60]), "+f"(d[61]), "+f"(d[62]), "+f"(d[63]), "+f"(d[64]), "+f"(d[65]), "+f"(d[66]), "+f"(d[67]), "+f"(d[68]), "+f"(d[69]), "+f"(d[70]), "+f"(d[71]), "+f"(d[72]), "+f"(d[73]), "+f"(d[74]), "+f"(d[75]), "+f"(d[76]), "+f"(d[77]), "+f"(d[78]), "+f"(d[79]), "+f"(d[80]), "+f"(d[81]), "+f"(d[82]), "+f"(d[83]), "+f"(d[84]), "+f"(d[85]), "+f"(d[86]), "+f"(d[87]), "+f"(d[88]), "+f"(d[89]), "+f"(d[90]), "+f"(d[91]), "+f"(d[92]), "+f"(d[93]), "+f"(d[94]), "+f"(d[95])
    : "l"(descA), "l"(descB), "r"(scaleD));
}
__device__ __forceinline__ void wgmma_ss_n64_tb(float (&d)[32], uint64_t descA, uint64_t descB, int scaleD) {
  asm volatile("{\n.reg .pred p;\nsetp.ne.b32 p, %34, 0;\n"
    "wgmma.mma_async.sync.aligned.m64n64k16.f32.bf16.bf16 {%0, %1, %2, %3, %4, %5, %6, %7, %8, %9, %10, %11, %12, %13, %14, %15, %16, %17, %18, %19, %20, %21, %22, %23, %24, %25, %26, %27, %28, %29, %30, %31}, %32, %33, p, 1, 1, 0, 1;\n}\n"
    : "+f"(d[0]), "+f"(d[1]), "+f"(d[2]), "+f"(d[3]), "+f"(d[4]), "+f"(d[5]), "+f"(d[6]), "+f"(d[7]), "+f"(d[8]), "+f"(d[9]), "+f"(d[10]), "+f"(d[11]), "+f"(d[12]), "+f"(d[13]), "+f"(d[14]), "+f"(d[15]), "+f"(d[16]), "+f"(d[17]), "+f"(d[18]), "+f"(d[19]), "+f"(d[20]), "+f"(d[21]), "+f"(d[22]), "+f"(d[23]), "+f"(d[24]), "+f"(d[25]), "+f"(d[26]), "+f"(d[27]), "+f"(d[28]), "+f"(d[29]), "+f"(d[30]), "+f"(d[31])
    : "l"(descA), "l"(descB), "r"(scaleD));
}
__device__ __forceinline__ void wgmma_ss_n16_tb(float (&d)[8], uint64_t descA, uint64_t descB, int scaleD) {
  asm volatile("{\n.reg .pred p;\nsetp.ne.b32 p, %10, 0;\n"
    "wgmma.mma_async.sync.aligned.m64n16k16.f32.bf16.bf16 {%0, %1, %2, %3, %4, %5, %6, %7}, %8, %9, p, 1, 1, 0, 1;\n}\n"
    : "+f"(d[0]), "+f"(d[1]), "+f"(d[2]), "+f"(d[3]), "+f"(d[4]), "+f"(d[5]), "+f"(d[6]), "+f"(d[7])
    : "l"(descA), "l"(descB), "r"(scaleD));
}
__device__ __forceinline__ void wgmma_rs_n128(float (&d)[64], uint32_t a0, uint32_t a1, uint32_t a2, uint32_t a3, uint64_t descB, int scaleD) {
  asm volatile("{\n.reg .pred p;\nsetp.ne.b32 p, %69, 0;\n"
    "wgmma.mma_async.sync.aligned.m64n128k16.f32.bf16.bf16 {%0, %1, %2, %3, %4, %5, %6, %7, %8, %9, %10, %11, %12, %13, %14, %15, %16, %17, %18, %19, %20, %21, %22, %23, %24, %25, %26, %27, %28, %29, %30, %31, %32, %33, %34, %35, %36, %37, %38, %39, %40, %41, %42, %43, %44, %45, %46, %47, %48, %49, %50, %51, %52, %53, %54, %55, %56, %57, %58, %59, %60, %61, %62, %63}, {%64, %65, %66, %67}, %68, p, 1, 1, 0;\n}\n"
    : "+f"(d[0]), "+f"(d[1]), "+f"(d[2]), "+f"(d[3]), "+f"(d[4]), "+f"(d[5]), "+f"(d[6]), "+f"(d[7]), "+f"(d[8]), "+f"(d[9]), "+f"(d[10]), "+f"(d[11]), "+f"(d[12]), "+f"(d[13]), "+f"(d[14]), "+f"(d[15]), "+f"(d[16]), "+f"(d[17]), "+f"(d[18]), "+f"(d[19]), "+f"(d[20]), "+f"(d[21]), "+f"(d[22]), "+f"(d[23]), "+f"(d[24]), "+f"(d[25]), "+f"(d[26]), "+f"(d[27]), "+f"(d[28]), "+f"(d[29]), "+f"(d[30]), "+f"(d[31]), "+f"(d[32]), "+f"(d[33]), "+f"(d[34]), "+f"(d[35]), "+f"(d[36]), "+f"(d[37]), "+f"(d[38]), "+f"(d[39]), "+f"(d[40]), "+f"(d[41]), "+f"(d[42]), "+f"(d[43]), "+f"(d[44]), "+f"(d[45]), "+f"(d[46]), "+f"(d[47]), "+f"(d[48]), "+f"(d[49]), "+f"(d[50]), "+f"(d[51]), "+f"(d[52]), "+f"(d[53]), "+f"(d[54]), "+f"(d[55]), "+f"(d[56]), "+f"(d[57]), "+f"(d[58]), "+f"(d[59]), "+f"(d[60]), "+f"(d[61]), "+f"(d[62]), "+f"(d[63])
    : "r"(a0), "r"(a1), "r"(a2), "r"(a3), "l"(descB), "r"(scaleD));
}
__device__ __forceinline__ void wgmma_rs_n64(float (&d)[32], uint32_t a0, uint32_t a1, uint32_t a2, uint32_t a3, uint64_t descB, int scaleD) {
  asm volatile("{\n.reg .pred p;\nsetp.ne.b32 p, %37, 0;\n"
    "wgmma.mma_async.sync.aligned.m64n64k16.f32.bf16.bf16 {%0, %1, %2, %3, %4, %5, %6, %7, %8, %9, %10, %11, %12, %13, %14, %15, %16, %17, %18, %19, %20, %21, %22, %23, %24, %25, %26, %27, %28, %29, %30, %31}, {%32, %33, %34, %35}, %36, p, 1, 1, 0;\n}\n"
    : "+f"(d[0]), "+f"(d[1]), "+f"(d[2]), "+f"(d[3]), "+f"(d[4]), "+f"(d[5]), "+f"(d[6]), "+f"(d[7]), "+f"(d[8]), "+f"(d[9]), "+f"(d[10]), "+f"(d[11]), "+f"(d[12]), "+f"(d[13]), "+f"(d[14]), "+f"(d[15]), "+f"(d[16]), "+f"(d[17]), "+f"(d[18]), "+f"(d[19]), "+f"(d[20]), "+f"(d[21]), "+f"(d[22]), "+f"(d[23]), "+f"(d[24]), "+f"(d[25]), "+f"(d[26]), "+f"(d[27]), "+f"(d[28]), "+f"(d[29]), "+f"(d[30]), "+f"(d[31])
    : "r"(a0), "r"(a1), "r"(a2), "r"(a3), "l"(descB), "r"(scaleD));
}
__device__ __forceinline__ void wgmma_rs_n24_tb(float (&d)[12], uint32_t a0, uint32_t a1, uint32_t a2, uint32_t a3, uint64_t descB, int scaleD) {
  asm volatile("{\n.reg .pred p;\nsetp.ne.b32 p, %17, 0;\n"
    "wgmma.mma_async.sync.aligned.m64n24k16.f32.bf16.bf16 {%0, %1, %2, %3, %4, %5, %6, %7, %8, %9, %10, %11}, {%12, %13, %14, %15}, %16, p, 1, 1, 1;\n}\n"
    : "+f"(d[0]), "+f"(d[1]), "+f"(d[2]), "+f"(d[3]), "+f"(d[4]), "+f"(d[5]), "+f"(d[6]), "+f"(d[7]), "+f"(d[8]), "+f"(d[9]), "+f"(d[10]), "+f"(d[11])
    : "r"(a0), "r"(a1), "r"(a2), "r"(a3), "l"(descB), "r"(scaleD));
}

constexpr int GT = 384;

__device__ __forceinline__ void release_stage(uint32_t bar, bool leader) {
  if (leader) {
    mbar_arrive_cluster(bar, 0);
    mbar_arrive_cluster(bar, 1);
  }
}

__device__ __forceinline__ float2 ln_row_stats(const bf16* __restrict__ xin, int l16) {
  const uint4* src = reinterpret_cast<const uint4*>(xin);
  uint4 v[5];
#pragma unroll
  for (int j = 0; j < 5; j++) v[j] = __ldg(src + j * 16 + l16);
  float s0 = 0.f, s1 = 0.f, s2 = 0.f, s3 = 0.f;
#pragma unroll
  for (int j = 0; j < 5; j++) {
    s0 += bf_lo(v[j].x) + bf_hi(v[j].x);
    s1 += bf_lo(v[j].y) + bf_hi(v[j].y);
    s2 += bf_lo(v[j].z) + bf_hi(v[j].z);
    s3 += bf_lo(v[j].w) + bf_hi(v[j].w);
  }
  float mean = (s0 + s1) + (s2 + s3);
#pragma unroll
  for (int o = 1; o < 16; o <<= 1) mean += __shfl_xor_sync(0xffffffffu, mean, o);
  mean *= (1.0f / DM);
  s0 = s1 = s2 = s3 = 0.f;
#pragma unroll
  for (int j = 0; j < 5; j++) {
    float d;
    d = bf_lo(v[j].x) - mean; s0 = fmaf(d, d, s0);
    d = bf_hi(v[j].x) - mean; s1 = fmaf(d, d, s1);
    d = bf_lo(v[j].y) - mean; s2 = fmaf(d, d, s2);
    d = bf_hi(v[j].y) - mean; s3 = fmaf(d, d, s3);
    d = bf_lo(v[j].z) - mean; s0 = fmaf(d, d, s0);
    d = bf_hi(v[j].z) - mean; s1 = fmaf(d, d, s1);
    d = bf_lo(v[j].w) - mean; s2 = fmaf(d, d, s2);
    d = bf_hi(v[j].w) - mean; s3 = fmaf(d, d, s3);
  }
  float sq = (s0 + s1) + (s2 + s3);
#pragma unroll
  for (int o = 1; o < 16; o <<= 1) sq += __shfl_xor_sync(0xffffffffu, sq, o);
  const float var_b = bf16_round(sq * (1.0f / DM));
  const float den = bf16_round(sqrtf(bf16_round(var_b + 1e-5f)));
  return make_float2(bf16_round(mean), __frcp_rn(den));
}

constexpr int LG_STAGES = 5;
constexpr int QKV_STAGE = 8192 + 4 * 4096;
constexpr int GLU_STAGE = 8192 + 6 * 4096;

template <int WG>
__device__ __forceinline__ void qkv_mainloop(float (&acc)[120], uint32_t sbase, uint32_t sBar, bool leader) {
  constexpr int STAGE_BYTES = QKV_STAGE, NST = LG_STAGES;
  const uint64_t da_base = make_desc(sbase + WG * 4096, 16, 512, 2);
  const uint64_t db_base = make_desc(sbase + 8192, 4096, 1024, 1);
#pragma unroll 1
  for (int r = 0; r < 20 / NST; r++) {
#pragma unroll
    for (int s = 0; s < NST; s++) {
      mbar_wait(sBar + 8 * s, r & 1);
      wgmma_fence();
#pragma unroll
      for (int ks = 0; ks < 2; ks++)
        wgmma_ss_n240_tb(acc, da_base + (uint64_t)((s * STAGE_BYTES + ks * 32) >> 4), db_base + (uint64_t)((s * STAGE_BYTES + ks * 2048) >> 4), 1);
      wgmma_commit();
      wgmma_wait<1>();
      release_stage(sBar + 8 * (NST + (s + NST - 1) % NST), leader && (s > 0 || r > 0));
    }
  }
}
template <int WG>
__device__ __forceinline__ void glu_mainloop(float (&accg)[96], float (&accu)[96], uint32_t sbase, uint32_t sBar, bool leader) {
  constexpr int STAGE_BYTES = GLU_STAGE, NST = LG_STAGES;
  const uint64_t da_base = make_desc(sbase + WG * 4096, 16, 512, 2);
  const uint64_t db_base = make_desc(sbase + 8192, 4096, 1024, 1);
#pragma unroll 1
  for (int r = 0; r < 20 / NST; r++) {
#pragma unroll
    for (int s = 0; s < NST; s++) {
      mbar_wait(sBar + 8 * s, r & 1);
      wgmma_fence();
#pragma unroll
      for (int ks = 0; ks < 2; ks++) {
        const uint64_t da = da_base + (uint64_t)((s * STAGE_BYTES + ks * 32) >> 4);
        wgmma_ss_n192_tb(accg, da, db_base + (uint64_t)((s * STAGE_BYTES + ks * 2048) >> 4), 1);
        wgmma_ss_n192_tb(accu, da, db_base + (uint64_t)((s * STAGE_BYTES + 3 * 4096 + ks * 2048) >> 4), 1);
      }
      wgmma_commit();
      wgmma_wait<1>();
      release_stage(sBar + 8 * (NST + (s + NST - 1) % NST), leader && (s > 0 || r > 0));
    }
  }
}
constexpr int RG_STAGE_BYTES = 16384 + 8192 + 2048;
template <int NKB, int NST, int WG>
__device__ __forceinline__ void res_mainloop(float (&acc0)[32], float (&acc1)[8], uint32_t sbase, uint32_t sBar, bool leader) {
  const uint64_t da_base = make_desc(sbase + WG * 8192, 16, 1024, 1);
  const uint64_t db0_base = make_desc(sbase + 16384, 8192, 1024, 1);
  const uint64_t db1_base = make_desc(sbase + 16384 + 8192, 2048, 256, 3);
#pragma unroll 1
  for (int r = 0; r < NKB / NST; r++) {
#pragma unroll
    for (int s = 0; s < NST; s++) {
      const uint64_t so = (uint64_t)(s * (RG_STAGE_BYTES >> 4));
      mbar_wait(sBar + 8 * s, r & 1);
      wgmma_fence();
#pragma unroll
      for (int ks = 0; ks < 4; ks++) {
        wgmma_ss_n64_tb(acc0, da_base + so + ks * 2, db0_base + so + ks * 128, 1);
        wgmma_ss_n16_tb(acc1, da_base + so + ks * 2, db1_base + so + ks * 32, 1);
      }
      wgmma_commit();
      wgmma_wait<1>();
      release_stage(sBar + 8 * (NST + (s + NST - 1) % NST), leader && (s > 0 || r > 0));
    }
  }
}

constexpr int KA_CS = LG_STAGES * QKV_STAGE + 128;
constexpr int KA_SMEM = KA_CS + 1024 + 3072 + 1024;

__global__ void __launch_bounds__(GT, 1)
qkv_kernel(const __grid_constant__ CUtensorMap tmA, const __grid_constant__ CUtensorMap tmB, const bf16* __restrict__ x,
           const bf16* __restrict__ wqkv) {
  constexpr int STAGE_BYTES = QKV_STAGE, NST = LG_STAGES, NKB = 20;
  extern __shared__ uint8_t smem_raw[];
  const uint32_t sbase = (smem_u32(smem_raw) + 1023u) & ~1023u;
  const uint32_t sBar = sbase + NST * STAGE_BYTES;
  const int tid = threadIdx.x, warp = tid >> 5, lane = tid & 31;
  const int rank = blockIdx.x & 1;
  const int pair = blockIdx.x >> 1;
  const int n_blk = pair & 7;
  const int m_blk = (pair >> 3) * 2 + rank;
  TS(0, 0);
  if (tid == 256) {
    prefetch_tmap(&tmA);
    prefetch_tmap(&tmB);
  }
  if (tid == 0) {
    for (int s = 0; s < NST; s++) {
      mbar_init(sBar + 8 * s, 1);
      mbar_init(sBar + 8 * (NST + s), 6);
    }
    fence_mbar_init();
    if (blockIdx.x < 32) g_flag[16 + blockIdx.x] = 0;
  }
  pdl_launch();
  cluster_sync_all();

  if (warp >= 8) {
    asm volatile("setmaxnreg.dec.sync.aligned.u32 56;");
    if (warp >= 9) {
      const int t96 = tid - 288;
      const int cc = t96 % 30, rg = t96 / 30;
      float* red = reinterpret_cast<float*>(smem_raw + (sbase - smem_u32(smem_raw)) + KA_CS + 1024);
      if (warp == 9) {
        named_bar_sync(5, 288);
        if (lane == 0) flag_signal(&g_flag[m_blk]);
        __syncwarp();
      }
      float a[8];
#pragma unroll
      for (int i = 0; i < 8; i++) a[i] = 0.f;
#pragma unroll 1
      for (int kb = 0; kb < NKB; kb++) {
        const int s = kb % NST;
        mbar_wait(sBar + 8 * s, (kb / NST) & 1);
        if (rg < 3) {
          const uint32_t base = sbase + s * STAGE_BYTES + 8192 + (cc >> 3) * 4096;
#pragma unroll
          for (int r = 0; r < 11; r++) {
            const int row = rg + r * 3;
            if (row < 32) {
              uint4 v;
              asm volatile("ld.shared.v4.b32 {%0, %1, %2, %3}, [%4];" : "=r"(v.x), "=r"(v.y), "=r"(v.z), "=r"(v.w) : "r"(base + row * 128 + (((cc & 7) ^ (row & 7)) << 4)));
              a[0] += bf_lo(v.x); a[1] += bf_hi(v.x); a[2] += bf_lo(v.y); a[3] += bf_hi(v.y);
              a[4] += bf_lo(v.z); a[5] += bf_hi(v.z); a[6] += bf_lo(v.w); a[7] += bf_hi(v.w);
            }
          }
        }
        named_bar_sync(4, 96);
        release_stage(sBar + 8 * (NST + s), t96 == 0);
      }
      if (rg < 3) {
#pragma unroll
        for (int i = 0; i < 8; i++) red[rg * 240 + cc * 8 + i] = a[i];
      }
      if (t96 == 0) flag_wait(&g_flag[m_blk], 8);
      named_bar_sync(4, 96);
      float* cs_s = reinterpret_cast<float*>(smem_raw + (sbase - smem_u32(smem_raw)) + KA_CS);
      for (int c = t96; c < 240; c += 96) cs_s[c] = (red[c] + red[240 + c]) + red[480 + c];
      named_bar_sync(6, 352);
    }
    if (tid == 256) {
      auto issue_b = [&](int kb) {
        const int s = kb % NST;
        const uint32_t full = sBar + 8 * s;
        mbar_expect_tx(full, STAGE_BYTES);
        const uint32_t dst = sbase + s * STAGE_BYTES + 8192;
#pragma unroll
        for (int j = 0; j < 2; j++) {
          const int sl = rank * 2 + j;
          tma_load_2d_mc(dst + sl * 4096, &tmB, n_blk * 240 + sl * 64, kb * 32, full, (uint16_t)3);
        }
      };
      for (int kb = 0; kb < NKB; kb++) {
        const int s = kb % NST;
        if (kb >= NST) mbar_wait(sBar + 8 * (NST + s), ((kb / NST) & 1) ^ 1);
        issue_b(kb);
        tma_load_2d(sbase + s * STAGE_BYTES, &tmA, kb * 32, m_blk * 128, sBar + 8 * s);
      }
    }
  } else {
    asm volatile("setmaxnreg.inc.sync.aligned.u32 224;");
    const int wg = __shfl_sync(0xffffffffu, warp >> 2, 0);
    const int wwarp = warp & 3;
    {
      const int row = m_blk * 128 + n_blk * 16 + warp * 2 + (lane >> 4);
      const float2 rs = ln_row_stats(x + (size_t)row * DM, lane & 15);
      if ((lane & 15) == 0) g_rs[row] = rs;
      asm volatile("bar.arrive 5, 288;" ::: "memory");
    }
    TS(0, 1);
    mbar_wait(sBar, 0);
    TS(0, 3);
    float acc[120];
#pragma unroll
    for (int i = 0; i < 120; i++) acc[i] = 0.f;
    if (wg == 0) qkv_mainloop<0>(acc, sbase, sBar, (tid & 127) == 0);
    else qkv_mainloop<1>(acc, sbase, sBar, (tid & 127) == 0);
    wgmma_wait<0>();
    fence_regs(acc);
    TS(0, 4);
    const int g = lane >> 2, c4 = lane & 3;
    float* cs_s = reinterpret_cast<float*>(smem_raw + (sbase - smem_u32(smem_raw)) + KA_CS);
    named_bar_sync(6, 352);
    const float2 rs0 = g_rs[m_blk * 128 + wg * 64 + wwarp * 16 + g], rs1 = g_rs[m_blk * 128 + wg * 64 + wwarp * 16 + g + 8];
    const uint32_t stg = sbase + wg * (12 * 3072) + (wwarp * 2) * 384 + g * 16;
    const int hbase = n_blk * 12;
#pragma unroll
    for (int j = 0; j < 30; j++) {
      const int cb = (j * 8) % 20;
      const int hb = (j * 8) / 20;
      int d = cb + c4 * 2;
      int hl = hb;
      if (cb == 16 && c4 >= 2) { d -= 20; hl += 1; }
      const uint32_t a0 = stg + hl * 3072 + (d >> 3) * 128 + (d & 7) * 2;
      const int hg = hbase + hl;
      const float sc = hg < 32 ? ATT_SCALE_LOG2E : 1.0f;
      const float2 cc = *reinterpret_cast<const float2*>(cs_s + j * 8 + c4 * 2);
      const float i0 = rs0.y * sc, i1 = rs1.y * sc;
      st_shared_b32(a0, pack_bf16(fmaf(-rs0.x, cc.x, acc[4 * j]) * i0, fmaf(-rs0.x, cc.y, acc[4 * j + 1]) * i0));
      st_shared_b32(a0 + 384, pack_bf16(fmaf(-rs1.x, cc.x, acc[4 * j + 2]) * i1, fmaf(-rs1.x, cc.y, acc[4 * j + 3]) * i1));
      if (d == 18) {
        const uint32_t pad0 = hg < 32 ? 0u : (hg < 64 ? 0x3f803f80u : 0x00003f80u);
        const uint32_t pad1 = (hg >= 32 && hg < 64) ? 0x00003f80u : 0u;
        st_shared_v2(a0 + 4, pad0, pad1);
        st_shared_v2(a0 + 388, pad0, pad1);
      }
      if (j % 10 == 9) {
        fence_proxy_async();
        named_bar_sync(1 + wg, 128);
        if ((tid & 127) < 4) {
          const int hs = (j / 10) * 4 + (tid & 127);
          bf16* dst = g_img + (size_t)(hbase + hs) * IMG_HEAD_ELEMS + (size_t)(m_blk * 16 + wg * 8) * 192;
          bulk_s2g(dst, sbase + wg * (12 * 3072) + hs * 3072, 3072);
          bulk_commit();
        }
      }
    }
    if ((tid & 127) < 4) bulk_wait_read();
  }
  __syncwarp();
  TS(0, 5);
  cluster_sync_relaxed();
  TS(0, 6);
}

constexpr int KC_NST1 = 5, KC_NST3 = 6;
constexpr int KC_STAGING = 160 * 1024;
constexpr int KC_BAR = KC_STAGING + 48 * 1024;
constexpr int KC_CS = KC_BAR + 512;
constexpr int KC_SMEM = KC_CS + 1536 + 1024;

__global__ void __launch_bounds__(GT, 1)
mlp_kernel(const __grid_constant__ CUtensorMap tmO, const __grid_constant__ CUtensorMap tmWo64, const __grid_constant__ CUtensorMap tmWo16,
           const __grid_constant__ CUtensorMap tmH, const __grid_constant__ CUtensorMap tmWg, const __grid_constant__ CUtensorMap tmWu,
           const __grid_constant__ CUtensorMap tmHHs, const __grid_constant__ CUtensorMap tmHH, const __grid_constant__ CUtensorMap tmWd64,
           const __grid_constant__ CUtensorMap tmWd16, const __grid_constant__ CUtensorMap tmHs, const __grid_constant__ CUtensorMap tmOut,
           const bf16* __restrict__ x) {
  extern __shared__ uint8_t smem_raw[];
  const uint32_t sbase = (smem_u32(smem_raw) + 1023u) & ~1023u;
  const uint32_t bar1 = sbase + KC_BAR;
  const uint32_t bar2 = bar1 + 128;
  const uint32_t bar3 = bar2 + 128;
  const uint32_t barD = bar3 + 128;
  const int tid = threadIdx.x, warp = tid >> 5, lane = tid & 31;
  const int rank = blockIdx.x & 1;
  const int pair = blockIdx.x >> 1;
  const int j_blk = pair & 7;
  const int m_blk = (pair >> 3) * 2 + rank;
  const int n0 = j_blk * 80;
  TS(2, 0);
  if (tid == 256) {
    prefetch_tmap(&tmO); prefetch_tmap(&tmWo64); prefetch_tmap(&tmWo16); prefetch_tmap(&tmH); prefetch_tmap(&tmWg);
    prefetch_tmap(&tmWu); prefetch_tmap(&tmHHs); prefetch_tmap(&tmHH); prefetch_tmap(&tmWd64); prefetch_tmap(&tmWd16);
    prefetch_tmap(&tmHs); prefetch_tmap(&tmOut);
  }
  if (tid == 0) {
    for (int s = 0; s < 5; s++) {
      mbar_init(bar1 + 8 * s, 1); mbar_init(bar1 + 8 * (5 + s), 4);
      mbar_init(bar2 + 8 * s, 1); mbar_init(bar2 + 8 * (5 + s), 4);
    }
    for (int s = 0; s < 6; s++) { mbar_init(bar3 + 8 * s, 1); mbar_init(bar3 + 8 * (6 + s), 4); }
    mbar_init(barD, 4); mbar_init(barD + 8, 4);
    fence_mbar_init();
  }
  cluster_sync_all();

  if (warp >= 8) {
    asm volatile("setmaxnreg.dec.sync.aligned.u32 40;");
    if (tid == 256) {
      auto issue_b80 = [&](const CUtensorMap* t64, const CUtensorMap* t16, uint32_t bars, int nst, int kb) {
        const int s = kb % nst;
        const uint32_t full = bars + 8 * s;
        const uint32_t st = sbase + s * RG_STAGE_BYTES;
        mbar_expect_tx(full, RG_STAGE_BYTES);
        tma_load_2d_mc(st + 16384 + rank * 4096, t64, n0, kb * 64 + rank * 32, full, (uint16_t)3);
        tma_load_2d_mc(st + 16384 + 8192 + rank * 1024, t16, n0 + 64, kb * 64 + rank * 32, full, (uint16_t)3);
      };
      for (int kb = 0; kb < KC_NST1; kb++) issue_b80(&tmWo64, &tmWo16, bar1, KC_NST1, kb);
      pdl_wait();
      for (int kb = 0; kb < 10; kb++) {
        const int s = kb % KC_NST1;
        if (kb >= KC_NST1) {
          mbar_wait(bar1 + 8 * (KC_NST1 + s), ((kb / KC_NST1) & 1) ^ 1);
          issue_b80(&tmWo64, &tmWo16, bar1, KC_NST1, kb);
        }
        tma_load_2d(sbase + s * RG_STAGE_BYTES, &tmO, kb * 64, m_blk * 128, bar1 + 8 * s);
      }
      auto issue_bglu = [&](int kb) {
        const int s = kb % LG_STAGES;
        const uint32_t full = bar2 + 8 * s;
        mbar_expect_tx(full, GLU_STAGE);
        const uint32_t dst = sbase + s * GLU_STAGE + 8192;
#pragma unroll
        for (int j = 0; j < 3; j++)
          tma_load_2d_mc(dst + (rank * 3 + j) * 4096, rank == 0 ? &tmWg : &tmWu, j_blk * 192 + j * 64, kb * 32, full, (uint16_t)3);
      };
      mbar_wait(barD, 0);
      for (int kb = 0; kb < LG_STAGES; kb++) issue_bglu(kb);
      flag_wait(&g_flag[16 + m_blk], 16);
      fence_proxy_async_all();
      for (int kb = 0; kb < 20; kb++) {
        const int s = kb % LG_STAGES;
        if (kb >= LG_STAGES) {
          mbar_wait(bar2 + 8 * (LG_STAGES + s), ((kb / LG_STAGES) & 1) ^ 1);
          issue_bglu(kb);
        }
        tma_load_2d(sbase + s * GLU_STAGE, &tmH, kb * 32, m_blk * 128, bar2 + 8 * s);
      }
      mbar_wait(barD + 8, 0);
      for (int kb = 0; kb < KC_NST3; kb++) issue_b80(&tmWd64, &tmWd16, bar3, KC_NST3, kb);
      flag_wait(&g_flag[32 + m_blk], 16);
      fence_proxy_async_all();
      for (int kb = 0; kb < 24; kb++) {
        const int s = kb % KC_NST3;
        if (kb >= KC_NST3) {
          mbar_wait(bar3 + 8 * (KC_NST3 + s), ((kb / KC_NST3) & 1) ^ 1);
          issue_b80(&tmWd64, &tmWd16, bar3, KC_NST3, kb);
        }
        tma_load_2d(sbase + s * RG_STAGE_BYTES, &tmHH, kb * 64, m_blk * 128, bar3 + 8 * s);
      }
    }
  } else {
    asm volatile("setmaxnreg.inc.sync.aligned.u32 232;");
    const int wg = __shfl_sync(0xffffffffu, warp >> 2, 0);
    const int wwarp = warp & 3;
    const int g = lane >> 2, c4 = lane & 3;
    const int row0 = m_blk * 128 + wg * 64 + wwarp * 16 + g;
    const bool leader = (tid & 127) == 0;
    const uint32_t stg80_base = sbase + KC_STAGING + wg * 24576;
    const uint32_t stg80 = stg80_base + (wwarp * 16 + g) * 160 + c4 * 4;
    {
      uint32_t res[20];
#pragma unroll
      for (int j = 0; j < 10; j++) {
        res[2 * j] = __ldg(reinterpret_cast<const uint32_t*>(x + (size_t)row0 * DM + n0 + j * 8 + c4 * 2));
        res[2 * j + 1] = __ldg(reinterpret_cast<const uint32_t*>(x + (size_t)(row0 + 8) * DM + n0 + j * 8 + c4 * 2));
      }
      float acc0[32], acc1[8];
#pragma unroll
      for (int i = 0; i < 32; i++) acc0[i] = 0.f;
#pragma unroll
      for (int i = 0; i < 8; i++) acc1[i] = 0.f;
      TS(2, 1);
      if (wg == 0) res_mainloop<10, KC_NST1, 0>(acc0, acc1, sbase, bar1, leader);
      else res_mainloop<10, KC_NST1, 1>(acc0, acc1, sbase, bar1, leader);
      wgmma_wait<0>();
      fence_regs(acc0); fence_regs(acc1);
      release_stage(barD, leader);
      TS(2, 4);
      float sum0 = 0.f, sum1 = 0.f;
#pragma unroll
      for (int j = 0; j < 10; j++) {
        const uint32_t a01 = j < 8 ? pack_bf16(acc0[4 * j], acc0[4 * j + 1]) : pack_bf16(acc1[4 * (j - 8)], acc1[4 * (j - 8) + 1]);
        const uint32_t a23 = j < 8 ? pack_bf16(acc0[4 * j + 2], acc0[4 * j + 3]) : pack_bf16(acc1[4 * (j - 8) + 2], acc1[4 * (j - 8) + 3]);
        res[2 * j] = pack_bf16(bf_lo(res[2 * j]) + bf_lo(a01), bf_hi(res[2 * j]) + bf_hi(a01));
        res[2 * j + 1] = pack_bf16(bf_lo(res[2 * j + 1]) + bf_lo(a23), bf_hi(res[2 * j + 1]) + bf_hi(a23));
        st_shared_b32(stg80 + j * 16, res[2 * j]);
        st_shared_b32(stg80 + 8 * 160 + j * 16, res[2 * j + 1]);
        sum0 += bf_lo(res[2 * j]) + bf_hi(res[2 * j]);
        sum1 += bf_lo(res[2 * j + 1]) + bf_hi(res[2 * j + 1]);
      }
      sum0 += __shfl_xor_sync(0xffffffffu, sum0, 1); sum1 += __shfl_xor_sync(0xffffffffu, sum1, 1);
      sum0 += __shfl_xor_sync(0xffffffffu, sum0, 2); sum1 += __shfl_xor_sync(0xffffffffu, sum1, 2);
      const float mu0 = sum0 * (1.0f / 80.0f), mu1 = sum1 * (1.0f / 80.0f);
      float q0 = 0.f, q1 = 0.f;
#pragma unroll
      for (int j = 0; j < 10; j++) {
        float d;
        d = bf_lo(res[2 * j]) - mu0; q0 = fmaf(d, d, q0);
        d = bf_hi(res[2 * j]) - mu0; q0 = fmaf(d, d, q0);
        d = bf_lo(res[2 * j + 1]) - mu1; q1 = fmaf(d, d, q1);
        d = bf_hi(res[2 * j + 1]) - mu1; q1 = fmaf(d, d, q1);
      }
      q0 += __shfl_xor_sync(0xffffffffu, q0, 1); q1 += __shfl_xor_sync(0xffffffffu, q1, 1);
      q0 += __shfl_xor_sync(0xffffffffu, q0, 2); q1 += __shfl_xor_sync(0xffffffffu, q1, 2);
      if (c4 == 0) {
        g_stats[row0 * 8 + j_blk] = make_float2(mu0, q0);
        g_stats[(row0 + 8) * 8 + j_blk] = make_float2(mu1, q1);
      }
      fence_proxy_async();
      named_bar_sync(1 + wg, 128);
      if (leader) {
        tma_store_2d(&tmHs, stg80_base, n0, m_blk * 128 + wg * 64);
        bulk_commit();
        bulk_wait_all();
        fence_proxy_async_all();
        flag_signal(&g_flag[16 + m_blk]);
      }
      TS(2, 5);
    }
    {
      pdl_wait();
      {
        float* cs_s = reinterpret_cast<float*>(smem_raw + (sbase - smem_u32(smem_raw)) + KC_CS);
        for (int i = tid; i < 384; i += 256) cs_s[i] = g_cs[(i >= 192 ? FF - 192 : 0) + j_blk * 192 + i];
        named_bar_sync(3, 256);
      }
      flag_wait(&g_flag[16 + m_blk], 16);
      float mb[2], iv[2];
#pragma unroll
      for (int h = 0; h < 2; h++) {
        const float4* sp = reinterpret_cast<const float4*>(g_stats + (row0 + 8 * h) * 8);
        const float4 p0 = sp[0], p1 = sp[1], p2 = sp[2], p3 = sp[3];
        const float mean = (((p0.x + p0.z) + (p1.x + p1.z)) + ((p2.x + p2.z) + (p3.x + p3.z))) * 0.125f;
        float m2 = ((p0.y + p0.w) + (p1.y + p1.w)) + ((p2.y + p2.w) + (p3.y + p3.w));
        float dd = 0.f, d;
        d = p0.x - mean; dd = fmaf(d, d, dd); d = p0.z - mean; dd = fmaf(d, d, dd);
        d = p1.x - mean; dd = fmaf(d, d, dd); d = p1.z - mean; dd = fmaf(d, d, dd);
        d = p2.x - mean; dd = fmaf(d, d, dd); d = p2.z - mean; dd = fmaf(d, d, dd);
        d = p3.x - mean; dd = fmaf(d, d, dd); d = p3.z - mean; dd = fmaf(d, d, dd);
        m2 = fmaf(dd, 80.0f, m2);
        const float var_b = bf16_round(m2 * (1.0f / DM));
        const float den = bf16_round(sqrtf(bf16_round(var_b + 1e-5f)));
        iv[h] = __frcp_rn(den);
        mb[h] = bf16_round(mean);
      }
      float accg[96], accu[96];
#pragma unroll
      for (int i = 0; i < 96; i++) { accg[i] = 0.f; accu[i] = 0.f; }
      TS(3, 3);
      if (wg == 0) glu_mainloop<0>(accg, accu, sbase, bar2, leader);
      else glu_mainloop<1>(accg, accu, sbase, bar2, leader);
      wgmma_wait<0>();
      fence_regs(accg); fence_regs(accu);
      release_stage(barD + 8, leader);
      TS(3, 4);
      const uint32_t stg = sbase + KC_STAGING + wg * 24576 + (wwarp * 16 + g) * 128 + c4 * 4;
      const float* csg = reinterpret_cast<const float*>(smem_raw + (sbase - smem_u32(smem_raw)) + KC_CS) + c4 * 2;
      const float nm0 = -mb[0] * iv[0], nm1 = -mb[1] * iv[1];
#pragma unroll
      for (int sl = 0; sl < 3; sl++) {
#pragma unroll
        for (int jj = 0; jj < 8; jj++) {
          const int j = sl * 8 + jj;
          const float2 cg = *reinterpret_cast<const float2*>(csg + j * 8);
          const float2 cu = *reinterpret_cast<const float2*>(csg + 192 + j * 8);
          const float r0 = fmaxf(fmaf(accg[4 * j], iv[0], nm0 * cg.x), 0.f) * fmaf(accu[4 * j], iv[0], nm0 * cu.x);
          const float r1 = fmaxf(fmaf(accg[4 * j + 1], iv[0], nm0 * cg.y), 0.f) * fmaf(accu[4 * j + 1], iv[0], nm0 * cu.y);
          const float r2 = fmaxf(fmaf(accg[4 * j + 2], iv[1], nm1 * cg.x), 0.f) * fmaf(accu[4 * j + 2], iv[1], nm1 * cu.x);
          const float r3 = fmaxf(fmaf(accg[4 * j + 3], iv[1], nm1 * cg.y), 0.f) * fmaf(accu[4 * j + 3], iv[1], nm1 * cu.y);
          const uint32_t a0 = stg + sl * 8192 + ((jj ^ g) << 4);
          st_shared_b32(a0, pack_bf16(r0, r1));
          st_shared_b32(a0 + 1024, pack_bf16(r2, r3));
        }
        fence_proxy_async();
        named_bar_sync(1 + wg, 128);
        if (leader) {
          tma_store_2d(&tmHHs, sbase + KC_STAGING + wg * 24576 + sl * 8192, j_blk * 192 + sl * 64, m_blk * 128 + wg * 64);
          bulk_commit();
        }
      }
      TS(3, 7);
      if (leader) {
        bulk_wait_all();
        TS(3, 8);
        fence_proxy_async_all();
        flag_signal(&g_flag[32 + m_blk]);
      }
      TS(3, 9);
    }
    {
      uint32_t res[20];
#pragma unroll
      for (int j = 0; j < 10; j++) {
        res[2 * j] = *reinterpret_cast<const uint32_t*>(g_h + (size_t)row0 * DM + n0 + j * 8 + c4 * 2);
        res[2 * j + 1] = *reinterpret_cast<const uint32_t*>(g_h + (size_t)(row0 + 8) * DM + n0 + j * 8 + c4 * 2);
      }
      float acc0[32], acc1[8];
#pragma unroll
      for (int i = 0; i < 32; i++) acc0[i] = 0.f;
#pragma unroll
      for (int i = 0; i < 8; i++) acc1[i] = 0.f;
      mbar_wait(bar3, 0);
      TS(4, 3);
      if (wg == 0) res_mainloop<24, KC_NST3, 0>(acc0, acc1, sbase, bar3, leader);
      else res_mainloop<24, KC_NST3, 1>(acc0, acc1, sbase, bar3, leader);
      wgmma_wait<0>();
      fence_regs(acc0); fence_regs(acc1);
      TS(4, 4);
#pragma unroll
      for (int j = 0; j < 10; j++) {
        const uint32_t a01 = j < 8 ? pack_bf16(acc0[4 * j], acc0[4 * j + 1]) : pack_bf16(acc1[4 * (j - 8)], acc1[4 * (j - 8) + 1]);
        const uint32_t a23 = j < 8 ? pack_bf16(acc0[4 * j + 2], acc0[4 * j + 3]) : pack_bf16(acc1[4 * (j - 8) + 2], acc1[4 * (j - 8) + 3]);
        st_shared_b32(stg80 + j * 16, pack_bf16(bf_lo(res[2 * j]) + bf_lo(a01), bf_hi(res[2 * j]) + bf_hi(a01)));
        st_shared_b32(stg80 + 8 * 160 + j * 16, pack_bf16(bf_lo(res[2 * j + 1]) + bf_lo(a23), bf_hi(res[2 * j + 1]) + bf_hi(a23)));
      }
      fence_proxy_async();
      named_bar_sync(1 + wg, 128);
      if (leader) {
        tma_store_2d(&tmOut, stg80_base, n0, m_blk * 128 + wg * 64);
        bulk_commit();
        bulk_wait_read();
      }
      TS(4, 5);
    }
  }
  __syncwarp();
  cluster_sync_relaxed();
  TS(4, 6);
}

constexpr int AT_THREADS = 512;
constexpr int AT_WGS = AT_THREADS / 128;
#define AT_CHUNK_MASK 3
#define AT_STAGGER 0
constexpr int AT_KV_BYTES = IMG_HEAD_ELEMS * 2;
constexpr int AT_SMEM = 2 * AT_KV_BYTES + 256 + 1024;
constexpr int AT_CHUNKS = 8;

__device__ __forceinline__ float exp2_poly(float x) {
  const float u = __saturatef(fmaf(x, 1.0f / 64.0f, 62.0f / 64.0f));
  const float MAGIC = 12582912.0f - 62.0f;
  const float r = fmaf(u, 64.0f, MAGIC);
  const float q = MAGIC - r;
  const float fr = fmaf(u, 64.0f, q);
  float p = fmaf(fr, 0.009570102207362652f, 0.05591785907745361f);
  p = fmaf(p, fr, 0.240247443318367f);
  p = fmaf(p, fr, 0.6931217908859253f);
  p = fmaf(p, fr, 0.9999992847442627f);
  return __uint_as_float(__float_as_uint(p) + (__float_as_uint(r) << 23));
}
#define AT_VARIANT 0
#define AT_POLY_MOD 8
__device__ __forceinline__ bool use_poly(int e) {
  return (e % AT_POLY_MOD) == 1;
}

struct AttnState {
  uint32_t qa0, qa1, qa2, qa3, qa4, qa5;
  float M0, M1;
};

__device__ __forceinline__ bool attn_exp_fast(const float (&s)[32], uint32_t (&p)[16]) {
#pragma unroll
  for (int j = 0; j < 16; j++) {
    const float e0 = use_poly(2 * j) ? exp2_poly(s[2 * j]) : ex2(s[2 * j]);
    const float e1 = use_poly(2 * j + 1) ? exp2_poly(s[2 * j + 1]) : ex2(s[2 * j + 1]);
    p[j] = pack_bf16(e0, e1);
  }
  uint32_t acc_or = 0;
#pragma unroll
  for (int j = 0; j < 16; j++) acc_or |= p[j];
  return __any_sync(0xffffffffu, (acc_or & 0x40004000u) != 0);
}
__device__ __forceinline__ void attn_exp_exact(const float (&s)[32], uint32_t (&p)[16], float (&o)[12], AttnState& st, bool first, int c4) {
  float mx0 = fmaxf(s[0], s[1]), mx1 = fmaxf(s[2], s[3]);
#pragma unroll
  for (int j = 1; j < 8; j++) {
    mx0 = fmaxf(mx0, fmaxf(s[4 * j], s[4 * j + 1]));
    mx1 = fmaxf(mx1, fmaxf(s[4 * j + 2], s[4 * j + 3]));
  }
  mx0 = fmaxf(mx0, __shfl_xor_sync(0xffffffffu, mx0, 1));
  mx1 = fmaxf(mx1, __shfl_xor_sync(0xffffffffu, mx1, 1));
  mx0 = fmaxf(mx0, __shfl_xor_sync(0xffffffffu, mx0, 2));
  mx1 = fmaxf(mx1, __shfl_xor_sync(0xffffffffu, mx1, 2));
  float d0 = mx0 + 7.0f, d1 = mx1 + 7.0f;
  if (!first) { d0 = fmaxf(d0, 0.f); d1 = fmaxf(d1, 0.f); }
  const float T0 = st.M0 + d0, T1 = st.M1 + d1;
  const float h0 = bf16_round(T0), h1 = bf16_round(T1);
  const float i0 = bf16_round(T0 - h0), i1 = bf16_round(T1 - h1);
  const float l0 = bf16_round((T0 - h0) - i0), l1 = bf16_round((T1 - h1) - i1);
  const float N0 = (h0 + i0) + l0, N1 = (h1 + i1) + l1;
  d0 = N0 - st.M0; d1 = N1 - st.M1;
  st.M0 = N0; st.M1 = N1;
  if (c4 == 2) { st.qa4 = pack_bf16(-h0, -i0); st.qa5 = pack_bf16(-h1, -i1); }
  if (c4 == 3) { st.qa4 = pack_bf16(-l0, 0.f); st.qa5 = pack_bf16(-l1, 0.f); }
  if (!first) {
    const float al0 = ex2(-d0), al1 = ex2(-d1);
#pragma unroll
    for (int j = 0; j < 3; j++) {
      o[4 * j] *= al0; o[4 * j + 1] *= al0;
      o[4 * j + 2] *= al1; o[4 * j + 3] *= al1;
    }
  }
#pragma unroll
  for (int j = 0; j < 8; j++) {
    p[2 * j] = pack_bf16(ex2(s[4 * j] - d0), ex2(s[4 * j + 1] - d0));
    p[2 * j + 1] = pack_bf16(ex2(s[4 * j + 2] - d1), ex2(s[4 * j + 3] - d1));
  }
}
__device__ __forceinline__ void attn_step(float (&s)[32], const uint32_t (&pp)[16], uint32_t (&pn)[16], float (&o)[12], AttnState& st,
                                          uint32_t k_addr, uint32_t v_addr_prev, int keep, int c4, int wgdbg = 0, int tdbg = 0) {
  PH(wgdbg, tdbg, 0);
  const uint64_t dk = make_desc(k_addr, 128, 384, 0);
  const uint64_t dv_prev = make_desc(v_addr_prev, 384, 128, 0);
  wgmma_fence();
  wgmma_rs_n64(s, st.qa0, st.qa1, st.qa2, st.qa3, dk, 0);
  wgmma_rs_n64(s, st.qa4, st.qa5, 0u, 0u, dk + 16, 1);
  wgmma_commit();
#pragma unroll
  for (int kk = 0; kk < 4; kk++) wgmma_rs_n24_tb(o, pp[4 * kk], pp[4 * kk + 1], pp[4 * kk + 2], pp[4 * kk + 3], dv_prev + kk * 48, kk == 0 ? keep : 1);
  wgmma_commit();
  wgmma_wait<1>();
  fence_regs(s);
  PH(wgdbg, tdbg, 1);
  const bool redo = attn_exp_fast(s, pn);
  PH(wgdbg, tdbg, 2);
  wgmma_wait<0>();
  fence_regs(o);
  if (redo) attn_exp_exact(s, pn, o, st, false, c4);
}

__global__ void __launch_bounds__(AT_THREADS, 1) attn_kernel(const bf16* __restrict__ wo, const bf16* __restrict__ wgt, const bf16* __restrict__ wup, const bf16* __restrict__ wdn) {
  extern __shared__ uint8_t smem_raw[];
  const uint32_t sbase = (smem_u32(smem_raw) + 1023u) & ~1023u;
  const uint32_t sK = sbase, sV = sbase + AT_KV_BYTES;
  const uint32_t sBar = sV + AT_KV_BYTES;
  const int tid = threadIdx.x, warp = tid >> 5, lane = tid & 31;
  const int head = blockIdx.x >> 2, quarter = blockIdx.x & 3;
  if (blockIdx.x >= 128) {
    pdl_launch();
    const int b = blockIdx.x - 128;
    const bf16* w = (b >> 1) ? wup : wgt;
    const int cgrp = tid % 96, rgrp = tid / 96;
    float acc[8];
#pragma unroll
    for (int i = 0; i < 8; i++) acc[i] = 0.f;
    float* red = reinterpret_cast<float*>(smem_raw);
    if (rgrp < 5) {
      const uint4* src = reinterpret_cast<const uint4*>(w + (size_t)(rgrp * 128) * FF + (b & 1) * 768 + cgrp * 8);
#pragma unroll 8
      for (int r = 0; r < 128; r++) {
        const uint4 v = __ldg(src + (size_t)r * (FF / 8));
        acc[0] += bf_lo(v.x); acc[1] += bf_hi(v.x); acc[2] += bf_lo(v.y); acc[3] += bf_hi(v.y);
        acc[4] += bf_lo(v.z); acc[5] += bf_hi(v.z); acc[6] += bf_lo(v.w); acc[7] += bf_hi(v.w);
      }
#pragma unroll
      for (int i = 0; i < 8; i++) red[rgrp * 768 + cgrp * 8 + i] = acc[i];
    }
    __syncthreads();
    pdl_wait();
    for (int c = tid; c < 768; c += AT_THREADS)
      g_cs[(b >> 1) * FF + (b & 1) * 768 + c] = ((red[c] + red[768 + c]) + (red[1536 + c] + red[2304 + c])) + red[3072 + c];
    if (b == 0 && tid < 16) g_flag[tid] = 0;
    return;
  }
  TS(1, 0);
  if (tid == 0) {
    for (int i = 0; i < AT_CHUNKS; i++) mbar_init(sBar + 8 * i, 1);
    fence_mbar_init();
  }
  pdl_launch();
  if (tid == 32) {
    prefetch_l2(reinterpret_cast<const uint8_t*>(wo) + blockIdx.x * 6400, 6400);
    prefetch_l2(reinterpret_cast<const uint8_t*>(wgt) + blockIdx.x * 15360, 15360);
    prefetch_l2(reinterpret_cast<const uint8_t*>(wup) + blockIdx.x * 15360, 15360);
    prefetch_l2(reinterpret_cast<const uint8_t*>(wdn) + blockIdx.x * 15360, 15360);
  }
  __syncthreads();
  TS(1, 1);
  pdl_wait();
  TS(1, 2);
  if (tid == 0) {
    const uint8_t* kg = reinterpret_cast<const uint8_t*>(g_img + (size_t)(32 + head) * IMG_HEAD_ELEMS);
    const uint8_t* vg = reinterpret_cast<const uint8_t*>(g_img + (size_t)(64 + head) * IMG_HEAD_ELEMS);
    constexpr int CB = AT_KV_BYTES / AT_CHUNKS;
    for (int i = 0; i < AT_CHUNKS; i++) {
      mbar_expect_tx(sBar + 8 * i, 2 * CB);
      bulk_g2s(sK + i * CB, kg + i * CB, CB, sBar + 8 * i);
      bulk_g2s(sV + i * CB, vg + i * CB, CB, sBar + 8 * i);
    }
  }
  const int wg = warp >> 2, wwarp = warp & 3;
  const int g = lane >> 2, c4 = lane & 3;
  const uint64_t dk_base = make_desc(sK, 128, 384, 0);
  const uint64_t dv_base = make_desc(sV, 384, 128, 0);

#pragma unroll 1
  for (int rep = 0; rep < 8 / AT_WGS; rep++) {
    const int row0 = quarter * 512 + (rep * AT_WGS + wg) * 64 + wwarp * 16 + g;
    AttnState st;
    {
      const bf16* q0 = g_img + (size_t)head * IMG_HEAD_ELEMS + (size_t)(row0 >> 3) * 192 + g * 8 + c4 * 2;
      const bf16* q1 = q0 + 192;
      st.qa0 = *reinterpret_cast<const uint32_t*>(q0);
      st.qa1 = *reinterpret_cast<const uint32_t*>(q1);
      st.qa2 = *reinterpret_cast<const uint32_t*>(q0 + 64);
      st.qa3 = *reinterpret_cast<const uint32_t*>(q1 + 64);
      st.qa4 = *reinterpret_cast<const uint32_t*>(q0 + 128);
      st.qa5 = *reinterpret_cast<const uint32_t*>(q1 + 128);
    }
    float o[12];
    float s[32];
    uint32_t pa[16], pb[16];
    st.M0 = st.M1 = 0.f;
    if (rep == 0) mbar_wait(sBar, 0);
    wgmma_fence();
    wgmma_rs_n64(s, st.qa0, st.qa1, st.qa2, st.qa3, dk_base, 0);
    wgmma_rs_n64(s, st.qa4, st.qa5, 0u, 0u, dk_base + 16, 1);
    wgmma_commit();
    wgmma_wait<0>();
    fence_regs(s);
    attn_exp_exact(s, pa, o, st, true, c4);
    attn_step(s, pa, pb, o, st, sK + 3072, sV, 0, c4);
#pragma unroll 1
    for (int tt = 1; tt < 16; tt++) {
      if (rep == 0 && !(tt & 1)) mbar_wait(sBar + 8 * (tt >> 1), 0);
      attn_step(s, pb, pa, o, st, sK + tt * 6144, sV + tt * 6144 - 3072, 1, c4, wg, rep * 32 + tt * 2);
      attn_step(s, pa, pb, o, st, sK + tt * 6144 + 3072, sV + tt * 6144, 1, c4, wg, rep * 32 + tt * 2 + 1);
    }
    wgmma_fence();
#pragma unroll
    for (int kk = 0; kk < 4; kk++) wgmma_rs_n24_tb(o, pb[4 * kk], pb[4 * kk + 1], pb[4 * kk + 2], pb[4 * kk + 3], dv_base + 31 * 192 + kk * 48, 1);
    wgmma_commit();
    wgmma_wait<0>();
    fence_regs(o);
    TS(1, 3 + rep);
    const float l0 = __shfl_sync(0xffffffffu, o[8], (lane & ~3) | 2);
    const float l1 = __shfl_sync(0xffffffffu, o[10], (lane & ~3) | 2);
    const float i0 = 1.0f / l0, i1 = 1.0f / l1;
    bf16* o0 = g_o + (size_t)row0 * DM + head * DH;
    bf16* o1 = o0 + 8 * DM;
#pragma unroll
    for (int j = 0; j < 3; j++) {
      if (j < 2 || c4 < 2) {
        *reinterpret_cast<uint32_t*>(o0 + j * 8 + c4 * 2) = pack_bf16(o[4 * j] * i0, o[4 * j + 1] * i0);
        *reinterpret_cast<uint32_t*>(o1 + j * 8 + c4 * 2) = pack_bf16(o[4 * j + 2] * i1, o[4 * j + 3] * i1);
      }
    }
  }
}

typedef CUresult (*EncodeTiledFn)(CUtensorMap*, CUtensorMapDataType, cuuint32_t, void*, const cuuint64_t*, const cuuint64_t*,
                                  const cuuint32_t*, const cuuint32_t*, CUtensorMapInterleave, CUtensorMapSwizzle,
                                  CUtensorMapL2promotion, CUtensorMapFloatOOBfill);

static void make_map(EncodeTiledFn fn, CUtensorMap* tm, const void* ptr, uint64_t rows, uint64_t cols, uint32_t box_rows,
                     uint32_t box_cols, CUtensorMapSwizzle sw) {
  cuuint64_t dims[2] = {cols, rows};
  cuuint64_t strides[1] = {cols * 2};
  cuuint32_t box[2] = {box_cols, box_rows};
  cuuint32_t es[2] = {1, 1};
  fn(tm, CU_TENSOR_MAP_DATA_TYPE_BFLOAT16, 2, const_cast<void*>(ptr), dims, strides, box, es, CU_TENSOR_MAP_INTERLEAVE_NONE, sw,
     CU_TENSOR_MAP_L2_PROMOTION_L2_256B, CU_TENSOR_MAP_FLOAT_OOB_FILL_NONE);
}

template <typename... KArgs, typename... Args>
static void launch(void (*kern)(KArgs...), int grid, int block, int smem, int cluster, bool pdl, Args... args) {
  cudaLaunchConfig_t cfg = {};
  cfg.gridDim = dim3(grid);
  cfg.blockDim = dim3(block);
  cfg.dynamicSmemBytes = smem;
  cfg.stream = cudaStreamPerThread;
  cudaLaunchAttribute at[2];
  int n = 0;
  if (cluster > 1) {
    at[n].id = cudaLaunchAttributeClusterDimension;
    at[n].val.clusterDim.x = cluster; at[n].val.clusterDim.y = 1; at[n].val.clusterDim.z = 1;
    n++;
  }
  if (pdl) {
    at[n].id = cudaLaunchAttributeProgrammaticStreamSerialization;
    at[n].val.programmaticStreamSerializationAllowed = 1;
    n++;
  }
  cfg.attrs = at;
  cfg.numAttrs = n;
  cudaLaunchKernelEx(&cfg, kern, KArgs(args)...);
}

extern "C" void kernel_launch(void* const* d_in, const int* in_sizes, int n_in, void* d_out, int out_size) {
  const bf16* x = (const bf16*)d_in[0];
  const bf16* wqkv = (const bf16*)d_in[1];
  const bf16* wo = (const bf16*)d_in[2];
  const bf16* wg = (const bf16*)d_in[4];
  const bf16* wu = (const bf16*)d_in[5];
  const bf16* wd = (const bf16*)d_in[6];
  bf16* out = (bf16*)d_out;

  static EncodeTiledFn enc = nullptr;
  static void *p_o = nullptr, *p_h = nullptr, *p_hh = nullptr;
  if (!enc) {
    void* fn = nullptr;
    cudaDriverEntryPointQueryResult qr;
    cudaGetDriverEntryPoint("cuTensorMapEncodeTiled", &fn, cudaEnableDefault, &qr);
    enc = (EncodeTiledFn)fn;
    cudaGetSymbolAddress(&p_o, g_o);
    cudaGetSymbolAddress(&p_h, g_h);
    cudaGetSymbolAddress(&p_hh, g_hh);
    cudaFuncSetAttribute(qkv_kernel, cudaFuncAttributeMaxDynamicSharedMemorySize, KA_SMEM);
    cudaFuncSetAttribute(mlp_kernel, cudaFuncAttributeMaxDynamicSharedMemorySize, KC_SMEM);
    cudaFuncSetAttribute(attn_kernel, cudaFuncAttributeMaxDynamicSharedMemorySize, AT_SMEM);
  }
  CUtensorMap tm_wqkv, tm_wg, tm_wu, tm_wo64, tm_wo16, tm_wd64, tm_wd16, tm_o, tm_h, tm_hh, tm_hhs, tm_xn, tm_hs, tm_out;
  make_map(enc, &tm_wqkv, wqkv, DM, 3 * DM, 32, 64, CU_TENSOR_MAP_SWIZZLE_128B);
  make_map(enc, &tm_wg, wg, DM, FF, 32, 64, CU_TENSOR_MAP_SWIZZLE_128B);
  make_map(enc, &tm_wu, wu, DM, FF, 32, 64, CU_TENSOR_MAP_SWIZZLE_128B);
  make_map(enc, &tm_wo64, wo, DM, DM, 32, 64, CU_TENSOR_MAP_SWIZZLE_128B);
  make_map(enc, &tm_wo16, wo, DM, DM, 32, 16, CU_TENSOR_MAP_SWIZZLE_32B);
  make_map(enc, &tm_wd64, wd, FF, DM, 32, 64, CU_TENSOR_MAP_SWIZZLE_128B);
  make_map(enc, &tm_wd16, wd, FF, DM, 32, 16, CU_TENSOR_MAP_SWIZZLE_32B);
  make_map(enc, &tm_o, p_o, SEQ, DM, 128, 64, CU_TENSOR_MAP_SWIZZLE_128B);
  make_map(enc, &tm_h, p_h, SEQ, DM, 128, 32, CU_TENSOR_MAP_SWIZZLE_64B);
  make_map(enc, &tm_hh, p_hh, SEQ, FF, 128, 64, CU_TENSOR_MAP_SWIZZLE_128B);
  make_map(enc, &tm_hhs, p_hh, SEQ, FF, 64, 64, CU_TENSOR_MAP_SWIZZLE_128B);
  make_map(enc, &tm_xn, x, SEQ, DM, 128, 32, CU_TENSOR_MAP_SWIZZLE_64B);
  make_map(enc, &tm_hs, p_h, SEQ, DM, 64, 80, CU_TENSOR_MAP_SWIZZLE_NONE);
  make_map(enc, &tm_out, out, SEQ, DM, 64, 80, CU_TENSOR_MAP_SWIZZLE_NONE);

  launch(qkv_kernel, 128, GT, KA_SMEM, 2, false, tm_xn, tm_wqkv, x, wqkv);
  launch(attn_kernel, 132, AT_THREADS, AT_SMEM, 1, true, wo, wg, wu, wd);
  launch(mlp_kernel, 128, GT, KC_SMEM, 2, true, tm_o, tm_wo64, tm_wo16, tm_h, tm_wg, tm_wu, tm_hhs, tm_hh, tm_wd64, tm_wd16, tm_hs, tm_out, x);
}
```

```cpp
#include <cuda_runtime.h>
#include <cuda_bf16.h>
#include <cuda.h>
#include <stdint.h>

typedef __nv_bfloat16 bf16;
#define FLAGV 0

constexpr int SEQ = 2048, DM = 640, NH = 32, DH = 20, FF = 1536;
constexpr float ATT_SCALE_LOG2E = 0.22360679774997896f * 1.4426950408889634f;
constexpr int IMG_HEAD_ELEMS = (SEQ / 8) * 192;

__device__ __align__(1024) bf16 g_img[3 * NH * IMG_HEAD_ELEMS];
__device__ __align__(1024) bf16 g_o[SEQ * DM];
__device__ __align__(1024) bf16 g_h[SEQ * DM];
__device__ float2 g_stats[SEQ * 8];
__device__ float g_cs[2 * FF];
__device__ int g_flag[4 * 16];
__device__ float g_csp[16 * 3 * DM];
__device__ float2 g_rs[SEQ];
__device__ __align__(1024) bf16 g_hh[SEQ * FF];

#define TS(k, i)
#define PH(w, t, i)
__device__ __forceinline__ uint32_t smem_u32(const void* p) { return (uint32_t)__cvta_generic_to_shared(p); }
__device__ __forceinline__ void mbar_init(uint32_t bar, uint32_t cnt) {
  asm volatile("mbarrier.init.shared::cta.b64 [%0], %1;" ::"r"(bar), "r"(cnt) : "memory");
}
__device__ __forceinline__ void mbar_expect_tx(uint32_t bar, uint32_t bytes) {
  asm volatile("mbarrier.arrive.expect_tx.shared::cta.b64 _, [%0], %1;" ::"r"(bar), "r"(bytes) : "memory");
}
__device__ __forceinline__ void mbar_arrive(uint32_t bar) {
  asm volatile("mbarrier.arrive.shared::cta.b64 _, [%0];" ::"r"(bar) : "memory");
}
__device__ __forceinline__ void mbar_arrive_cluster(uint32_t bar, uint32_t cta) {
  asm volatile(
      "{\n.reg .b32 r;\nmapa.shared::cluster.u32 r, %0, %1;\n"
      "mbarrier.arrive.shared::cluster.b64 _, [r];\n}\n" ::"r"(bar), "r"(cta)
      : "memory");
}
__device__ __forceinline__ void mbar_wait(uint32_t bar, uint32_t parity) {
  asm volatile(
      "{\n.reg .pred p;\nLAB_WAIT:\n"
      "mbarrier.try_wait.parity.shared::cta.b64 p, [%0], %1;\n"
      "@p bra DONE;\nbra LAB_WAIT;\nDONE:\n}\n" ::"r"(bar), "r"(parity)
      : "memory");
}
__device__ __forceinline__ void mbar_wait_cluster(uint32_t bar, uint32_t parity) {
  asm volatile(
      "{\n.reg .pred p;\nLAB_WAIT:\n"
      "mbarrier.try_wait.parity.acquire.cluster.shared::cta.b64 p, [%0], %1;\n"
      "@p bra DONE;\nbra LAB_WAIT;\nDONE:\n}\n" ::"r"(bar), "r"(parity)
      : "memory");
}
__device__ __forceinline__ void fence_mbar_init() { asm volatile("fence.mbarrier_init.release.cluster;" ::: "memory"); }
__device__ __forceinline__ void fence_proxy_async() { asm volatile("fence.proxy.async.shared::cta;" ::: "memory"); }
__device__ __forceinline__ void cluster_sync_all() {
  asm volatile("barrier.cluster.arrive.release.aligned;\nbarrier.cluster.wait.acquire.aligned;" ::: "memory");
}
__device__ __forceinline__ void cluster_sync_relaxed() {
  asm volatile("barrier.cluster.arrive.relaxed.aligned;\nbarrier.cluster.wait.aligned;" ::: "memory");
}
__device__ __forceinline__ void named_bar_sync(int id, int n) { asm volatile("bar.sync %0, %1;" ::"r"(id), "r"(n) : "memory"); }
__device__ __forceinline__ bool wg_any(bool pred, int id) {
  uint32_t r;
  asm volatile("{\n.reg .pred p, q;\nsetp.ne.u32 p, %1, 0;\nbar.red.or.pred q, %2, 128, p;\nselp.u32 %0, 1, 0, q;\n}\n" : "=r"(r) : "r"((uint32_t)pred), "r"(id) : "memory");
  return r != 0;
}
__device__ __forceinline__ void fence_proxy_async_all() { asm volatile("fence.proxy.async;" ::: "memory"); }
__device__ __forceinline__ void flag_signal(int* f) {
  __threadfence();
  atomicAdd(f, 1);
}
__device__ __forceinline__ void flag_wait(const int* f, int target) {
  int v;
  unsigned spins = 0;
  do {
    asm volatile("ld.acquire.gpu.global.s32 %0, [%1];" : "=r"(v) : "l"(f) : "memory");
    if (++spins > (1u << 24)) __trap();
  } while (v < target);
}
__device__ __forceinline__ void pdl_launch() { asm volatile("griddepcontrol.launch_dependents;" ::: "memory"); }
__device__ __forceinline__ void pdl_wait() { asm volatile("griddepcontrol.wait;" ::: "memory"); }

__device__ __forceinline__ void tma_load_2d(uint32_t dst, const CUtensorMap* tm, int c0, int c1, uint32_t bar) {
  asm volatile(
      "cp.async.bulk.tensor.2d.shared::cluster.global.mbarrier::complete_tx::bytes [%0], [%1, {%3, %4}], [%2];" ::"r"(dst),
      "l"((uint64_t)tm), "r"(bar), "r"(c0), "r"(c1)
      : "memory");
}
__device__ __forceinline__ void tma_load_2d_mc(uint32_t dst, const CUtensorMap* tm, int c0, int c1, uint32_t bar, uint16_t mask) {
  asm volatile(
      "cp.async.bulk.tensor.2d.shared::cluster.global.mbarrier::complete_tx::bytes.multicast::cluster [%0], [%1, {%3, %4}], [%2], %5;" ::"r"(dst),
      "l"((uint64_t)tm), "r"(bar), "r"(c0), "r"(c1), "h"(mask)
      : "memory");
}
__device__ __forceinline__ void bulk_g2s(uint32_t dst, const void* src, uint32_t bytes, uint32_t bar) {
  asm volatile("cp.async.bulk.shared::cluster.global.mbarrier::complete_tx::bytes [%0], [%1], %2, [%3];" ::"r"(dst), "l"(src),
               "r"(bytes), "r"(bar)
               : "memory");
}
__device__ __forceinline__ void bulk_s2g(void* dst, uint32_t src, uint32_t bytes) {
  asm volatile("cp.async.bulk.global.shared::cta.bulk_group [%0], [%1], %2;" ::"l"(dst), "r"(src), "r"(bytes) : "memory");
}
__device__ __forceinline__ void tma_store_2d(const CUtensorMap* tm, uint32_t src, int c0, int c1) {
  asm volatile("cp.async.bulk.tensor.2d.global.shared::cta.bulk_group [%0, {%2, %3}], [%1];" ::"l"((uint64_t)tm), "r"(src), "r"(c0), "r"(c1) : "memory");
}
__device__ __forceinline__ void bulk_commit() { asm volatile("cp.async.bulk.commit_group;" ::: "memory"); }
__device__ __forceinline__ void bulk_wait_read() { asm volatile("cp.async.bulk.wait_group.read 0;" ::: "memory"); }
__device__ __forceinline__ void prefetch_l2(const void* p, uint32_t bytes) {
  asm volatile("cp.async.bulk.prefetch.L2.global [%0], %1;" ::"l"(p), "r"(bytes) : "memory");
}
__device__ __forceinline__ void bulk_wait_all() { asm volatile("cp.async.bulk.wait_group 0;" ::: "memory"); }
__device__ __forceinline__ void st_shared_b32(uint32_t addr, uint32_t v) { asm volatile("st.shared.b32 [%0], %1;" ::"r"(addr), "r"(v) : "memory"); }
__device__ __forceinline__ void st_shared_v2(uint32_t addr, uint32_t a, uint32_t b) { asm volatile("st.shared.v2.b32 [%0], {%1, %2};" ::"r"(addr), "r"(a), "r"(b) : "memory"); }
__device__ __forceinline__ void prefetch_tmap(const CUtensorMap* tm) {
  asm volatile("prefetch.tensormap [%0];" ::"l"((uint64_t)tm) : "memory");
}
__device__ __forceinline__ void wgmma_fence() { asm volatile("wgmma.fence.sync.aligned;" ::: "memory"); }
__device__ __forceinline__ void wgmma_commit() { asm volatile("wgmma.commit_group.sync.aligned;" ::: "memory"); }
template <int N>
__device__ __forceinline__ void wgmma_wait() { asm volatile("wgmma.wait_group.sync.aligned %0;" ::"n"(N) : "memory"); }

template <int N>
__device__ __forceinline__ void fence_regs(float (&r)[N]) {
#pragma unroll
  for (int i = 0; i < N; i++) asm volatile("" : "+f"(r[i])::"memory");
}
template <int N>
__device__ __forceinline__ void fence_regs(uint32_t (&r)[N]) {
#pragma unroll
  for (int i = 0; i < N; i++) asm volatile("" : "+r"(r[i])::"memory");
}
__device__ __forceinline__ uint64_t make_desc(uint32_t addr, uint32_t lbo, uint32_t sbo, uint32_t layout) {
  return (uint64_t)((addr & 0x3FFFF) >> 4) | ((uint64_t)((lbo & 0x3FFFF) >> 4) << 16) | ((uint64_t)((sbo & 0x3FFFF) >> 4) << 32) |
         ((uint64_t)layout << 62);
}
__device__ __forceinline__ uint32_t pack_bf16(float lo, float hi) {
  uint32_t r;
  asm("cvt.rn.bf16x2.f32 %0, %1, %2;" : "=r"(r) : "f"(hi), "f"(lo));
  return r;
}
__device__ __forceinline__ float bf16_round(float x) { return __bfloat162float(__float2bfloat16_rn(x)); }
__device__ __forceinline__ float bf_lo(uint32_t u) { return __uint_as_float(u << 16); }
__device__ __forceinline__ float bf_hi(uint32_t u) { return __uint_as_float(u & 0xffff0000u); }
__device__ __forceinline__ float ex2(float x) {
  float y;
  asm("ex2.approx.ftz.f32 %0, %1;" : "=f"(y) : "f"(x));
  return y;
}

__device__ __forceinline__ void wgmma_ss_n240_tb(float (&d)[120], uint64_t descA, uint64_t descB, int scaleD) {
  asm volatile("{\n.reg .pred p;\nsetp.ne.b32 p, %122, 0;\n"
    "wgmma.mma_async.sync.aligned.m64n240k16.f32.bf16.bf16 {%0, %1, %2, %3, %4, %5, %6, %7, %8, %9, %10, %11, %12, %13, %14, %15, %16, %17, %18, %19, %20, %21, %22, %23, %24, %25, %26, %27, %28, %29, %30, %31, %32, %33, %34, %35, %36, %37, %38, %39, %40, %41, %42, %43, %44, %45, %46, %47, %48, %49, %50, %51, %52, %53, %54, %55, %56, %57, %58, %59, %60, %61, %62, %63, %64, %65, %66, %67, %68, %69, %70, %71, %72, %73, %74, %75, %76, %77, %78, %79, %80, %81, %82, %83, %84, %85, %86, %87, %88, %89, %90, %91, %92, %93, %94, %95, %96, %97, %98, %99, %100, %101, %102, %103, %104, %105, %106, %107, %108, %109, %110, %111, %112, %113, %114, %115, %116, %117, %118, %119}, %120, %121, p, 1, 1, 0, 1;\n}\n"
    : "+f"(d[0]), "+f"(d[1]), "+f"(d[2]), "+f"(d[3]), "+f"(d[4]), "+f"(d[5]), "+f"(d[6]), "+f"(d[7]), "+f"(d[8]), "+f"(d[9]), "+f"(d[10]), "+f"(d[11]), "+f"(d[12]), "+f"(d[13]), "+f"(d[14]), "+f"(d[15]), "+f"(d[16]), "+f"(d[17]), "+f"(d[18]), "+f"(d[19]), "+f"(d[20]), "+f"(d[21]), "+f"(d[22]), "+f"(d[23]), "+f"(d[24]), "+f"(d[25]), "+f"(d[26]), "+f"(d[27]), "+f"(d[28]), "+f"(d[29]), "+f"(d[30]), "+f"(d[31]), "+f"(d[32]), "+f"(d[33]), "+f"(d[34]), "+f"(d[35]), "+f"(d[36]), "+f"(d[37]), "+f"(d[38]), "+f"(d[39]), "+f"(d[40]), "+f"(d[41]), "+f"(d[42]), "+f"(d[43]), "+f"(d[44]), "+f"(d[45]), "+f"(d[46]), "+f"(d[47]), "+f"(d[48]), "+f"(d[49]), "+f"(d[50]), "+f"(d[51]), "+f"(d[52]), "+f"(d[53]), "+f"(d[54]), "+f"(d[55]), "+f"(d[56]), "+f"(d[57]), "+f"(d[58]), "+f"(d[59]), "+f"(d[60]), "+f"(d[61]), "+f"(d[62]), "+f"(d[63]), "+f"(d[64]), "+f"(d[65]), "+f"(d[66]), "+f"(d[67]), "+f"(d[68]), "+f"(d[69]), "+f"(d[70]), "+f"(d[71]), "+f"(d[72]), "+f"(d[73]), "+f"(d[74]), "+f"(d[75]), "+f"(d[76]), "+f"(d[77]), "+f"(d[78]), "+f"(d[79]), "+f"(d[80]), "+f"(d[81]), "+f"(d[82]), "+f"(d[83]), "+f"(d[84]), "+f"(d[85]), "+f"(d[86]), "+f"(d[87]), "+f"(d[88]), "+f"(d[89]), "+f"(d[90]), "+f"(d[91]), "+f"(d[92]), "+f"(d[93]), "+f"(d[94]), "+f"(d[95]), "+f"(d[96]), "+f"(d[97]), "+f"(d[98]), "+f"(d[99]), "+f"(d[100]), "+f"(d[101]), "+f"(d[102]), "+f"(d[103]), "+f"(d[104]), "+f"(d[105]), "+f"(d[106]), "+f"(d[107]), "+f"(d[108]), "+f"(d[109]), "+f"(d[110]), "+f"(d[111]), "+f"(d[112]), "+f"(d[113]), "+f"(d[114]), "+f"(d[115]), "+f"(d[116]), "+f"(d[117]), "+f"(d[118]), "+f"(d[119])
    : "l"(descA), "l"(descB), "r"(scaleD));
}
__device__ __forceinline__ void wgmma_ss_n192_tb(float (&d)[96], uint64_t descA, uint64_t descB, int scaleD) {
  asm volatile("{\n.reg .pred p;\nsetp.ne.b32 p, %98, 0;\n"
    "wgmma.mma_async.sync.aligned.m64n192k16.f32.bf16.bf16 {%0, %1, %2, %3, %4, %5, %6, %7, %8, %9, %10, %11, %12, %13, %14, %15, %16, %17, %18, %19, %20, %21, %22, %23, %24, %25, %26, %27, %28, %29, %30, %31, %32, %33, %34, %35, %36, %37, %38, %39, %40, %41, %42, %43, %44, %45, %46, %47, %48, %49, %50, %51, %52, %53, %54, %55, %56, %57, %58, %59, %60, %61, %62, %63, %64, %65, %66, %67, %68, %69, %70, %71, %72, %73, %74, %75, %76, %77, %78, %79, %80, %81, %82, %83, %84, %85, %86, %87, %88, %89, %90, %91, %92, %93, %94, %95}, %96, %97, p, 1, 1, 0, 1;\n}\n"
    : "+f"(d[0]), "+f"(d[1]), "+f"(d[2]), "+f"(d[3]), "+f"(d[4]), "+f"(d[5]), "+f"(d[6]), "+f"(d[7]), "+f"(d[8]), "+f"(d[9]), "+f"(d[10]), "+f"(d[11]), "+f"(d[12]), "+f"(d[13]), "+f"(d[14]), "+f"(d[15]), "+f"(d[16]), "+f"(d[17]), "+f"(d[18]), "+f"(d[19]), "+f"(d[20]), "+f"(d[21]), "+f"(d[22]), "+f"(d[23]), "+f"(d[24]), "+f"(d[25]), "+f"(d[26]), "+f"(d[27]), "+f"(d[28]), "+f"(d[29]), "+f"(d[30]), "+f"(d[31]), "+f"(d[32]), "+f"(d[33]), "+f"(d[34]), "+f"(d[35]), "+f"(d[36]), "+f"(d[37]), "+f"(d[38]), "+f"(d[39]), "+f"(d[40]), "+f"(d[41]), "+f"(d[42]), "+f"(d[43]), "+f"(d[44]), "+f"(d[45]), "+f"(d[46]), "+f"(d[47]), "+f"(d[48]), "+f"(d[49]), "+f"(d[50]), "+f"(d[51]), "+f"(d[52]), "+f"(d[53]), "+f"(d[54]), "+f"(d[55]), "+f"(d[56]), "+f"(d[57]), "+f"(d[58]), "+f"(d[59]), "+f"(d[60]), "+f"(d[61]), "+f"(d[62]), "+f"(d[63]), "+f"(d[64]), "+f"(d[65]), "+f"(d[66]), "+f"(d[67]), "+f"(d[68]), "+f"(d[69]), "+f"(d[70]), "+f"(d[71]), "+f"(d[72]), "+f"(d[73]), "+f"(d[74]), "+f"(d[75]), "+f"(d[76]), "+f"(d[77]), "+f"(d[78]), "+f"(d[79]), "+f"(d[80]), "+f"(d[81]), "+f"(d[82]), "+f"(d[83]), "+f"(d[84]), "+f"(d[85]), "+f"(d[86]), "+f"(d[87]), "+f"(d[88]), "+f"(d[89]), "+f"(d[90]), "+f"(d[91]), "+f"(d[92]), "+f"(d[93]), "+f"(d[94]), "+f"(d[95])
    : "l"(descA), "l"(descB), "r"(scaleD));
}
__device__ __forceinline__ void wgmma_ss_n64_tb(float (&d)[32], uint64_t descA, uint64_t descB, int scaleD) {
  asm volatile("{\n.reg .pred p;\nsetp.ne.b32 p, %34, 0;\n"
    "wgmma.mma_async.sync.aligned.m64n64k16.f32.bf16.bf16 {%0, %1, %2, %3, %4, %5, %6, %7, %8, %9, %10, %11, %12, %13, %14, %15, %16, %17, %18, %19, %20, %21, %22, %23, %24, %25, %26, %27, %28, %29, %30, %31}, %32, %33, p, 1, 1, 0, 1;\n}\n"
    : "+f"(d[0]), "+f"(d[1]), "+f"(d[2]), "+f"(d[3]), "+f"(d[4]), "+f"(d[5]), "+f"(d[6]), "+f"(d[7]), "+f"(d[8]), "+f"(d[9]), "+f"(d[10]), "+f"(d[11]), "+f"(d[12]), "+f"(d[13]), "+f"(d[14]), "+f"(d[15]), "+f"(d[16]), "+f"(d[17]), "+f"(d[18]), "+f"(d[19]), "+f"(d[20]), "+f"(d[21]), "+f"(d[22]), "+f"(d[23]), "+f"(d[24]), "+f"(d[25]), "+f"(d[26]), "+f"(d[27]), "+f"(d[28]), "+f"(d[29]), "+f"(d[30]), "+f"(d[31])
    : "l"(descA), "l"(descB), "r"(scaleD));
}
__device__ __forceinline__ void wgmma_ss_n16_tb(float (&d)[8], uint64_t descA, uint64_t descB, int scaleD) {
  asm volatile("{\n.reg .pred p;\nsetp.ne.b32 p, %10, 0;\n"
    "wgmma.mma_async.sync.aligned.m64n16k16.f32.bf16.bf16 {%0, %1, %2, %3, %4, %5, %6, %7}, %8, %9, p, 1, 1, 0, 1;\n}\n"
    : "+f"(d[0]), "+f"(d[1]), "+f"(d[2]), "+f"(d[3]), "+f"(d[4]), "+f"(d[5]), "+f"(d[6]), "+f"(d[7])
    : "l"(descA), "l"(descB), "r"(scaleD));
}
__device__ __forceinline__ void wgmma_rs_n128(float (&d)[64], uint32_t a0, uint32_t a1, uint32_t a2, uint32_t a3, uint64_t descB, int scaleD) {
  asm volatile("{\n.reg .pred p;\nsetp.ne.b32 p, %69, 0;\n"
    "wgmma.mma_async.sync.aligned.m64n128k16.f32.bf16.bf16 {%0, %1, %2, %3, %4, %5, %6, %7, %8, %9, %10, %11, %12, %13, %14, %15, %16, %17, %18, %19, %20, %21, %22, %23, %24, %25, %26, %27, %28, %29, %30, %31, %32, %33, %34, %35, %36, %37, %38, %39, %40, %41, %42, %43, %44, %45, %46, %47, %48, %49, %50, %51, %52, %53, %54, %55, %56, %57, %58, %59, %60, %61, %62, %63}, {%64, %65, %66, %67}, %68, p, 1, 1, 0;\n}\n"
    : "+f"(d[0]), "+f"(d[1]), "+f"(d[2]), "+f"(d[3]), "+f"(d[4]), "+f"(d[5]), "+f"(d[6]), "+f"(d[7]), "+f"(d[8]), "+f"(d[9]), "+f"(d[10]), "+f"(d[11]), "+f"(d[12]), "+f"(d[13]), "+f"(d[14]), "+f"(d[15]), "+f"(d[16]), "+f"(d[17]), "+f"(d[18]), "+f"(d[19]), "+f"(d[20]), "+f"(d[21]), "+f"(d[22]), "+f"(d[23]), "+f"(d[24]), "+f"(d[25]), "+f"(d[26]), "+f"(d[27]), "+f"(d[28]), "+f"(d[29]), "+f"(d[30]), "+f"(d[31]), "+f"(d[32]), "+f"(d[33]), "+f"(d[34]), "+f"(d[35]), "+f"(d[36]), "+f"(d[37]), "+f"(d[38]), "+f"(d[39]), "+f"(d[40]), "+f"(d[41]), "+f"(d[42]), "+f"(d[43]), "+f"(d[44]), "+f"(d[45]), "+f"(d[46]), "+f"(d[47]), "+f"(d[48]), "+f"(d[49]), "+f"(d[50]), "+f"(d[51]), "+f"(d[52]), "+f"(d[53]), "+f"(d[54]), "+f"(d[55]), "+f"(d[56]), "+f"(d[57]), "+f"(d[58]), "+f"(d[59]), "+f"(d[60]), "+f"(d[61]), "+f"(d[62]), "+f"(d[63])
    : "r"(a0), "r"(a1), "r"(a2), "r"(a3), "l"(descB), "r"(scaleD));
}
__device__ __forceinline__ void wgmma_rs_n64(float (&d)[32], uint32_t a0, uint32_t a1, uint32_t a2, uint32_t a3, uint64_t descB, int scaleD) {
  asm volatile("{\n.reg .pred p;\nsetp.ne.b32 p, %37, 0;\n"
    "wgmma.mma_async.sync.aligned.m64n64k16.f32.bf16.bf16 {%0, %1, %2, %3, %4, %5, %6, %7, %8, %9, %10, %11, %12, %13, %14, %15, %16, %17, %18, %19, %20, %21, %22, %23, %24, %25, %26, %27, %28, %29, %30, %31}, {%32, %33, %34, %35}, %36, p, 1, 1, 0;\n}\n"
    : "+f"(d[0]), "+f"(d[1]), "+f"(d[2]), "+f"(d[3]), "+f"(d[4]), "+f"(d[5]), "+f"(d[6]), "+f"(d[7]), "+f"(d[8]), "+f"(d[9]), "+f"(d[10]), "+f"(d[11]), "+f"(d[12]), "+f"(d[13]), "+f"(d[14]), "+f"(d[15]), "+f"(d[16]), "+f"(d[17]), "+f"(d[18]), "+f"(d[19]), "+f"(d[20]), "+f"(d[21]), "+f"(d[22]), "+f"(d[23]), "+f"(d[24]), "+f"(d[25]), "+f"(d[26]), "+f"(d[27]), "+f"(d[28]), "+f"(d[29]), "+f"(d[30]), "+f"(d[31])
    : "r"(a0), "r"(a1), "r"(a2), "r"(a3), "l"(descB), "r"(scaleD));
}
__device__ __forceinline__ void wgmma_rs_n24_tb(float (&d)[12], uint32_t a0, uint32_t a1, uint32_t a2, uint32_t a3, uint64_t descB, int scaleD) {
  asm volatile("{\n.reg .pred p;\nsetp.ne.b32 p, %17, 0;\n"
    "wgmma.mma_async.sync.aligned.m64n24k16.f32.bf16.bf16 {%0, %1, %2, %3, %4, %5, %6, %7, %8, %9, %10, %11}, {%12, %13, %14, %15}, %16, p, 1, 1, 1;\n}\n"
    : "+f"(d[0]), "+f"(d[1]), "+f"(d[2]), "+f"(d[3]), "+f"(d[4]), "+f"(d[5]), "+f"(d[6]), "+f"(d[7]), "+f"(d[8]), "+f"(d[9]), "+f"(d[10]), "+f"(d[11])
    : "r"(a0), "r"(a1), "r"(a2), "r"(a3), "l"(descB), "r"(scaleD));
}

constexpr int GT = 384;

__device__ __forceinline__ void release_stage(uint32_t bar, bool leader) {
  if (leader) {
    mbar_arrive_cluster(bar, 0);
    mbar_arrive_cluster(bar, 1);
  }
}

__device__ __forceinline__ float2 ln_row_stats(const bf16* __restrict__ xin, int l16) {
  const uint4* src = reinterpret_cast<const uint4*>(xin);
  uint4 v[5];
#pragma unroll
  for (int j = 0; j < 5; j++) v[j] = __ldg(src + j * 16 + l16);
  float s0 = 0.f, s1 = 0.f, s2 = 0.f, s3 = 0.f;
#pragma unroll
  for (int j = 0; j < 5; j++) {
    s0 += bf_lo(v[j].x) + bf_hi(v[j].x);
    s1 += bf_lo(v[j].y) + bf_hi(v[j].y);
    s2 += bf_lo(v[j].z) + bf_hi(v[j].z);
    s3 += bf_lo(v[j].w) + bf_hi(v[j].w);
  }
  float mean = (s0 + s1) + (s2 + s3);
#pragma unroll
  for (int o = 1; o < 16; o <<= 1) mean += __shfl_xor_sync(0xffffffffu, mean, o);
  mean *= (1.0f / DM);
  s0 = s1 = s2 = s3 = 0.f;
#pragma unroll
  for (int j = 0; j < 5; j++) {
    float d;
    d = bf_lo(v[j].x) - mean; s0 = fmaf(d, d, s0);
    d = bf_hi(v[j].x) - mean; s1 = fmaf(d, d, s1);
    d = bf_lo(v[j].y) - mean; s2 = fmaf(d, d, s2);
    d = bf_hi(v[j].y) - mean; s3 = fmaf(d, d, s3);
    d = bf_lo(v[j].z) - mean; s0 = fmaf(d, d, s0);
    d = bf_hi(v[j].z) - mean; s1 = fmaf(d, d, s1);
    d = bf_lo(v[j].w) - mean; s2 = fmaf(d, d, s2);
    d = bf_hi(v[j].w) - mean; s3 = fmaf(d, d, s3);
  }
  float sq = (s0 + s1) + (s2 + s3);
#pragma unroll
  for (int o = 1; o < 16; o <<= 1) sq += __shfl_xor_sync(0xffffffffu, sq, o);
  const float var_b = bf16_round(sq * (1.0f / DM));
  const float den = bf16_round(sqrtf(bf16_round(var_b + 1e-5f)));
  return make_float2(bf16_round(mean), __frcp_rn(den));
}

constexpr int LG_STAGES = 5;
constexpr int QKV_STAGE = 8192 + 4 * 4096;
constexpr int GLU_STAGE = 8192 + 6 * 4096;

template <int WG>
__device__ __forceinline__ void qkv_mainloop(float (&acc)[120], uint32_t sbase, uint32_t sBar, bool leader) {
  constexpr int STAGE_BYTES = QKV_STAGE, NST = LG_STAGES;
  const uint64_t da_base = make_desc(sbase + WG * 4096, 16, 512, 2);
  const uint64_t db_base = make_desc(sbase + 8192, 4096, 1024, 1);
#pragma unroll 1
  for (int r = 0; r < 20 / NST; r++) {
#pragma unroll
    for (int s = 0; s < NST; s++) {
      mbar_wait(sBar + 8 * s, r & 1);
      wgmma_fence();
#pragma unroll
      for (int ks = 0; ks < 2; ks++)
        wgmma_ss_n240_tb(acc, da_base + (uint64_t)((s * STAGE_BYTES + ks * 32) >> 4), db_base + (uint64_t)((s * STAGE_BYTES + ks * 2048) >> 4), 1);
      wgmma_commit();
      wgmma_wait<1>();
      release_stage(sBar + 8 * (NST + (s + NST - 1) % NST), leader && (s > 0 || r > 0));
    }
  }
}
template <int WG>
__device__ __forceinline__ void glu_mainloop(float (&accg)[96], float (&accu)[96], uint32_t sbase, uint32_t sBar, bool leader) {
  constexpr int STAGE_BYTES = GLU_STAGE, NST = LG_STAGES;
  const uint64_t da_base = make_desc(sbase + WG * 4096, 16, 512, 2);
  const uint64_t db_base = make_desc(sbase + 8192, 4096, 1024, 1);
#pragma unroll 1
  for (int r = 0; r < 20 / NST; r++) {
#pragma unroll
    for (int s = 0; s < NST; s++) {
      mbar_wait(sBar + 8 * s, r & 1);
      wgmma_fence();
#pragma unroll
      for (int ks = 0; ks < 2; ks++) {
        const uint64_t da = da_base + (uint64_t)((s * STAGE_BYTES + ks * 32) >> 4);
        wgmma_ss_n192_tb(accg, da, db_base + (uint64_t)((s * STAGE_BYTES + ks * 2048) >> 4), 1);
        wgmma_ss_n192_tb(accu, da, db_base + (uint64_t)((s * STAGE_BYTES + 3 * 4096 + ks * 2048) >> 4), 1);
      }
      wgmma_commit();
      wgmma_wait<1>();
      release_stage(sBar + 8 * (NST + (s + NST - 1) % NST), leader && (s > 0 || r > 0));
    }
  }
}
constexpr int RG_STAGE_BYTES = 16384 + 8192 + 2048;
template <int NKB, int NST, int WG>
__device__ __forceinline__ void res_mainloop(float (&acc0)[32], float (&acc1)[8], uint32_t sbase, uint32_t sBar, bool leader) {
  const uint64_t da_base = make_desc(sbase + WG * 8192, 16, 1024, 1);
  const uint64_t db0_base = make_desc(sbase + 16384, 8192, 1024, 1);
  const uint64_t db1_base = make_desc(sbase + 16384 + 8192, 2048, 256, 3);
#pragma unroll 1
  for (int r = 0; r < NKB / NST; r++) {
#pragma unroll
    for (int s = 0; s < NST; s++) {
      const uint64_t so = (uint64_t)(s * (RG_STAGE_BYTES >> 4));
      mbar_wait(sBar + 8 * s, r & 1);
      wgmma_fence();
#pragma unroll
      for (int ks = 0; ks < 4; ks++) {
        wgmma_ss_n64_tb(acc0, da_base + so + ks * 2, db0_base + so + ks * 128, 1);
        wgmma_ss_n16_tb(acc1, da_base + so + ks * 2, db1_base + so + ks * 32, 1);
      }
      wgmma_commit();
      wgmma_wait<1>();
      release_stage(sBar + 8 * (NST + (s + NST - 1) % NST), leader && (s > 0 || r > 0));
    }
  }
}

constexpr int KA_CS = LG_STAGES * QKV_STAGE + 128;
constexpr int KA_SMEM = KA_CS + 1024 + 3072 + 1024;

__global__ void __launch_bounds__(GT, 1)
qkv_kernel(const __grid_constant__ CUtensorMap tmA, const __grid_constant__ CUtensorMap tmB, const bf16* __restrict__ x,
           const bf16* __restrict__ wqkv) {
  constexpr int STAGE_BYTES = QKV_STAGE, NST = LG_STAGES, NKB = 20;
  extern __shared__ uint8_t smem_raw[];
  const uint32_t sbase = (smem_u32(smem_raw) + 1023u) & ~1023u;
  const uint32_t sBar = sbase + NST * STAGE_BYTES;
  const int tid = threadIdx.x, warp = tid >> 5, lane = tid & 31;
  const int rank = blockIdx.x & 1;
  const int pair = blockIdx.x >> 1;
  const int n_blk = pair & 7;
  const int m_blk = (pair >> 3) * 2 + rank;
  TS(0, 0);
  if (tid == 256) {
    prefetch_tmap(&tmA);
    prefetch_tmap(&tmB);
  }
  if (tid == 0) {
    for (int s = 0; s < NST; s++) {
      mbar_init(sBar + 8 * s, 1);
      mbar_init(sBar + 8 * (NST + s), 4);
    }
    fence_mbar_init();
    if (blockIdx.x < 32) g_flag[16 + blockIdx.x] = 0;
  }
  pdl_launch();
  cluster_sync_all();

  if (warp >= 8) {
    asm volatile("setmaxnreg.dec.sync.aligned.u32 56;");
    if (warp >= 9) {
      const int w3 = warp - 9;
      float* red = reinterpret_cast<float*>(smem_raw + (sbase - smem_u32(smem_raw)) + KA_CS + 1024);
      if (lane < 30) {
        float a[8];
#pragma unroll
        for (int i = 0; i < 8; i++) a[i] = 0.f;
        const uint4* w = reinterpret_cast<const uint4*>(wqkv + (size_t)(m_blk * 40) * (3 * DM) + n_blk * 240) + lane;
#pragma unroll
        for (int r = w3; r < 42; r += 3) {
          if (r >= 40) break;
          const uint4 v = __ldg(w + (size_t)r * (3 * DM / 8));
          a[0] += bf_lo(v.x); a[1] += bf_hi(v.x); a[2] += bf_lo(v.y); a[3] += bf_hi(v.y);
          a[4] += bf_lo(v.z); a[5] += bf_hi(v.z); a[6] += bf_lo(v.w); a[7] += bf_hi(v.w);
        }
#pragma unroll
        for (int i = 0; i < 8; i++) red[w3 * 240 + lane * 8 + i] = a[i];
      }
      named_bar_sync(4, 96);
      for (int c = tid - 288; c < 240; c += 96) g_csp[m_blk * (3 * DM) + n_blk * 240 + c] = (red[c] + red[240 + c]) + red[480 + c];
      named_bar_sync(4, 96);
      if (tid == 288) flag_signal(&g_flag[48 + n_blk]);
      if (warp == 10) {
        named_bar_sync(5, 288);
        if (lane == 0) flag_signal(&g_flag[m_blk]);
      }
      if (lane == 0) {
        flag_wait(&g_flag[m_blk], 8);
        flag_wait(&g_flag[48 + n_blk], 16);
      }
      __syncwarp();
      float* cs_s = reinterpret_cast<float*>(smem_raw + (sbase - smem_u32(smem_raw)) + KA_CS);
      for (int c = tid - 288; c < 240; c += 96) {
        float t = 0.f;
#pragma unroll
        for (int mm = 0; mm < 16; mm++) t += g_csp[mm * (3 * DM) + n_blk * 240 + c];
        cs_s[c] = t;
      }
      float2* rs_s = reinterpret_cast<float2*>(red);
      named_bar_sync(4, 96);
      for (int r = tid - 288; r < 128; r += 96) rs_s[r] = g_rs[m_blk * 128 + r];
      named_bar_sync(6, 352);
    }
    if (tid == 256) {
      auto issue_b = [&](int kb) {
        const int s = kb % NST;
        const uint32_t full = sBar + 8 * s;
        mbar_expect_tx(full, STAGE_BYTES);
        const uint32_t dst = sbase + s * STAGE_BYTES + 8192;
#pragma unroll
        for (int j = 0; j < 2; j++) {
          const int sl = rank * 2 + j;
          tma_load_2d_mc(dst + sl * 4096, &tmB, n_blk * 240 + sl * 64, kb * 32, full, (uint16_t)3);
        }
      };
      for (int kb = 0; kb < NKB; kb++) {
        const int s = kb % NST;
        if (kb >= NST) mbar_wait(sBar + 8 * (NST + s), ((kb / NST) & 1) ^ 1);
        issue_b(kb);
        tma_load_2d(sbase + s * STAGE_BYTES, &tmA, kb * 32, m_blk * 128, sBar + 8 * s);
      }
    }
  } else {
    asm volatile("setmaxnreg.inc.sync.aligned.u32 224;");
    const int wg = __shfl_sync(0xffffffffu, warp >> 2, 0);
    const int wwarp = warp & 3;
    {
      const int row = m_blk * 128 + n_blk * 16 + warp * 2 + (lane >> 4);
      const float2 rs = ln_row_stats(x + (size_t)row * DM, lane & 15);
      if ((lane & 15) == 0) g_rs[row] = rs;
      asm volatile("bar.arrive 5, 288;" ::: "memory");
    }
    TS(0, 1);
    mbar_wait(sBar, 0);
    TS(0, 3);
    float acc[120];
#pragma unroll
    for (int i = 0; i < 120; i++) acc[i] = 0.f;
    if (wg == 0) qkv_mainloop<0>(acc, sbase, sBar, (tid & 127) == 0);
    else qkv_mainloop<1>(acc, sbase, sBar, (tid & 127) == 0);
    wgmma_wait<0>();
    fence_regs(acc);
    TS(0, 4);
    const int g = lane >> 2, c4 = lane & 3;
    float* cs_s = reinterpret_cast<float*>(smem_raw + (sbase - smem_u32(smem_raw)) + KA_CS);
    named_bar_sync(6, 352);
    TS(0, 7);
    const float2* rs_s = reinterpret_cast<const float2*>(smem_raw + (sbase - smem_u32(smem_raw)) + KA_CS + 1024);
    const float2 rs0 = rs_s[wg * 64 + wwarp * 16 + g], rs1 = rs_s[wg * 64 + wwarp * 16 + g + 8];
    const uint32_t stg = sbase + wg * (12 * 3072) + (wwarp * 2) * 384 + g * 16;
    const int hbase = n_blk * 12;
#pragma unroll
    for (int j = 0; j < 30; j++) {
      const int cb = (j * 8) % 20;
      const int hb = (j * 8) / 20;
      int d = cb + c4 * 2;
      int hl = hb;
      if (cb == 16 && c4 >= 2) { d -= 20; hl += 1; }
      const uint32_t a0 = stg + hl * 3072 + (d >> 3) * 128 + (d & 7) * 2;
      const int hg = hbase + hl;
      const float sc = hg < 32 ? ATT_SCALE_LOG2E : 1.0f;
      const float2 cc = *reinterpret_cast<const float2*>(cs_s + j * 8 + c4 * 2);
      const float i0 = rs0.y * sc, i1 = rs1.y * sc;
      st_shared_b32(a0, pack_bf16(fmaf(-rs0.x, cc.x, acc[4 * j]) * i0, fmaf(-rs0.x, cc.y, acc[4 * j + 1]) * i0));
      st_shared_b32(a0 + 384, pack_bf16(fmaf(-rs1.x, cc.x, acc[4 * j + 2]) * i1, fmaf(-rs1.x, cc.y, acc[4 * j + 3]) * i1));
      if (d == 18) {
        const uint32_t pad0 = hg < 32 ? 0u : (hg < 64 ? 0x3f803f80u : 0x00003f80u);
        const uint32_t pad1 = (hg >= 32 && hg < 64) ? 0x00003f80u : 0u;
        st_shared_v2(a0 + 4, pad0, pad1);
        st_shared_v2(a0 + 388, pad0, pad1);
      }
      if (j % 10 == 9) {
        fence_proxy_async();
        named_bar_sync(1 + wg, 128);
        if ((tid & 127) < 4) {
          const int hs = (j / 10) * 4 + (tid & 127);
          bf16* dst = g_img + (size_t)(hbase + hs) * IMG_HEAD_ELEMS + (size_t)(m_blk * 16 + wg * 8) * 192;
          bulk_s2g(dst, sbase + wg * (12 * 3072) + hs * 3072, 3072);
          bulk_commit();
        }
      }
    }
    TS(0, 8);
    if ((tid & 127) < 4) bulk_wait_read();
  }
  __syncwarp();
  TS(0, 5);
  cluster_sync_relaxed();
  TS(0, 6);
}

constexpr int KC_NST1 = 5, KC_NST3 = 6;
constexpr int KC_STAGING = 160 * 1024;
constexpr int KC_BAR = KC_STAGING + 48 * 1024;
constexpr int KC_CS = KC_BAR + 512;
constexpr int KC_SMEM = KC_CS + 1536 + 1024;

__global__ void __launch_bounds__(GT, 1)
mlp_kernel(const __grid_constant__ CUtensorMap tmO, const __grid_constant__ CUtensorMap tmWo64, const __grid_constant__ CUtensorMap tmWo16,
           const __grid_constant__ CUtensorMap tmH, const __grid_constant__ CUtensorMap tmWg, const __grid_constant__ CUtensorMap tmWu,
           const __grid_constant__ CUtensorMap tmHHs, const __grid_constant__ CUtensorMap tmHH, const __grid_constant__ CUtensorMap tmWd64,
           const __grid_constant__ CUtensorMap tmWd16, const __grid_constant__ CUtensorMap tmHs, const __grid_constant__ CUtensorMap tmOut,
           const bf16* __restrict__ x) {
  extern __shared__ uint8_t smem_raw[];
  const uint32_t sbase = (smem_u32(smem_raw) + 1023u) & ~1023u;
  const uint32_t bar1 = sbase + KC_BAR;
  const uint32_t bar2 = bar1 + 128;
  const uint32_t bar3 = bar2 + 128;
  const uint32_t barD = bar3 + 128;
  const int tid = threadIdx.x, warp = tid >> 5, lane = tid & 31;
  const int rank = blockIdx.x & 1;
  const int pair = blockIdx.x >> 1;
  const int j_blk = pair & 7;
  const int m_blk = (pair >> 3) * 2 + rank;
  const int n0 = j_blk * 80;
  TS(2, 0);
  if (tid == 256) {
    prefetch_tmap(&tmO); prefetch_tmap(&tmWo64); prefetch_tmap(&tmWo16); prefetch_tmap(&tmH); prefetch_tmap(&tmWg);
    prefetch_tmap(&tmWu); prefetch_tmap(&tmHHs); prefetch_tmap(&tmHH); prefetch_tmap(&tmWd64); prefetch_tmap(&tmWd16);
    prefetch_tmap(&tmHs); prefetch_tmap(&tmOut);
  }
  if (tid == 0) {
    for (int s = 0; s < 5; s++) {
      mbar_init(bar1 + 8 * s, 1); mbar_init(bar1 + 8 * (5 + s), 4);
      mbar_init(bar2 + 8 * s, 1); mbar_init(bar2 + 8 * (5 + s), 4);
    }
    for (int s = 0; s < 6; s++) { mbar_init(bar3 + 8 * s, 1); mbar_init(bar3 + 8 * (6 + s), 4); }
    mbar_init(barD, 4); mbar_init(barD + 8, 4);
    fence_mbar_init();
  }
  cluster_sync_all();

  if (warp >= 8) {
    asm volatile("setmaxnreg.dec.sync.aligned.u32 40;");
    if (tid == 256) {
      auto issue_b80 = [&](const CUtensorMap* t64, const CUtensorMap* t16, uint32_t bars, int nst, int kb) {
        const int s = kb % nst;
        const uint32_t full = bars + 8 * s;
        const uint32_t st = sbase + s * RG_STAGE_BYTES;
        mbar_expect_tx(full, RG_STAGE_BYTES);
        tma_load_2d_mc(st + 16384 + rank * 4096, t64, n0, kb * 64 + rank * 32, full, (uint16_t)3);
        tma_load_2d_mc(st + 16384 + 8192 + rank * 1024, t16, n0 + 64, kb * 64 + rank * 32, full, (uint16_t)3);
      };
      for (int kb = 0; kb < KC_NST1; kb++) issue_b80(&tmWo64, &tmWo16, bar1, KC_NST1, kb);
      pdl_wait();
      for (int kb = 0; kb < 10; kb++) {
        const int s = kb % KC_NST1;
        if (kb >= KC_NST1) {
          mbar_wait(bar1 + 8 * (KC_NST1 + s), ((kb / KC_NST1) & 1) ^ 1);
          issue_b80(&tmWo64, &tmWo16, bar1, KC_NST1, kb);
        }
        tma_load_2d(sbase + s * RG_STAGE_BYTES, &tmO, kb * 64, m_blk * 128, bar1 + 8 * s);
      }
      auto issue_bglu = [&](int kb) {
        const int s = kb % LG_STAGES;
        const uint32_t full = bar2 + 8 * s;
        mbar_expect_tx(full, GLU_STAGE);
        const uint32_t dst = sbase + s * GLU_STAGE + 8192;
#pragma unroll
        for (int j = 0; j < 3; j++)
          tma_load_2d_mc(dst + (rank * 3 + j) * 4096, rank == 0 ? &tmWg : &tmWu, j_blk * 192 + j * 64, kb * 32, full, (uint16_t)3);
      };
      mbar_wait(barD, 0);
      for (int kb = 0; kb < LG_STAGES; kb++) issue_bglu(kb);
      flag_wait(&g_flag[16 + m_blk], 16);
      fence_proxy_async_all();
      for (int kb = 0; kb < 20; kb++) {
        const int s = kb % LG_STAGES;
        if (kb >= LG_STAGES) {
          mbar_wait(bar2 + 8 * (LG_STAGES + s), ((kb / LG_STAGES) & 1) ^ 1);
          issue_bglu(kb);
        }
        tma_load_2d(sbase + s * GLU_STAGE, &tmH, kb * 32, m_blk * 128, bar2 + 8 * s);
      }
      mbar_wait(barD + 8, 0);
      for (int kb = 0; kb < KC_NST3; kb++) issue_b80(&tmWd64, &tmWd16, bar3, KC_NST3, kb);
      flag_wait(&g_flag[32 + m_blk], 16);
      fence_proxy_async_all();
      for (int kb = 0; kb < 24; kb++) {
        const int s = kb % KC_NST3;
        if (kb >= KC_NST3) {
          mbar_wait(bar3 + 8 * (KC_NST3 + s), ((kb / KC_NST3) & 1) ^ 1);
          issue_b80(&tmWd64, &tmWd16, bar3, KC_NST3, kb);
        }
        tma_load_2d(sbase + s * RG_STAGE_BYTES, &tmHH, kb * 64, m_blk * 128, bar3 + 8 * s);
      }
    }
  } else {
    asm volatile("setmaxnreg.inc.sync.aligned.u32 232;");
    const int wg = __shfl_sync(0xffffffffu, warp >> 2, 0);
    const int wwarp = warp & 3;
    const int g = lane >> 2, c4 = lane & 3;
    const int row0 = m_blk * 128 + wg * 64 + wwarp * 16 + g;
    const bool leader = (tid & 127) == 0;
    const uint32_t stg80_base = sbase + KC_STAGING + wg * 24576;
    const uint32_t stg80 = stg80_base + (wwarp * 16 + g) * 160 + c4 * 4;
    {
      uint32_t res[20];
#pragma unroll
      for (int j = 0; j < 10; j++) {
        res[2 * j] = __ldg(reinterpret_cast<const uint32_t*>(x + (size_t)row0 * DM + n0 + j * 8 + c4 * 2));
        res[2 * j + 1] = __ldg(reinterpret_cast<const uint32_t*>(x + (size_t)(row0 + 8) * DM + n0 + j * 8 + c4 * 2));
      }
      float acc0[32], acc1[8];
#pragma unroll
      for (int i = 0; i < 32; i++) acc0[i] = 0.f;
#pragma unroll
      for (int i = 0; i < 8; i++) acc1[i] = 0.f;
      TS(2, 1);
      if (wg == 0) res_mainloop<10, KC_NST1, 0>(acc0, acc1, sbase, bar1, leader);
      else res_mainloop<10, KC_NST1, 1>(acc0, acc1, sbase, bar1, leader);
      wgmma_wait<0>();
      fence_regs(acc0); fence_regs(acc1);
      release_stage(barD, leader);
      TS(2, 4);
      float sum0 = 0.f, sum1 = 0.f;
#pragma unroll
      for (int j = 0; j < 10; j++) {
        const uint32_t a01 = j < 8 ? pack_bf16(acc0[4 * j], acc0[4 * j + 1]) : pack_bf16(acc1[4 * (j - 8)], acc1[4 * (j - 8) + 1]);
        const uint32_t a23 = j < 8 ? pack_bf16(acc0[4 * j + 2], acc0[4 * j + 3]) : pack_bf16(acc1[4 * (j - 8) + 2], acc1[4 * (j - 8) + 3]);
        res[2 * j] = pack_bf16(bf_lo(res[2 * j]) + bf_lo(a01), bf_hi(res[2 * j]) + bf_hi(a01));
        res[2 * j + 1] = pack_bf16(bf_lo(res[2 * j + 1]) + bf_lo(a23), bf_hi(res[2 * j + 1]) + bf_hi(a23));
        st_shared_b32(stg80 + j * 16, res[2 * j]);
        st_shared_b32(stg80 + 8 * 160 + j * 16, res[2 * j + 1]);
        sum0 += bf_lo(res[2 * j]) + bf_hi(res[2 * j]);
        sum1 += bf_lo(res[2 * j + 1]) + bf_hi(res[2 * j + 1]);
      }
      sum0 += __shfl_xor_sync(0xffffffffu, sum0, 1); sum1 += __shfl_xor_sync(0xffffffffu, sum1, 1);
      sum0 += __shfl_xor_sync(0xffffffffu, sum0, 2); sum1 += __shfl_xor_sync(0xffffffffu, sum1, 2);
      const float mu0 = sum0 * (1.0f / 80.0f), mu1 = sum1 * (1.0f / 80.0f);
      float q0 = 0.f, q1 = 0.f;
#pragma unroll
      for (int j = 0; j < 10; j++) {
        float d;
        d = bf_lo(res[2 * j]) - mu0; q0 = fmaf(d, d, q0);
        d = bf_hi(res[2 * j]) - mu0; q0 = fmaf(d, d, q0);
        d = bf_lo(res[2 * j + 1]) - mu1; q1 = fmaf(d, d, q1);
        d = bf_hi(res[2 * j + 1]) - mu1; q1 = fmaf(d, d, q1);
      }
      q0 += __shfl_xor_sync(0xffffffffu, q0, 1); q1 += __shfl_xor_sync(0xffffffffu, q1, 1);
      q0 += __shfl_xor_sync(0xffffffffu, q0, 2); q1 += __shfl_xor_sync(0xffffffffu, q1, 2);
      if (c4 == 0) {
        g_stats[row0 * 8 + j_blk] = make_float2(mu0, q0);
        g_stats[(row0 + 8) * 8 + j_blk] = make_float2(mu1, q1);
      }
      fence_proxy_async();
      named_bar_sync(1 + wg, 128);
      if (leader) {
        tma_store_2d(&tmHs, stg80_base, n0, m_blk * 128 + wg * 64);
        bulk_commit();
        bulk_wait_all();
        fence_proxy_async_all();
        flag_signal(&g_flag[16 + m_blk]);
      }
      TS(2, 5);
    }
    {
      pdl_wait();
      {
        float* cs_s = reinterpret_cast<float*>(smem_raw + (sbase - smem_u32(smem_raw)) + KC_CS);
        for (int i = tid; i < 384; i += 256) cs_s[i] = g_cs[(i >= 192 ? FF - 192 : 0) + j_blk * 192 + i];
        named_bar_sync(3, 256);
      }
      flag_wait(&g_flag[16 + m_blk], 16);
      float mb[2], iv[2];
#pragma unroll
      for (int h = 0; h < 2; h++) {
        const float4* sp = reinterpret_cast<const float4*>(g_stats + (row0 + 8 * h) * 8);
        const float4 p0 = sp[0], p1 = sp[1], p2 = sp[2], p3 = sp[3];
        const float mean = (((p0.x + p0.z) + (p1.x + p1.z)) + ((p2.x + p2.z) + (p3.x + p3.z))) * 0.125f;
        float m2 = ((p0.y + p0.w) + (p1.y + p1.w)) + ((p2.y + p2.w) + (p3.y + p3.w));
        float dd = 0.f, d;
        d = p0.x - mean; dd = fmaf(d, d, dd); d = p0.z - mean; dd = fmaf(d, d, dd);
        d = p1.x - mean; dd = fmaf(d, d, dd); d = p1.z - mean; dd = fmaf(d, d, dd);
        d = p2.x - mean; dd = fmaf(d, d, dd); d = p2.z - mean; dd = fmaf(d, d, dd);
        d = p3.x - mean; dd = fmaf(d, d, dd); d = p3.z - mean; dd = fmaf(d, d, dd);
        m2 = fmaf(dd, 80.0f, m2);
        const float var_b = bf16_round(m2 * (1.0f / DM));
        const float den = bf16_round(sqrtf(bf16_round(var_b + 1e-5f)));
        iv[h] = __frcp_rn(den);
        mb[h] = bf16_round(mean);
      }
      float accg[96], accu[96];
#pragma unroll
      for (int i = 0; i < 96; i++) { accg[i] = 0.f; accu[i] = 0.f; }
      TS(3, 3);
      if (wg == 0) glu_mainloop<0>(accg, accu, sbase, bar2, leader);
      else glu_mainloop<1>(accg, accu, sbase, bar2, leader);
      wgmma_wait<0>();
      fence_regs(accg); fence_regs(accu);
      release_stage(barD + 8, leader);
      TS(3, 4);
      const uint32_t stg = sbase + KC_STAGING + wg * 24576 + (wwarp * 16 + g) * 128 + c4 * 4;
      const float* csg = reinterpret_cast<const float*>(smem_raw + (sbase - smem_u32(smem_raw)) + KC_CS) + c4 * 2;
      const float nm0 = -mb[0] * iv[0], nm1 = -mb[1] * iv[1];
#pragma unroll
      for (int sl = 0; sl < 3; sl++) {
#pragma unroll
        for (int jj = 0; jj < 8; jj++) {
          const int j = sl * 8 + jj;
          const float2 cg = *reinterpret_cast<const float2*>(csg + j * 8);
          const float2 cu = *reinterpret_cast<const float2*>(csg + 192 + j * 8);
          const float r0 = fmaxf(fmaf(accg[4 * j], iv[0], nm0 * cg.x), 0.f) * fmaf(accu[4 * j], iv[0], nm0 * cu.x);
          const float r1 = fmaxf(fmaf(accg[4 * j + 1], iv[0], nm0 * cg.y), 0.f) * fmaf(accu[4 * j + 1], iv[0], nm0 * cu.y);
          const float r2 = fmaxf(fmaf(accg[4 * j + 2], iv[1], nm1 * cg.x), 0.f) * fmaf(accu[4 * j + 2], iv[1], nm1 * cu.x);
          const float r3 = fmaxf(fmaf(accg[4 * j + 3], iv[1], nm1 * cg.y), 0.f) * fmaf(accu[4 * j + 3], iv[1], nm1 * cu.y);
          const uint32_t a0 = stg + sl * 8192 + ((jj ^ g) << 4);
          st_shared_b32(a0, pack_bf16(r0, r1));
          st_shared_b32(a0 + 1024, pack_bf16(r2, r3));
        }
        fence_proxy_async();
        named_bar_sync(1 + wg, 128);
        if (leader) {
          tma_store_2d(&tmHHs, sbase + KC_STAGING + wg * 24576 + sl * 8192, j_blk * 192 + sl * 64, m_blk * 128 + wg * 64);
          bulk_commit();
        }
      }
      TS(3, 7);
      if (leader) {
        bulk_wait_all();
        TS(3, 8);
        fence_proxy_async_all();
        flag_signal(&g_flag[32 + m_blk]);
      }
      TS(3, 9);
    }
    {
      uint32_t res[20];
#pragma unroll
      for (int j = 0; j < 10; j++) {
        res[2 * j] = *reinterpret_cast<const uint32_t*>(g_h + (size_t)row0 * DM + n0 + j * 8 + c4 * 2);
        res[2 * j + 1] = *reinterpret_cast<const uint32_t*>(g_h + (size_t)(row0 + 8) * DM + n0 + j * 8 + c4 * 2);
      }
      float acc0[32], acc1[8];
#pragma unroll
      for (int i = 0; i < 32; i++) acc0[i] = 0.f;
#pragma unroll
      for (int i = 0; i < 8; i++) acc1[i] = 0.f;
      mbar_wait(bar3, 0);
      TS(4, 3);
      if (wg == 0) res_mainloop<24, KC_NST3, 0>(acc0, acc1, sbase, bar3, leader);
      else res_mainloop<24, KC_NST3, 1>(acc0, acc1, sbase, bar3, leader);
      wgmma_wait<0>();
      fence_regs(acc0); fence_regs(acc1);
      TS(4, 4);
#pragma unroll
      for (int j = 0; j < 10; j++) {
        const uint32_t a01 = j < 8 ? pack_bf16(acc0[4 * j], acc0[4 * j + 1]) : pack_bf16(acc1[4 * (j - 8)], acc1[4 * (j - 8) + 1]);
        const uint32_t a23 = j < 8 ? pack_bf16(acc0[4 * j + 2], acc0[4 * j + 3]) : pack_bf16(acc1[4 * (j - 8) + 2], acc1[4 * (j - 8) + 3]);
        st_shared_b32(stg80 + j * 16, pack_bf16(bf_lo(res[2 * j]) + bf_lo(a01), bf_hi(res[2 * j]) + bf_hi(a01)));
        st_shared_b32(stg80 + 8 * 160 + j * 16, pack_bf16(bf_lo(res[2 * j + 1]) + bf_lo(a23), bf_hi(res[2 * j + 1]) + bf_hi(a23)));
      }
      fence_proxy_async();
      named_bar_sync(1 + wg, 128);
      if (leader) {
        tma_store_2d(&tmOut, stg80_base, n0, m_blk * 128 + wg * 64);
        bulk_commit();
        bulk_wait_read();
      }
      TS(4, 5);
    }
  }
  __syncwarp();
  cluster_sync_relaxed();
  TS(4, 6);
}

constexpr int AT_THREADS = 512;
constexpr int AT_WGS = AT_THREADS / 128;
#define AT_CHUNK_MASK 3
#define AT_STAGGER 0
constexpr int AT_KV_BYTES = IMG_HEAD_ELEMS * 2;
constexpr int AT_SMEM = 2 * AT_KV_BYTES + 256 + 1024;
constexpr int AT_CHUNKS = 8;

__device__ __forceinline__ float exp2_poly(float x) {
  const float u = __saturatef(fmaf(x, 1.0f / 64.0f, 62.0f / 64.0f));
  const float MAGIC = 12582912.0f - 62.0f;
  const float r = fmaf(u, 64.0f, MAGIC);
  const float q = MAGIC - r;
  const float fr = fmaf(u, 64.0f, q);
  float p = fmaf(fr, 0.009570102207362652f, 0.05591785907745361f);
  p = fmaf(p, fr, 0.240247443318367f);
  p = fmaf(p, fr, 0.6931217908859253f);
  p = fmaf(p, fr, 0.9999992847442627f);
  return __uint_as_float(__float_as_uint(p) + (__float_as_uint(r) << 23));
}
#define AT_VARIANT 0
#define AT_POLY_MOD 8
__device__ __forceinline__ bool use_poly(int e) {
  return (e % AT_POLY_MOD) == 1;
}

struct AttnState {
  uint32_t qa0, qa1, qa2, qa3, qa4, qa5;
  float M0, M1;
};

__device__ __forceinline__ bool attn_exp_fast(const float (&s)[32], uint32_t (&p)[16]) {
#pragma unroll
  for (int j = 0; j < 16; j++) {
    const float e0 = use_poly(2 * j) ? exp2_poly(s[2 * j]) : ex2(s[2 * j]);
    const float e1 = use_poly(2 * j + 1) ? exp2_poly(s[2 * j + 1]) : ex2(s[2 * j + 1]);
    p[j] = pack_bf16(e0, e1);
  }
  uint32_t acc_or = 0;
#pragma unroll
  for (int j = 0; j < 16; j++) acc_or |= p[j];
  return __any_sync(0xffffffffu, (acc_or & 0x40004000u) != 0);
}
__device__ __forceinline__ void attn_exp_exact(const float (&s)[32], uint32_t (&p)[16], float (&o)[12], AttnState& st, bool first, int c4) {
  float mx0 = fmaxf(s[0], s[1]), mx1 = fmaxf(s[2], s[3]);
#pragma unroll
  for (int j = 1; j < 8; j++) {
    mx0 = fmaxf(mx0, fmaxf(s[4 * j], s[4 * j + 1]));
    mx1 = fmaxf(mx1, fmaxf(s[4 * j + 2], s[4 * j + 3]));
  }
  mx0 = fmaxf(mx0, __shfl_xor_sync(0xffffffffu, mx0, 1));
  mx1 = fmaxf(mx1, __shfl_xor_sync(0xffffffffu, mx1, 1));
  mx0 = fmaxf(mx0, __shfl_xor_sync(0xffffffffu, mx0, 2));
  mx1 = fmaxf(mx1, __shfl_xor_sync(0xffffffffu, mx1, 2));
  float d0 = mx0 + 7.0f, d1 = mx1 + 7.0f;
  if (!first) { d0 = fmaxf(d0, 0.f); d1 = fmaxf(d1, 0.f); }
  const float T0 = st.M0 + d0, T1 = st.M1 + d1;
  const float h0 = bf16_round(T0), h1 = bf16_round(T1);
  const float i0 = bf16_round(T0 - h0), i1 = bf16_round(T1 - h1);
  const float l0 = bf16_round((T0 - h0) - i0), l1 = bf16_round((T1 - h1) - i1);
  const float N0 = (h0 + i0) + l0, N1 = (h1 + i1) + l1;
  d0 = N0 - st.M0; d1 = N1 - st.M1;
  st.M0 = N0; st.M1 = N1;
  if (c4 == 2) { st.qa4 = pack_bf16(-h0, -i0); st.qa5 = pack_bf16(-h1, -i1); }
  if (c4 == 3) { st.qa4 = pack_bf16(-l0, 0.f); st.qa5 = pack_bf16(-l1, 0.f); }
  if (!first) {
    const float al0 = ex2(-d0), al1 = ex2(-d1);
#pragma unroll
    for (int j = 0; j < 3; j++) {
      o[4 * j] *= al0; o[4 * j + 1] *= al0;
      o[4 * j + 2] *= al1; o[4 * j + 3] *= al1;
    }
  }
#pragma unroll
  for (int j = 0; j < 8; j++) {
    p[2 * j] = pack_bf16(ex2(s[4 * j] - d0), ex2(s[4 * j + 1] - d0));
    p[2 * j + 1] = pack_bf16(ex2(s[4 * j + 2] - d1), ex2(s[4 * j + 3] - d1));
  }
}
__device__ __forceinline__ void attn_step(float (&s)[32], const uint32_t (&pp)[16], uint32_t (&pn)[16], float (&o)[12], AttnState& st,
                                          uint32_t k_addr, uint32_t v_addr_prev, int keep, int c4, int wgdbg = 0, int tdbg = 0) {
  PH(wgdbg, tdbg, 0);
  const uint64_t dk = make_desc(k_addr, 128, 384, 0);
  const uint64_t dv_prev = make_desc(v_addr_prev, 384, 128, 0);
  wgmma_fence();
  wgmma_rs_n64(s, st.qa0, st.qa1, st.qa2, st.qa3, dk, 0);
  wgmma_rs_n64(s, st.qa4, st.qa5, 0u, 0u, dk + 16, 1);
  wgmma_commit();
#pragma unroll
  for (int kk = 0; kk < 4; kk++) wgmma_rs_n24_tb(o, pp[4 * kk], pp[4 * kk + 1], pp[4 * kk + 2], pp[4 * kk + 3], dv_prev + kk * 48, kk == 0 ? keep : 1);
  wgmma_commit();
  wgmma_wait<1>();
  fence_regs(s);
  PH(wgdbg, tdbg, 1);
  const bool redo = attn_exp_fast(s, pn);
  PH(wgdbg, tdbg, 2);
  wgmma_wait<0>();
  fence_regs(o);
  if (redo) attn_exp_exact(s, pn, o, st, false, c4);
}

__global__ void __launch_bounds__(AT_THREADS, 1) attn_kernel(const bf16* __restrict__ wo, const bf16* __restrict__ wgt, const bf16* __restrict__ wup, const bf16* __restrict__ wdn) {
  extern __shared__ uint8_t smem_raw[];
  const uint32_t sbase = (smem_u32(smem_raw) + 1023u) & ~1023u;
  const uint32_t sK = sbase, sV = sbase + AT_KV_BYTES;
  const uint32_t sBar = sV + AT_KV_BYTES;
  const int tid = threadIdx.x, warp = tid >> 5, lane = tid & 31;
  const int head = blockIdx.x >> 2, quarter = blockIdx.x & 3;
  if (blockIdx.x >= 128) {
    pdl_launch();
    const int b = blockIdx.x - 128;
    const bf16* w = (b >> 1) ? wup : wgt;
    const int cgrp = tid % 96, rgrp = tid / 96;
    float acc[8];
#pragma unroll
    for (int i = 0; i < 8; i++) acc[i] = 0.f;
    float* red = reinterpret_cast<float*>(smem_raw);
    if (rgrp < 5) {
      const uint4* src = reinterpret_cast<const uint4*>(w + (size_t)(rgrp * 128) * FF + (b & 1) * 768 + cgrp * 8);
#pragma unroll 8
      for (int r = 0; r < 128; r++) {
        const uint4 v = __ldg(src + (size_t)r * (FF / 8));
        acc[0] += bf_lo(v.x); acc[1] += bf_hi(v.x); acc[2] += bf_lo(v.y); acc[3] += bf_hi(v.y);
        acc[4] += bf_lo(v.z); acc[5] += bf_hi(v.z); acc[6] += bf_lo(v.w); acc[7] += bf_hi(v.w);
      }
#pragma unroll
      for (int i = 0; i < 8; i++) red[rgrp * 768 + cgrp * 8 + i] = acc[i];
    }
    __syncthreads();
    pdl_wait();
    for (int c = tid; c < 768; c += AT_THREADS)
      g_cs[(b >> 1) * FF + (b & 1) * 768 + c] = ((red[c] + red[768 + c]) + (red[1536 + c] + red[2304 + c])) + red[3072 + c];
    if (b == 0 && tid < 16) g_flag[tid] = 0;
    if (b == 0 && tid < 8) g_flag[48 + tid] = 0;
    return;
  }
  TS(1, 0);
  if (tid == 0) {
    for (int i = 0; i < AT_CHUNKS; i++) mbar_init(sBar + 8 * i, 1);
    fence_mbar_init();
  }
  pdl_launch();
  if (tid == 32) {
    prefetch_l2(reinterpret_cast<const uint8_t*>(wo) + blockIdx.x * 6400, 6400);
    prefetch_l2(reinterpret_cast<const uint8_t*>(wgt) + blockIdx.x * 15360, 15360);
    prefetch_l2(reinterpret_cast<const uint8_t*>(wup) + blockIdx.x * 15360, 15360);
    prefetch_l2(reinterpret_cast<const uint8_t*>(wdn) + blockIdx.x * 15360, 15360);
  }
  __syncthreads();
  TS(1, 1);
  pdl_wait();
  TS(1, 2);
  if (tid == 0) {
    const uint8_t* kg = reinterpret_cast<const uint8_t*>(g_img + (size_t)(32 + head) * IMG_HEAD_ELEMS);
    const uint8_t* vg = reinterpret_cast<const uint8_t*>(g_img + (size_t)(64 + head) * IMG_HEAD_ELEMS);
    constexpr int CB = AT_KV_BYTES / AT_CHUNKS;
    for (int i = 0; i < AT_CHUNKS; i++) {
      mbar_expect_tx(sBar + 8 * i, 2 * CB);
      bulk_g2s(sK + i * CB, kg + i * CB, CB, sBar + 8 * i);
      bulk_g2s(sV + i * CB, vg + i * CB, CB, sBar + 8 * i);
    }
  }
  const int wg = warp >> 2, wwarp = warp & 3;
  const int g = lane >> 2, c4 = lane & 3;
  const uint64_t dk_base = make_desc(sK, 128, 384, 0);
  const uint64_t dv_base = make_desc(sV, 384, 128, 0);

#pragma unroll 1
  for (int rep = 0; rep < 8 / AT_WGS; rep++) {
    const int row0 = quarter * 512 + (rep * AT_WGS + wg) * 64 + wwarp * 16 + g;
    AttnState st;
    {
      const bf16* q0 = g_img + (size_t)head * IMG_HEAD_ELEMS + (size_t)(row0 >> 3) * 192 + g * 8 + c4 * 2;
      const bf16* q1 = q0 + 192;
      st.qa0 = *reinterpret_cast<const uint32_t*>(q0);
      st.qa1 = *reinterpret_cast<const uint32_t*>(q1);
      st.qa2 = *reinterpret_cast<const uint32_t*>(q0 + 64);
      st.qa3 = *reinterpret_cast<const uint32_t*>(q1 + 64);
      st.qa4 = *reinterpret_cast<const uint32_t*>(q0 + 128);
      st.qa5 = *reinterpret_cast<const uint32_t*>(q1 + 128);
    }
    float o[12];
    float s[32];
    uint32_t pa[16], pb[16];
    st.M0 = st.M1 = 0.f;
    if (rep == 0) mbar_wait(sBar, 0);
    wgmma_fence();
    wgmma_rs_n64(s, st.qa0, st.qa1, st.qa2, st.qa3, dk_base, 0);
    wgmma_rs_n64(s, st.qa4, st.qa5, 0u, 0u, dk_base + 16, 1);
    wgmma_commit();
    wgmma_wait<0>();
    fence_regs(s);
    attn_exp_exact(s, pa, o, st, true, c4);
    attn_step(s, pa, pb, o, st, sK + 3072, sV, 0, c4);
#pragma unroll 1
    for (int tt = 1; tt < 16; tt++) {
      if (rep == 0 && !(tt & 1)) mbar_wait(sBar + 8 * (tt >> 1), 0);
      attn_step(s, pb, pa, o, st, sK + tt * 6144, sV + tt * 6144 - 3072, 1, c4, wg, rep * 32 + tt * 2);
      attn_step(s, pa, pb, o, st, sK + tt * 6144 + 3072, sV + tt * 6144, 1, c4, wg, rep * 32 + tt * 2 + 1);
    }
    wgmma_fence();
#pragma unroll
    for (int kk = 0; kk < 4; kk++) wgmma_rs_n24_tb(o, pb[4 * kk], pb[4 * kk + 1], pb[4 * kk + 2], pb[4 * kk + 3], dv_base + 31 * 192 + kk * 48, 1);
    wgmma_commit();
    wgmma_wait<0>();
    fence_regs(o);
    TS(1, 3 + rep);
    const float l0 = __shfl_sync(0xffffffffu, o[8], (lane & ~3) | 2);
    const float l1 = __shfl_sync(0xffffffffu, o[10], (lane & ~3) | 2);
    const float i0 = 1.0f / l0, i1 = 1.0f / l1;
    bf16* o0 = g_o + (size_t)row0 * DM + head * DH;
    bf16* o1 = o0 + 8 * DM;
#pragma unroll
    for (int j = 0; j < 3; j++) {
      if (j < 2 || c4 < 2) {
        *reinterpret_cast<uint32_t*>(o0 + j * 8 + c4 * 2) = pack_bf16(o[4 * j] * i0, o[4 * j + 1] * i0);
        *reinterpret_cast<uint32_t*>(o1 + j * 8 + c4 * 2) = pack_bf16(o[4 * j + 2] * i1, o[4 * j + 3] * i1);
      }
    }
  }
}

typedef CUresult (*EncodeTiledFn)(CUtensorMap*, CUtensorMapDataType, cuuint32_t, void*, const cuuint64_t*, const cuuint64_t*,
                                  const cuuint32_t*, const cuuint32_t*, CUtensorMapInterleave, CUtensorMapSwizzle,
                                  CUtensorMapL2promotion, CUtensorMapFloatOOBfill);

static void make_map(EncodeTiledFn fn, CUtensorMap* tm, const void* ptr, uint64_t rows, uint64_t cols, uint32_t box_rows,
                     uint32_t box_cols, CUtensorMapSwizzle sw) {
  cuuint64_t dims[2] = {cols, rows};
  cuuint64_t strides[1] = {cols * 2};
  cuuint32_t box[2] = {box_cols, box_rows};
  cuuint32_t es[2] = {1, 1};
  fn(tm, CU_TENSOR_MAP_DATA_TYPE_BFLOAT16, 2, const_cast<void*>(ptr), dims, strides, box, es, CU_TENSOR_MAP_INTERLEAVE_NONE, sw,
     CU_TENSOR_MAP_L2_PROMOTION_L2_256B, CU_TENSOR_MAP_FLOAT_OOB_FILL_NONE);
}

template <typename... KArgs, typename... Args>
static void launch(void (*kern)(KArgs...), int grid, int block, int smem, int cluster, bool pdl, Args... args) {
  cudaLaunchConfig_t cfg = {};
  cfg.gridDim = dim3(grid);
  cfg.blockDim = dim3(block);
  cfg.dynamicSmemBytes = smem;
  cfg.stream = cudaStreamPerThread;
  cudaLaunchAttribute at[2];
  int n = 0;
  if (cluster > 1) {
    at[n].id = cudaLaunchAttributeClusterDimension;
    at[n].val.clusterDim.x = cluster; at[n].val.clusterDim.y = 1; at[n].val.clusterDim.z = 1;
    n++;
  }
  if (pdl) {
    at[n].id = cudaLaunchAttributeProgrammaticStreamSerialization;
    at[n].val.programmaticStreamSerializationAllowed = 1;
    n++;
  }
  cfg.attrs = at;
  cfg.numAttrs = n;
  cudaLaunchKernelEx(&cfg, kern, KArgs(args)...);
}

extern "C" void kernel_launch(void* const* d_in, const int* in_sizes, int n_in, void* d_out, int out_size) {
  const bf16* x = (const bf16*)d_in[0];
  const bf16* wqkv = (const bf16*)d_in[1];
  const bf16* wo = (const bf16*)d_in[2];
  const bf16* wg = (const bf16*)d_in[4];
  const bf16* wu = (const bf16*)d_in[5];
  const bf16* wd = (const bf16*)d_in[6];
  bf16* out = (bf16*)d_out;

  static EncodeTiledFn enc = nullptr;
  static void *p_o = nullptr, *p_h = nullptr, *p_hh = nullptr;
  if (!enc) {
    void* fn = nullptr;
    cudaDriverEntryPointQueryResult qr;
    cudaGetDriverEntryPoint("cuTensorMapEncodeTiled", &fn, cudaEnableDefault, &qr);
    enc = (EncodeTiledFn)fn;
    cudaGetSymbolAddress(&p_o, g_o);
    cudaGetSymbolAddress(&p_h, g_h);
    cudaGetSymbolAddress(&p_hh, g_hh);
    cudaFuncSetAttribute(qkv_kernel, cudaFuncAttributeMaxDynamicSharedMemorySize, KA_SMEM);
    cudaFuncSetAttribute(mlp_kernel, cudaFuncAttributeMaxDynamicSharedMemorySize, KC_SMEM);
    cudaFuncSetAttribute(attn_kernel, cudaFuncAttributeMaxDynamicSharedMemorySize, AT_SMEM);
  }
  CUtensorMap tm_wqkv, tm_wg, tm_wu, tm_wo64, tm_wo16, tm_wd64, tm_wd16, tm_o, tm_h, tm_hh, tm_hhs, tm_xn, tm_hs, tm_out;
  make_map(enc, &tm_wqkv, wqkv, DM, 3 * DM, 32, 64, CU_TENSOR_MAP_SWIZZLE_128B);
  make_map(enc, &tm_wg, wg, DM, FF, 32, 64, CU_TENSOR_MAP_SWIZZLE_128B);
  make_map(enc, &tm_wu, wu, DM, FF, 32, 64, CU_TENSOR_MAP_SWIZZLE_128B);
  make_map(enc, &tm_wo64, wo, DM, DM, 32, 64, CU_TENSOR_MAP_SWIZZLE_128B);
  make_map(enc, &tm_wo16, wo, DM, DM, 32, 16, CU_TENSOR_MAP_SWIZZLE_32B);
  make_map(enc, &tm_wd64, wd, FF, DM, 32, 64, CU_TENSOR_MAP_SWIZZLE_128B);
  make_map(enc, &tm_wd16, wd, FF, DM, 32, 16, CU_TENSOR_MAP_SWIZZLE_32B);
  make_map(enc, &tm_o, p_o, SEQ, DM, 128, 64, CU_TENSOR_MAP_SWIZZLE_128B);
  make_map(enc, &tm_h, p_h, SEQ, DM, 128, 32, CU_TENSOR_MAP_SWIZZLE_64B);
  make_map(enc, &tm_hh, p_hh, SEQ, FF, 128, 64, CU_TENSOR_MAP_SWIZZLE_128B);
  make_map(enc, &tm_hhs, p_hh, SEQ, FF, 64, 64, CU_TENSOR_MAP_SWIZZLE_128B);
  make_map(enc, &tm_xn, x, SEQ, DM, 128, 32, CU_TENSOR_MAP_SWIZZLE_64B);
  make_map(enc, &tm_hs, p_h, SEQ, DM, 64, 80, CU_TENSOR_MAP_SWIZZLE_NONE);
  make_map(enc, &tm_out, out, SEQ, DM, 64, 80, CU_TENSOR_MAP_SWIZZLE_NONE);

  launch(qkv_kernel, 128, GT, KA_SMEM, 2, false, tm_xn, tm_wqkv, x, wqkv);
  launch(attn_kernel, 132, AT_THREADS, AT_SMEM, 1, true, wo, wg, wu, wd);
  launch(mlp_kernel, 128, GT, KC_SMEM, 2, true, tm_o, tm_wo64, tm_wo16, tm_h, tm_wg, tm_wu, tm_hhs, tm_hh, tm_wd64, tm_wd16, tm_hs, tm_out, x);
}
```

```cpp
#include <cuda_runtime.h>
#include <cuda_bf16.h>
#include <cuda.h>
#include <stdint.h>

typedef __nv_bfloat16 bf16;
#define FLAGV 0

constexpr int SEQ = 2048, DM = 640, NH = 32, DH = 20, FF = 1536;
constexpr float ATT_SCALE_LOG2E = 0.22360679774997896f * 1.4426950408889634f;
constexpr int IMG_HEAD_ELEMS = (SEQ / 8) * 192;

__device__ __align__(1024) bf16 g_img[3 * NH * IMG_HEAD_ELEMS];
__device__ __align__(1024) bf16 g_o[SEQ * DM];
__device__ __align__(1024) bf16 g_h[SEQ * DM];
__device__ float2 g_stats[SEQ * 8];
__device__ float g_cs[2 * FF];
__device__ int g_flag[4 * 16];
__device__ float g_csp[16 * 3 * DM];
__device__ float2 g_rs[SEQ];
__device__ __align__(1024) bf16 g_hh[SEQ * FF];

#define TS(k, i)
#define PH(w, t, i)
__device__ __forceinline__ uint32_t smem_u32(const void* p) { return (uint32_t)__cvta_generic_to_shared(p); }
__device__ __forceinline__ void mbar_init(uint32_t bar, uint32_t cnt) {
  asm volatile("mbarrier.init.shared::cta.b64 [%0], %1;" ::"r"(bar), "r"(cnt) : "memory");
}
__device__ __forceinline__ void mbar_expect_tx(uint32_t bar, uint32_t bytes) {
  asm volatile("mbarrier.arrive.expect_tx.shared::cta.b64 _, [%0], %1;" ::"r"(bar), "r"(bytes) : "memory");
}
__device__ __forceinline__ void mbar_arrive(uint32_t bar) {
  asm volatile("mbarrier.arrive.shared::cta.b64 _, [%0];" ::"r"(bar) : "memory");
}
__device__ __forceinline__ void mbar_arrive_cluster(uint32_t bar, uint32_t cta) {
  asm volatile(
      "{\n.reg .b32 r;\nmapa.shared::cluster.u32 r, %0, %1;\n"
      "mbarrier.arrive.shared::cluster.b64 _, [r];\n}\n" ::"r"(bar), "r"(cta)
      : "memory");
}
__device__ __forceinline__ void mbar_wait(uint32_t bar, uint32_t parity) {
  asm volatile(
      "{\n.reg .pred p;\nLAB_WAIT:\n"
      "mbarrier.try_wait.parity.shared::cta.b64 p, [%0], %1;\n"
      "@p bra DONE;\nbra LAB_WAIT;\nDONE:\n}\n" ::"r"(bar), "r"(parity)
      : "memory");
}
__device__ __forceinline__ void mbar_wait_cluster(uint32_t bar, uint32_t parity) {
  asm volatile(
      "{\n.reg .pred p;\nLAB_WAIT:\n"
      "mbarrier.try_wait.parity.acquire.cluster.shared::cta.b64 p, [%0], %1;\n"
      "@p bra DONE;\nbra LAB_WAIT;\nDONE:\n}\n" ::"r"(bar), "r"(parity)
      : "memory");
}
__device__ __forceinline__ void fence_mbar_init() { asm volatile("fence.mbarrier_init.release.cluster;" ::: "memory"); }
__device__ __forceinline__ void fence_proxy_async() { asm volatile("fence.proxy.async.shared::cta;" ::: "memory"); }
__device__ __forceinline__ void cluster_sync_all() {
  asm volatile("barrier.cluster.arrive.release.aligned;\nbarrier.cluster.wait.acquire.aligned;" ::: "memory");
}
__device__ __forceinline__ void cluster_sync_relaxed() {
  asm volatile("barrier.cluster.arrive.relaxed.aligned;\nbarrier.cluster.wait.aligned;" ::: "memory");
}
__device__ __forceinline__ void named_bar_sync(int id, int n) { asm volatile("bar.sync %0, %1;" ::"r"(id), "r"(n) : "memory"); }
__device__ __forceinline__ bool wg_any(bool pred, int id) {
  uint32_t r;
  asm volatile("{\n.reg .pred p, q;\nsetp.ne.u32 p, %1, 0;\nbar.red.or.pred q, %2, 128, p;\nselp.u32 %0, 1, 0, q;\n}\n" : "=r"(r) : "r"((uint32_t)pred), "r"(id) : "memory");
  return r != 0;
}
__device__ __forceinline__ void fence_proxy_async_all() { asm volatile("fence.proxy.async;" ::: "memory"); }
__device__ __forceinline__ void flag_signal(int* f) {
  __threadfence();
  atomicAdd(f, 1);
}
__device__ __forceinline__ void flag_wait(const int* f, int target) {
  int v;
  unsigned spins = 0;
  do {
    asm volatile("ld.acquire.gpu.global.s32 %0, [%1];" : "=r"(v) : "l"(f) : "memory");
    if (++spins > (1u << 24)) __trap();
  } while (v < target);
}
__device__ __forceinline__ void pdl_launch() { asm volatile("griddepcontrol.launch_dependents;" ::: "memory"); }
__device__ __forceinline__ void pdl_wait() { asm volatile("griddepcontrol.wait;" ::: "memory"); }

__device__ __forceinline__ void tma_load_2d(uint32_t dst, const CUtensorMap* tm, int c0, int c1, uint32_t bar) {
  asm volatile(
      "cp.async.bulk.tensor.2d.shared::cluster.global.mbarrier::complete_tx::bytes [%0], [%1, {%3, %4}], [%2];" ::"r"(dst),
      "l"((uint64_t)tm), "r"(bar), "r"(c0), "r"(c1)
      : "memory");
}
__device__ __forceinline__ void tma_load_2d_mc(uint32_t dst, const CUtensorMap* tm, int c0, int c1, uint32_t bar, uint16_t mask) {
  asm volatile(
      "cp.async.bulk.tensor.2d.shared::cluster.global.mbarrier::complete_tx::bytes.multicast::cluster [%0], [%1, {%3, %4}], [%2], %5;" ::"r"(dst),
      "l"((uint64_t)tm), "r"(bar), "r"(c0), "r"(c1), "h"(mask)
      : "memory");
}
__device__ __forceinline__ void bulk_g2s(uint32_t dst, const void* src, uint32_t bytes, uint32_t bar) {
  asm volatile("cp.async.bulk.shared::cluster.global.mbarrier::complete_tx::bytes [%0], [%1], %2, [%3];" ::"r"(dst), "l"(src),
               "r"(bytes), "r"(bar)
               : "memory");
}
__device__ __forceinline__ void bulk_s2g(void* dst, uint32_t src, uint32_t bytes) {
  asm volatile("cp.async.bulk.global.shared::cta.bulk_group [%0], [%1], %2;" ::"l"(dst), "r"(src), "r"(bytes) : "memory");
}
__device__ __forceinline__ void tma_store_2d(const CUtensorMap* tm, uint32_t src, int c0, int c1) {
  asm volatile("cp.async.bulk.tensor.2d.global.shared::cta.bulk_group [%0, {%2, %3}], [%1];" ::"l"((uint64_t)tm), "r"(src), "r"(c0), "r"(c1) : "memory");
}
__device__ __forceinline__ void bulk_commit() { asm volatile("cp.async.bulk.commit_group;" ::: "memory"); }
__device__ __forceinline__ void bulk_wait_read() { asm volatile("cp.async.bulk.wait_group.read 0;" ::: "memory"); }
__device__ __forceinline__ void prefetch_l2(const void* p, uint32_t bytes) {
  asm volatile("cp.async.bulk.prefetch.L2.global [%0], %1;" ::"l"(p), "r"(bytes) : "memory");
}
__device__ __forceinline__ void bulk_wait_all() { asm volatile("cp.async.bulk.wait_group 0;" ::: "memory"); }
__device__ __forceinline__ void st_shared_b32(uint32_t addr, uint32_t v) { asm volatile("st.shared.b32 [%0], %1;" ::"r"(addr), "r"(v) : "memory"); }
__device__ __forceinline__ void st_shared_v2(uint32_t addr, uint32_t a, uint32_t b) { asm volatile("st.shared.v2.b32 [%0], {%1, %2};" ::"r"(addr), "r"(a), "r"(b) : "memory"); }
__device__ __forceinline__ void prefetch_tmap(const CUtensorMap* tm) {
  asm volatile("prefetch.tensormap [%0];" ::"l"((uint64_t)tm) : "memory");
}
__device__ __forceinline__ void wgmma_fence() { asm volatile("wgmma.fence.sync.aligned;" ::: "memory"); }
__device__ __forceinline__ void wgmma_commit() { asm volatile("wgmma.commit_group.sync.aligned;" ::: "memory"); }
template <int N>
__device__ __forceinline__ void wgmma_wait() { asm volatile("wgmma.wait_group.sync.aligned %0;" ::"n"(N) : "memory"); }

template <int N>
__device__ __forceinline__ void fence_regs(float (&r)[N]) {
#pragma unroll
  for (int i = 0; i < N; i++) asm volatile("" : "+f"(r[i])::"memory");
}
template <int N>
__device__ __forceinline__ void fence_regs(uint32_t (&r)[N]) {
#pragma unroll
  for (int i = 0; i < N; i++) asm volatile("" : "+r"(r[i])::"memory");
}
__device__ __forceinline__ uint64_t make_desc(uint32_t addr, uint32_t lbo, uint32_t sbo, uint32_t layout) {
  return (uint64_t)((addr & 0x3FFFF) >> 4) | ((uint64_t)((lbo & 0x3FFFF) >> 4) << 16) | ((uint64_t)((sbo & 0x3FFFF) >> 4) << 32) |
         ((uint64_t)layout << 62);
}
__device__ __forceinline__ uint32_t pack_bf16(float lo, float hi) {
  uint32_t r;
  asm("cvt.rn.bf16x2.f32 %0, %1, %2;" : "=r"(r) : "f"(hi), "f"(lo));
  return r;
}
__device__ __forceinline__ float bf16_round(float x) { return __bfloat162float(__float2bfloat16_rn(x)); }
__device__ __forceinline__ float bf_lo(uint32_t u) { return __uint_as_float(u << 16); }
__device__ __forceinline__ float bf_hi(uint32_t u) { return __uint_as_float(u & 0xffff0000u); }
__device__ __forceinline__ float ex2(float x) {
  float y;
  asm("ex2.approx.ftz.f32 %0, %1;" : "=f"(y) : "f"(x));
  return y;
}

__device__ __forceinline__ void wgmma_ss_n240_tb(float (&d)[120], uint64_t descA, uint64_t descB, int scaleD) {
  asm volatile("{\n.reg .pred p;\nsetp.ne.b32 p, %122, 0;\n"
    "wgmma.mma_async.sync.aligned.m64n240k16.f32.bf16.bf16 {%0, %1, %2, %3, %4, %5, %6, %7, %8, %9, %10, %11, %12, %13, %14, %15, %16, %17, %18, %19, %20, %21, %22, %23, %24, %25, %26, %27, %28, %29, %30, %31, %32, %33, %34, %35, %36, %37, %38, %39, %40, %41, %42, %43, %44, %45, %46, %47, %48, %49, %50, %51, %52, %53, %54, %55, %56, %57, %58, %59, %60, %61, %62, %63, %64, %65, %66, %67, %68, %69, %70, %71, %72, %73, %74, %75, %76, %77, %78, %79, %80, %81, %82, %83, %84, %85, %86, %87, %88, %89, %90, %91, %92, %93, %94, %95, %96, %97, %98, %99, %100, %101, %102, %103, %104, %105, %106, %107, %108, %109, %110, %111, %112, %113, %114, %115, %116, %117, %118, %119}, %120, %121, p, 1, 1, 0, 1;\n}\n"
    : "+f"(d[0]), "+f"(d[1]), "+f"(d[2]), "+f"(d[3]), "+f"(d[4]), "+f"(d[5]), "+f"(d[6]), "+f"(d[7]), "+f"(d[8]), "+f"(d[9]), "+f"(d[10]), "+f"(d[11]), "+f"(d[12]), "+f"(d[13]), "+f"(d[14]), "+f"(d[15]), "+f"(d[16]), "+f"(d[17]), "+f"(d[18]), "+f"(d[19]), "+f"(d[20]), "+f"(d[21]), "+f"(d[22]), "+f"(d[23]), "+f"(d[24]), "+f"(d[25]), "+f"(d[26]), "+f"(d[27]), "+f"(d[28]), "+f"(d[29]), "+f"(d[30]), "+f"(d[31]), "+f"(d[32]), "+f"(d[33]), "+f"(d[34]), "+f"(d[35]), "+f"(d[36]), "+f"(d[37]), "+f"(d[38]), "+f"(d[39]), "+f"(d[40]), "+f"(d[41]), "+f"(d[42]), "+f"(d[43]), "+f"(d[44]), "+f"(d[45]), "+f"(d[46]), "+f"(d[47]), "+f"(d[48]), "+f"(d[49]), "+f"(d[50]), "+f"(d[51]), "+f"(d[52]), "+f"(d[53]), "+f"(d[54]), "+f"(d[55]), "+f"(d[56]), "+f"(d[57]), "+f"(d[58]), "+f"(d[59]), "+f"(d[60]), "+f"(d[61]), "+f"(d[62]), "+f"(d[63]), "+f"(d[64]), "+f"(d[65]), "+f"(d[66]), "+f"(d[67]), "+f"(d[68]), "+f"(d[69]), "+f"(d[70]), "+f"(d[71]), "+f"(d[72]), "+f"(d[73]), "+f"(d[74]), "+f"(d[75]), "+f"(d[76]), "+f"(d[77]), "+f"(d[78]), "+f"(d[79]), "+f"(d[80]), "+f"(d[81]), "+f"(d[82]), "+f"(d[83]), "+f"(d[84]), "+f"(d[85]), "+f"(d[86]), "+f"(d[87]), "+f"(d[88]), "+f"(d[89]), "+f"(d[90]), "+f"(d[91]), "+f"(d[92]), "+f"(d[93]), "+f"(d[94]), "+f"(d[95]), "+f"(d[96]), "+f"(d[97]), "+f"(d[98]), "+f"(d[99]), "+f"(d[100]), "+f"(d[101]), "+f"(d[102]), "+f"(d[103]), "+f"(d[104]), "+f"(d[105]), "+f"(d[106]), "+f"(d[107]), "+f"(d[108]), "+f"(d[109]), "+f"(d[110]), "+f"(d[111]), "+f"(d[112]), "+f"(d[113]), "+f"(d[114]), "+f"(d[115]), "+f"(d[116]), "+f"(d[117]), "+f"(d[118]), "+f"(d[119])
    : "l"(descA), "l"(descB), "r"(scaleD));
}
__device__ __forceinline__ void wgmma_ss_n192_tb(float (&d)[96], uint64_t descA, uint64_t descB, int scaleD) {
  asm volatile("{\n.reg .pred p;\nsetp.ne.b32 p, %98, 0;\n"
    "wgmma.mma_async.sync.aligned.m64n192k16.f32.bf16.bf16 {%0, %1, %2, %3, %4, %5, %6, %7, %8, %9, %10, %11, %12, %13, %14, %15, %16, %17, %18, %19, %20, %21, %22, %23, %24, %25, %26, %27, %28, %29, %30, %31, %32, %33, %34, %35, %36, %37, %38, %39, %40, %41, %42, %43, %44, %45, %46, %47, %48, %49, %50, %51, %52, %53, %54, %55, %56, %57, %58, %59, %60, %61, %62, %63, %64, %65, %66, %67, %68, %69, %70, %71, %72, %73, %74, %75, %76, %77, %78, %79, %80, %81, %82, %83, %84, %85, %86, %87, %88, %89, %90, %91, %92, %93, %94, %95}, %96, %97, p, 1, 1, 0, 1;\n}\n"
    : "+f"(d[0]), "+f"(d[1]), "+f"(d[2]), "+f"(d[3]), "+f"(d[4]), "+f"(d[5]), "+f"(d[6]), "+f"(d[7]), "+f"(d[8]), "+f"(d[9]), "+f"(d[10]), "+f"(d[11]), "+f"(d[12]), "+f"(d[13]), "+f"(d[14]), "+f"(d[15]), "+f"(d[16]), "+f"(d[17]), "+f"(d[18]), "+f"(d[19]), "+f"(d[20]), "+f"(d[21]), "+f"(d[22]), "+f"(d[23]), "+f"(d[24]), "+f"(d[25]), "+f"(d[26]), "+f"(d[27]), "+f"(d[28]), "+f"(d[29]), "+f"(d[30]), "+f"(d[31]), "+f"(d[32]), "+f"(d[33]), "+f"(d[34]), "+f"(d[35]), "+f"(d[36]), "+f"(d[37]), "+f"(d[38]), "+f"(d[39]), "+f"(d[40]), "+f"(d[41]), "+f"(d[42]), "+f"(d[43]), "+f"(d[44]), "+f"(d[45]), "+f"(d[46]), "+f"(d[47]), "+f"(d[48]), "+f"(d[49]), "+f"(d[50]), "+f"(d[51]), "+f"(d[52]), "+f"(d[53]), "+f"(d[54]), "+f"(d[55]), "+f"(d[56]), "+f"(d[57]), "+f"(d[58]), "+f"(d[59]), "+f"(d[60]), "+f"(d[61]), "+f"(d[62]), "+f"(d[63]), "+f"(d[64]), "+f"(d[65]), "+f"(d[66]), "+f"(d[67]), "+f"(d[68]), "+f"(d[69]), "+f"(d[70]), "+f"(d[71]), "+f"(d[72]), "+f"(d[73]), "+f"(d[74]), "+f"(d[75]), "+f"(d[76]), "+f"(d[77]), "+f"(d[78]), "+f"(d[79]), "+f"(d[80]), "+f"(d[81]), "+f"(d[82]), "+f"(d[83]), "+f"(d[84]), "+f"(d[85]), "+f"(d[86]), "+f"(d[87]), "+f"(d[88]), "+f"(d[89]), "+f"(d[90]), "+f"(d[91]), "+f"(d[92]), "+f"(d[93]), "+f"(d[94]), "+f"(d[95])
    : "l"(descA), "l"(descB), "r"(scaleD));
}
__device__ __forceinline__ void wgmma_ss_n64_tb(float (&d)[32], uint64_t descA, uint64_t descB, int scaleD) {
  asm volatile("{\n.reg .pred p;\nsetp.ne.b32 p, %34, 0;\n"
    "wgmma.mma_async.sync.aligned.m64n64k16.f32.bf16.bf16 {%0, %1, %2, %3, %4, %5, %6, %7, %8, %9, %10, %11, %12, %13, %14, %15, %16, %17, %18, %19, %20, %21, %22, %23, %24, %25, %26, %27, %28, %29, %30, %31}, %32, %33, p, 1, 1, 0, 1;\n}\n"
    : "+f"(d[0]), "+f"(d[1]), "+f"(d[2]), "+f"(d[3]), "+f"(d[4]), "+f"(d[5]), "+f"(d[6]), "+f"(d[7]), "+f"(d[8]), "+f"(d[9]), "+f"(d[10]), "+f"(d[11]), "+f"(d[12]), "+f"(d[13]), "+f"(d[14]), "+f"(d[15]), "+f"(d[16]), "+f"(d[17]), "+f"(d[18]), "+f"(d[19]), "+f"(d[20]), "+f"(d[21]), "+f"(d[22]), "+f"(d[23]), "+f"(d[24]), "+f"(d[25]), "+f"(d[26]), "+f"(d[27]), "+f"(d[28]), "+f"(d[29]), "+f"(d[30]), "+f"(d[31])
    : "l"(descA), "l"(descB), "r"(scaleD));
}
__device__ __forceinline__ void wgmma_ss_n16_tb(float (&d)[8], uint64_t descA, uint64_t descB, int scaleD) {
  asm volatile("{\n.reg .pred p;\nsetp.ne.b32 p, %10, 0;\n"
    "wgmma.mma_async.sync.aligned.m64n16k16.f32.bf16.bf16 {%0, %1, %2, %3, %4, %5, %6, %7}, %8, %9, p, 1, 1, 0, 1;\n}\n"
    : "+f"(d[0]), "+f"(d[1]), "+f"(d[2]), "+f"(d[3]), "+f"(d[4]), "+f"(d[5]), "+f"(d[6]), "+f"(d[7])
    : "l"(descA), "l"(descB), "r"(scaleD));
}
__device__ __forceinline__ void wgmma_rs_n128(float (&d)[64], uint32_t a0, uint32_t a1, uint32_t a2, uint32_t a3, uint64_t descB, int scaleD) {
  asm volatile("{\n.reg .pred p;\nsetp.ne.b32 p, %69, 0;\n"
    "wgmma.mma_async.sync.aligned.m64n128k16.f32.bf16.bf16 {%0, %1, %2, %3, %4, %5, %6, %7, %8, %9, %10, %11, %12, %13, %14, %15, %16, %17, %18, %19, %20, %21, %22, %23, %24, %25, %26, %27, %28, %29, %30, %31, %32, %33, %34, %35, %36, %37, %38, %39, %40, %41, %42, %43, %44, %45, %46, %47, %48, %49, %50, %51, %52, %53, %54, %55, %56, %57, %58, %59, %60, %61, %62, %63}, {%64, %65, %66, %67}, %68, p, 1, 1, 0;\n}\n"
    : "+f"(d[0]), "+f"(d[1]), "+f"(d[2]), "+f"(d[3]), "+f"(d[4]), "+f"(d[5]), "+f"(d[6]), "+f"(d[7]), "+f"(d[8]), "+f"(d[9]), "+f"(d[10]), "+f"(d[11]), "+f"(d[12]), "+f"(d[13]), "+f"(d[14]), "+f"(d[15]), "+f"(d[16]), "+f"(d[17]), "+f"(d[18]), "+f"(d[19]), "+f"(d[20]), "+f"(d[21]), "+f"(d[22]), "+f"(d[23]), "+f"(d[24]), "+f"(d[25]), "+f"(d[26]), "+f"(d[27]), "+f"(d[28]), "+f"(d[29]), "+f"(d[30]), "+f"(d[31]), "+f"(d[32]), "+f"(d[33]), "+f"(d[34]), "+f"(d[35]), "+f"(d[36]), "+f"(d[37]), "+f"(d[38]), "+f"(d[39]), "+f"(d[40]), "+f"(d[41]), "+f"(d[42]), "+f"(d[43]), "+f"(d[44]), "+f"(d[45]), "+f"(d[46]), "+f"(d[47]), "+f"(d[48]), "+f"(d[49]), "+f"(d[50]), "+f"(d[51]), "+f"(d[52]), "+f"(d[53]), "+f"(d[54]), "+f"(d[55]), "+f"(d[56]), "+f"(d[57]), "+f"(d[58]), "+f"(d[59]), "+f"(d[60]), "+f"(d[61]), "+f"(d[62]), "+f"(d[63])
    : "r"(a0), "r"(a1), "r"(a2), "r"(a3), "l"(descB), "r"(scaleD));
}
__device__ __forceinline__ void wgmma_rs_n64(float (&d)[32], uint32_t a0, uint32_t a1, uint32_t a2, uint32_t a3, uint64_t descB, int scaleD) {
  asm volatile("{\n.reg .pred p;\nsetp.ne.b32 p, %37, 0;\n"
    "wgmma.mma_async.sync.aligned.m64n64k16.f32.bf16.bf16 {%0, %1, %2, %3, %4, %5, %6, %7, %8, %9, %10, %11, %12, %13, %14, %15, %16, %17, %18, %19, %20, %21, %22, %23, %24, %25, %26, %27, %28, %29, %30, %31}, {%32, %33, %34, %35}, %36, p, 1, 1, 0;\n}\n"
    : "+f"(d[0]), "+f"(d[1]), "+f"(d[2]), "+f"(d[3]), "+f"(d[4]), "+f"(d[5]), "+f"(d[6]), "+f"(d[7]), "+f"(d[8]), "+f"(d[9]), "+f"(d[10]), "+f"(d[11]), "+f"(d[12]), "+f"(d[13]), "+f"(d[14]), "+f"(d[15]), "+f"(d[16]), "+f"(d[17]), "+f"(d[18]), "+f"(d[19]), "+f"(d[20]), "+f"(d[21]), "+f"(d[22]), "+f"(d[23]), "+f"(d[24]), "+f"(d[25]), "+f"(d[26]), "+f"(d[27]), "+f"(d[28]), "+f"(d[29]), "+f"(d[30]), "+f"(d[31])
    : "r"(a0), "r"(a1), "r"(a2), "r"(a3), "l"(descB), "r"(scaleD));
}
__device__ __forceinline__ void wgmma_rs_n24_tb(float (&d)[12], uint32_t a0, uint32_t a1, uint32_t a2, uint32_t a3, uint64_t descB, int scaleD) {
  asm volatile("{\n.reg .pred p;\nsetp.ne.b32 p, %17, 0;\n"
    "wgmma.mma_async.sync.aligned.m64n24k16.f32.bf16.bf16 {%0, %1, %2, %3, %4, %5, %6, %7, %8, %9, %10, %11}, {%12, %13, %14, %15}, %16, p, 1, 1, 1;\n}\n"
    : "+f"(d[0]), "+f"(d[1]), "+f"(d[2]), "+f"(d[3]), "+f"(d[4]), "+f"(d[5]), "+f"(d[6]), "+f"(d[7]), "+f"(d[8]), "+f"(d[9]), "+f"(d[10]), "+f"(d[11])
    : "r"(a0), "r"(a1), "r"(a2), "r"(a3), "l"(descB), "r"(scaleD));
}

constexpr int GT = 384;

__device__ __forceinline__ void release_stage(uint32_t bar, bool leader) {
  if (leader) {
    mbar_arrive_cluster(bar, 0);
    mbar_arrive_cluster(bar, 1);
  }
}

__device__ __forceinline__ float2 ln_row_stats(const bf16* __restrict__ xin, int l16) {
  const uint4* src = reinterpret_cast<const uint4*>(xin);
  uint4 v[5];
#pragma unroll
  for (int j = 0; j < 5; j++) v[j] = __ldg(src + j * 16 + l16);
  float s0 = 0.f, s1 = 0.f, s2 = 0.f, s3 = 0.f;
#pragma unroll
  for (int j = 0; j < 5; j++) {
    s0 += bf_lo(v[j].x) + bf_hi(v[j].x);
    s1 += bf_lo(v[j].y) + bf_hi(v[j].y);
    s2 += bf_lo(v[j].z) + bf_hi(v[j].z);
    s3 += bf_lo(v[j].w) + bf_hi(v[j].w);
  }
  float mean = (s0 + s1) + (s2 + s3);
#pragma unroll
  for (int o = 1; o < 16; o <<= 1) mean += __shfl_xor_sync(0xffffffffu, mean, o);
  mean *= (1.0f / DM);
  s0 = s1 = s2 = s3 = 0.f;
#pragma unroll
  for (int j = 0; j < 5; j++) {
    float d;
    d = bf_lo(v[j].x) - mean; s0 = fmaf(d, d, s0);
    d = bf_hi(v[j].x) - mean; s1 = fmaf(d, d, s1);
    d = bf_lo(v[j].y) - mean; s2 = fmaf(d, d, s2);
    d = bf_hi(v[j].y) - mean; s3 = fmaf(d, d, s3);
    d = bf_lo(v[j].z) - mean; s0 = fmaf(d, d, s0);
    d = bf_hi(v[j].z) - mean; s1 = fmaf(d, d, s1);
    d = bf_lo(v[j].w) - mean; s2 = fmaf(d, d, s2);
    d = bf_hi(v[j].w) - mean; s3 = fmaf(d, d, s3);
  }
  float sq = (s0 + s1) + (s2 + s3);
#pragma unroll
  for (int o = 1; o < 16; o <<= 1) sq += __shfl_xor_sync(0xffffffffu, sq, o);
  const float var_b = bf16_round(sq * (1.0f / DM));
  const float den = bf16_round(sqrtf(bf16_round(var_b + 1e-5f)));
  return make_float2(bf16_round(mean), __frcp_rn(den));
}

constexpr int LG_STAGES = 5;
constexpr int QKV_STAGE = 8192 + 4 * 4096;
constexpr int GLU_STAGE = 8192 + 6 * 4096;

template <int WG>
__device__ __forceinline__ void qkv_mainloop(float (&acc)[120], uint32_t sbase, uint32_t sBar, bool leader) {
  constexpr int STAGE_BYTES = QKV_STAGE, NST = LG_STAGES;
  const uint64_t da_base = make_desc(sbase + WG * 4096, 16, 512, 2);
  const uint64_t db_base = make_desc(sbase + 8192, 4096, 1024, 1);
#pragma unroll 1
  for (int r = 0; r < 20 / NST; r++) {
#pragma unroll
    for (int s = 0; s < NST; s++) {
      mbar_wait(sBar + 8 * s, r & 1);
      wgmma_fence();
#pragma unroll
      for (int ks = 0; ks < 2; ks++)
        wgmma_ss_n240_tb(acc, da_base + (uint64_t)((s * STAGE_BYTES + ks * 32) >> 4), db_base + (uint64_t)((s * STAGE_BYTES + ks * 2048) >> 4), 1);
      wgmma_commit();
      wgmma_wait<1>();
      release_stage(sBar + 8 * (NST + (s + NST - 1) % NST), leader && (s > 0 || r > 0));
    }
  }
}
template <int WG>
__device__ __forceinline__ void glu_mainloop(float (&accg)[96], float (&accu)[96], uint32_t sbase, uint32_t sBar, bool leader) {
  constexpr int STAGE_BYTES = GLU_STAGE, NST = LG_STAGES;
  const uint64_t da_base = make_desc(sbase + WG * 4096, 16, 512, 2);
  const uint64_t db_base = make_desc(sbase + 8192, 4096, 1024, 1);
#pragma unroll 1
  for (int r = 0; r < 20 / NST; r++) {
#pragma unroll
    for (int s = 0; s < NST; s++) {
      mbar_wait(sBar + 8 * s, r & 1);
      wgmma_fence();
#pragma unroll
      for (int ks = 0; ks < 2; ks++) {
        const uint64_t da = da_base + (uint64_t)((s * STAGE_BYTES + ks * 32) >> 4);
        wgmma_ss_n192_tb(accg, da, db_base + (uint64_t)((s * STAGE_BYTES + ks * 2048) >> 4), 1);
        wgmma_ss_n192_tb(accu, da, db_base + (uint64_t)((s * STAGE_BYTES + 3 * 4096 + ks * 2048) >> 4), 1);
      }
      wgmma_commit();
      wgmma_wait<1>();
      release_stage(sBar + 8 * (NST + (s + NST - 1) % NST), leader && (s > 0 || r > 0));
    }
  }
}
constexpr int RG_STAGE_BYTES = 16384 + 8192 + 2048;
template <int NKB, int NST, int WG>
__device__ __forceinline__ void res_mainloop(float (&acc0)[32], float (&acc1)[8], uint32_t sbase, uint32_t sBar, bool leader) {
  const uint64_t da_base = make_desc(sbase + WG * 8192, 16, 1024, 1);
  const uint64_t db0_base = make_desc(sbase + 16384, 8192, 1024, 1);
  const uint64_t db1_base = make_desc(sbase + 16384 + 8192, 2048, 256, 3);
#pragma unroll 1
  for (int r = 0; r < NKB / NST; r++) {
#pragma unroll
    for (int s = 0; s < NST; s++) {
      const uint64_t so = (uint64_t)(s * (RG_STAGE_BYTES >> 4));
      mbar_wait(sBar + 8 * s, r & 1);
      wgmma_fence();
#pragma unroll
      for (int ks = 0; ks < 4; ks++) {
        wgmma_ss_n64_tb(acc0, da_base + so + ks * 2, db0_base + so + ks * 128, 1);
        wgmma_ss_n16_tb(acc1, da_base + so + ks * 2, db1_base + so + ks * 32, 1);
      }
      wgmma_commit();
      wgmma_wait<1>();
      release_stage(sBar + 8 * (NST + (s + NST - 1) % NST), leader && (s > 0 || r > 0));
    }
  }
}

constexpr int KA_CS = LG_STAGES * QKV_STAGE + 128;
constexpr int KA_SMEM = KA_CS + 1024 + 3072 + 1024;

__global__ void __launch_bounds__(GT, 1)
qkv_kernel(const __grid_constant__ CUtensorMap tmA, const __grid_constant__ CUtensorMap tmB, const bf16* __restrict__ x,
           const bf16* __restrict__ wqkv) {
  constexpr int STAGE_BYTES = QKV_STAGE, NST = LG_STAGES, NKB = 20;
  extern __shared__ uint8_t smem_raw[];
  const uint32_t sbase = (smem_u32(smem_raw) + 1023u) & ~1023u;
  const uint32_t sBar = sbase + NST * STAGE_BYTES;
  const int tid = threadIdx.x, warp = tid >> 5, lane = tid & 31;
  const int rank = blockIdx.x & 1;
  const int pair = blockIdx.x >> 1;
  const int n_blk = pair & 7;
  const int m_blk = (pair >> 3) * 2 + rank;
  TS(0, 0);
  if (tid == 256) {
    prefetch_tmap(&tmA);
    prefetch_tmap(&tmB);
  }
  if (tid == 0) {
    for (int s = 0; s < NST; s++) {
      mbar_init(sBar + 8 * s, 1);
      mbar_init(sBar + 8 * (NST + s), 4);
    }
    fence_mbar_init();
    if (blockIdx.x < 32) g_flag[16 + blockIdx.x] = 0;
  }
  pdl_launch();
  cluster_sync_all();

  if (warp >= 8) {
    asm volatile("setmaxnreg.dec.sync.aligned.u32 56;");
    if (warp >= 9) {
      const int w3 = warp - 9;
      float* red = reinterpret_cast<float*>(smem_raw + (sbase - smem_u32(smem_raw)) + KA_CS + 1024);
      if (lane < 30) {
        float a[8];
#pragma unroll
        for (int i = 0; i < 8; i++) a[i] = 0.f;
        const uint4* w = reinterpret_cast<const uint4*>(wqkv + (size_t)(m_blk * 40) * (3 * DM) + n_blk * 240) + lane;
#pragma unroll
        for (int r = w3; r < 42; r += 3) {
          if (r >= 40) break;
          const uint4 v = __ldg(w + (size_t)r * (3 * DM / 8));
          a[0] += bf_lo(v.x); a[1] += bf_hi(v.x); a[2] += bf_lo(v.y); a[3] += bf_hi(v.y);
          a[4] += bf_lo(v.z); a[5] += bf_hi(v.z); a[6] += bf_lo(v.w); a[7] += bf_hi(v.w);
        }
#pragma unroll
        for (int i = 0; i < 8; i++) red[w3 * 240 + lane * 8 + i] = a[i];
      }
      named_bar_sync(4, 96);
      for (int c = tid - 288; c < 240; c += 96) g_csp[m_blk * (3 * DM) + n_blk * 240 + c] = (red[c] + red[240 + c]) + red[480 + c];
      named_bar_sync(4, 96);
      if (tid == 288) flag_signal(&g_flag[48 + n_blk]);
      if (warp == 10) {
        named_bar_sync(5, 288);
        if (lane == 0) flag_signal(&g_flag[m_blk]);
      }
      if (lane == 0) {
        flag_wait(&g_flag[m_blk], 8);
        flag_wait(&g_flag[48 + n_blk], 16);
      }
      __syncwarp();
      float* cs_s = reinterpret_cast<float*>(smem_raw + (sbase - smem_u32(smem_raw)) + KA_CS);
      for (int c = tid - 288; c < 240; c += 96) {
        float t = 0.f;
#pragma unroll
        for (int mm = 0; mm < 16; mm++) t += g_csp[mm * (3 * DM) + n_blk * 240 + c];
        cs_s[c] = t;
      }
      float2* rs_s = reinterpret_cast<float2*>(red);
      named_bar_sync(4, 96);
      for (int r = tid - 288; r < 128; r += 96) rs_s[r] = g_rs[m_blk * 128 + r];
      named_bar_sync(6, 352);
    }
    if (tid == 256) {
      auto issue_b = [&](int kb) {
        const int s = kb % NST;
        const uint32_t full = sBar + 8 * s;
        mbar_expect_tx(full, STAGE_BYTES);
        const uint32_t dst = sbase + s * STAGE_BYTES + 8192;
#pragma unroll
        for (int j = 0; j < 2; j++) {
          const int sl = rank * 2 + j;
          tma_load_2d_mc(dst + sl * 4096, &tmB, n_blk * 240 + sl * 64, kb * 32, full, (uint16_t)3);
        }
      };
      for (int kb = 0; kb < NKB; kb++) {
        const int s = kb % NST;
        if (kb >= NST) mbar_wait(sBar + 8 * (NST + s), ((kb / NST) & 1) ^ 1);
        issue_b(kb);
        tma_load_2d(sbase + s * STAGE_BYTES, &tmA, kb * 32, m_blk * 128, sBar + 8 * s);
      }
    }
  } else {
    asm volatile("setmaxnreg.inc.sync.aligned.u32 224;");
    const int wg = __shfl_sync(0xffffffffu, warp >> 2, 0);
    const int wwarp = warp & 3;
    {
      const int row = m_blk * 128 + n_blk * 16 + warp * 2 + (lane >> 4);
      const float2 rs = ln_row_stats(x + (size_t)row * DM, lane & 15);
      if ((lane & 15) == 0) g_rs[row] = rs;
      asm volatile("bar.arrive 5, 288;" ::: "memory");
    }
    TS(0, 1);
    mbar_wait(sBar, 0);
    TS(0, 3);
    float acc[120];
#pragma unroll
    for (int i = 0; i < 120; i++) acc[i] = 0.f;
    if (wg == 0) qkv_mainloop<0>(acc, sbase, sBar, (tid & 127) == 0);
    else qkv_mainloop<1>(acc, sbase, sBar, (tid & 127) == 0);
    wgmma_wait<0>();
    fence_regs(acc);
    TS(0, 4);
    const int g = lane >> 2, c4 = lane & 3;
    float* cs_s = reinterpret_cast<float*>(smem_raw + (sbase - smem_u32(smem_raw)) + KA_CS);
    named_bar_sync(6, 352);
    TS(0, 7);
    const float2* rs_s = reinterpret_cast<const float2*>(smem_raw + (sbase - smem_u32(smem_raw)) + KA_CS + 1024);
    const float2 rs0 = rs_s[wg * 64 + wwarp * 16 + g], rs1 = rs_s[wg * 64 + wwarp * 16 + g + 8];
    const uint32_t stg = sbase + wg * (12 * 3072) + (wwarp * 2) * 384 + g * 16;
    const int hbase = n_blk * 12;
    float2 ccv[10];
#pragma unroll
    for (int j = 0; j < 30; j++) {
      if (j % 10 == 0) {
#pragma unroll
        for (int jj = 0; jj < 10; jj++) ccv[jj] = *reinterpret_cast<const float2*>(cs_s + (j + jj) * 8 + c4 * 2);
      }
      const int cb = (j * 8) % 20;
      const int hb = (j * 8) / 20;
      int d = cb + c4 * 2;
      int hl = hb;
      if (cb == 16 && c4 >= 2) { d -= 20; hl += 1; }
      const uint32_t a0 = stg + hl * 3072 + (d >> 3) * 128 + (d & 7) * 2;
      const int hg = hbase + hl;
      const float sc = hg < 32 ? ATT_SCALE_LOG2E : 1.0f;
      const float2 cc = ccv[j % 10];
      const float i0 = rs0.y * sc, i1 = rs1.y * sc;
      st_shared_b32(a0, pack_bf16(fmaf(-rs0.x, cc.x, acc[4 * j]) * i0, fmaf(-rs0.x, cc.y, acc[4 * j + 1]) * i0));
      st_shared_b32(a0 + 384, pack_bf16(fmaf(-rs1.x, cc.x, acc[4 * j + 2]) * i1, fmaf(-rs1.x, cc.y, acc[4 * j + 3]) * i1));
      if (d == 18) {
        const uint32_t pad0 = hg < 32 ? 0u : (hg < 64 ? 0x3f803f80u : 0x00003f80u);
        const uint32_t pad1 = (hg >= 32 && hg < 64) ? 0x00003f80u : 0u;
        st_shared_v2(a0 + 4, pad0, pad1);
        st_shared_v2(a0 + 388, pad0, pad1);
      }
      if (j % 10 == 9) {
        fence_proxy_async();
        named_bar_sync(1 + wg, 128);
        if ((tid & 127) < 4) {
          const int hs = (j / 10) * 4 + (tid & 127);
          bf16* dst = g_img + (size_t)(hbase + hs) * IMG_HEAD_ELEMS + (size_t)(m_blk * 16 + wg * 8) * 192;
          bulk_s2g(dst, sbase + wg * (12 * 3072) + hs * 3072, 3072);
          bulk_commit();
        }
      }
    }
    TS(0, 8);
    if ((tid & 127) < 4) bulk_wait_read();
  }
  __syncwarp();
  TS(0, 5);
  cluster_sync_relaxed();
  TS(0, 6);
}

constexpr int KC_NST1 = 5, KC_NST3 = 6;
constexpr int KC_STAGING = 160 * 1024;
constexpr int KC_BAR = KC_STAGING + 48 * 1024;
constexpr int KC_CS = KC_BAR + 512;
constexpr int KC_SMEM = KC_CS + 1536 + 1024;

__global__ void __launch_bounds__(GT, 1)
mlp_kernel(const __grid_constant__ CUtensorMap tmO, const __grid_constant__ CUtensorMap tmWo64, const __grid_constant__ CUtensorMap tmWo16,
           const __grid_constant__ CUtensorMap tmH, const __grid_constant__ CUtensorMap tmWg, const __grid_constant__ CUtensorMap tmWu,
           const __grid_constant__ CUtensorMap tmHHs, const __grid_constant__ CUtensorMap tmHH, const __grid_constant__ CUtensorMap tmWd64,
           const __grid_constant__ CUtensorMap tmWd16, const __grid_constant__ CUtensorMap tmHs, const __grid_constant__ CUtensorMap tmOut,
           const bf16* __restrict__ x) {
  extern __shared__ uint8_t smem_raw[];
  const uint32_t sbase = (smem_u32(smem_raw) + 1023u) & ~1023u;
  const uint32_t bar1 = sbase + KC_BAR;
  const uint32_t bar2 = bar1 + 128;
  const uint32_t bar3 = bar2 + 128;
  const uint32_t barD = bar3 + 128;
  const int tid = threadIdx.x, warp = tid >> 5, lane = tid & 31;
  const int rank = blockIdx.x & 1;
  const int pair = blockIdx.x >> 1;
  const int j_blk = pair & 7;
  const int m_blk = (pair >> 3) * 2 + rank;
  const int n0 = j_blk * 80;
  TS(2, 0);
  if (tid == 256) {
    prefetch_tmap(&tmO); prefetch_tmap(&tmWo64); prefetch_tmap(&tmWo16); prefetch_tmap(&tmH); prefetch_tmap(&tmWg);
    prefetch_tmap(&tmWu); prefetch_tmap(&tmHHs); prefetch_tmap(&tmHH); prefetch_tmap(&tmWd64); prefetch_tmap(&tmWd16);
    prefetch_tmap(&tmHs); prefetch_tmap(&tmOut);
  }
  if (tid == 0) {
    for (int s = 0; s < 5; s++) {
      mbar_init(bar1 + 8 * s, 1); mbar_init(bar1 + 8 * (5 + s), 4);
      mbar_init(bar2 + 8 * s, 1); mbar_init(bar2 + 8 * (5 + s), 4);
    }
    for (int s = 0; s < 6; s++) { mbar_init(bar3 + 8 * s, 1); mbar_init(bar3 + 8 * (6 + s), 4); }
    mbar_init(barD, 4); mbar_init(barD + 8, 4);
    fence_mbar_init();
  }
  cluster_sync_all();

  if (warp >= 8) {
    asm volatile("setmaxnreg.dec.sync.aligned.u32 40;");
    if (tid == 256) {
      auto issue_b80 = [&](const CUtensorMap* t64, const CUtensorMap* t16, uint32_t bars, int nst, int kb) {
        const int s = kb % nst;
        const uint32_t full = bars + 8 * s;
        const uint32_t st = sbase + s * RG_STAGE_BYTES;
        mbar_expect_tx(full, RG_STAGE_BYTES);
        tma_load_2d_mc(st + 16384 + rank * 4096, t64, n0, kb * 64 + rank * 32, full, (uint16_t)3);
        tma_load_2d_mc(st + 16384 + 8192 + rank * 1024, t16, n0 + 64, kb * 64 + rank * 32, full, (uint16_t)3);
      };
      for (int kb = 0; kb < KC_NST1; kb++) issue_b80(&tmWo64, &tmWo16, bar1, KC_NST1, kb);
      pdl_wait();
      for (int kb = 0; kb < 10; kb++) {
        const int s = kb % KC_NST1;
        if (kb >= KC_NST1) {
          mbar_wait(bar1 + 8 * (KC_NST1 + s), ((kb / KC_NST1) & 1) ^ 1);
          issue_b80(&tmWo64, &tmWo16, bar1, KC_NST1, kb);
        }
        tma_load_2d(sbase + s * RG_STAGE_BYTES, &tmO, kb * 64, m_blk * 128, bar1 + 8 * s);
      }
      auto issue_bglu = [&](int kb) {
        const int s = kb % LG_STAGES;
        const uint32_t full = bar2 + 8 * s;
        mbar_expect_tx(full, GLU_STAGE);
        const uint32_t dst = sbase + s * GLU_STAGE + 8192;
#pragma unroll
        for (int j = 0; j < 3; j++)
          tma_load_2d_mc(dst + (rank * 3 + j) * 4096, rank == 0 ? &tmWg : &tmWu, j_blk * 192 + j * 64, kb * 32, full, (uint16_t)3);
      };
      mbar_wait(barD, 0);
      for (int kb = 0; kb < LG_STAGES; kb++) issue_bglu(kb);
      flag_wait(&g_flag[16 + m_blk], 16);
      fence_proxy_async_all();
      for (int kb = 0; kb < 20; kb++) {
        const int s = kb % LG_STAGES;
        if (kb >= LG_STAGES) {
          mbar_wait(bar2 + 8 * (LG_STAGES + s), ((kb / LG_STAGES) & 1) ^ 1);
          issue_bglu(kb);
        }
        tma_load_2d(sbase + s * GLU_STAGE, &tmH, kb * 32, m_blk * 128, bar2 + 8 * s);
      }
      mbar_wait(barD + 8, 0);
      for (int kb = 0; kb < KC_NST3; kb++) issue_b80(&tmWd64, &tmWd16, bar3, KC_NST3, kb);
      flag_wait(&g_flag[32 + m_blk], 16);
      fence_proxy_async_all();
      for (int kb = 0; kb < 24; kb++) {
        const int s = kb % KC_NST3;
        if (kb >= KC_NST3) {
          mbar_wait(bar3 + 8 * (KC_NST3 + s), ((kb / KC_NST3) & 1) ^ 1);
          issue_b80(&tmWd64, &tmWd16, bar3, KC_NST3, kb);
        }
        tma_load_2d(sbase + s * RG_STAGE_BYTES, &tmHH, kb * 64, m_blk * 128, bar3 + 8 * s);
      }
    }
  } else {
    asm volatile("setmaxnreg.inc.sync.aligned.u32 232;");
    const int wg = __shfl_sync(0xffffffffu, warp >> 2, 0);
    const int wwarp = warp & 3;
    const int g = lane >> 2, c4 = lane & 3;
    const int row0 = m_blk * 128 + wg * 64 + wwarp * 16 + g;
    const bool leader = (tid & 127) == 0;
    const uint32_t stg80_base = sbase + KC_STAGING + wg * 24576;
    const uint32_t stg80 = stg80_base + (wwarp * 16 + g) * 160 + c4 * 4;
    {
      uint32_t res[20];
#pragma unroll
      for (int j = 0; j < 10; j++) {
        res[2 * j] = __ldg(reinterpret_cast<const uint32_t*>(x + (size_t)row0 * DM + n0 + j * 8 + c4 * 2));
        res[2 * j + 1] = __ldg(reinterpret_cast<const uint32_t*>(x + (size_t)(row0 + 8) * DM + n0 + j * 8 + c4 * 2));
      }
      float acc0[32], acc1[8];
#pragma unroll
      for (int i = 0; i < 32; i++) acc0[i] = 0.f;
#pragma unroll
      for (int i = 0; i < 8; i++) acc1[i] = 0.f;
      TS(2, 1);
      if (wg == 0) res_mainloop<10, KC_NST1, 0>(acc0, acc1, sbase, bar1, leader);
      else res_mainloop<10, KC_NST1, 1>(acc0, acc1, sbase, bar1, leader);
      wgmma_wait<0>();
      fence_regs(acc0); fence_regs(acc1);
      release_stage(barD, leader);
      TS(2, 4);
      float sum0 = 0.f, sum1 = 0.f;
#pragma unroll
      for (int j = 0; j < 10; j++) {
        const uint32_t a01 = j < 8 ? pack_bf16(acc0[4 * j], acc0[4 * j + 1]) : pack_bf16(acc1[4 * (j - 8)], acc1[4 * (j - 8) + 1]);
        const uint32_t a23 = j < 8 ? pack_bf16(acc0[4 * j + 2], acc0[4 * j + 3]) : pack_bf16(acc1[4 * (j - 8) + 2], acc1[4 * (j - 8) + 3]);
        res[2 * j] = pack_bf16(bf_lo(res[2 * j]) + bf_lo(a01), bf_hi(res[2 * j]) + bf_hi(a01));
        res[2 * j + 1] = pack_bf16(bf_lo(res[2 * j + 1]) + bf_lo(a23), bf_hi(res[2 * j + 1]) + bf_hi(a23));
        st_shared_b32(stg80 + j * 16, res[2 * j]);
        st_shared_b32(stg80 + 8 * 160 + j * 16, res[2 * j + 1]);
        sum0 += bf_lo(res[2 * j]) + bf_hi(res[2 * j]);
        sum1 += bf_lo(res[2 * j + 1]) + bf_hi(res[2 * j + 1]);
      }
      sum0 += __shfl_xor_sync(0xffffffffu, sum0, 1); sum1 += __shfl_xor_sync(0xffffffffu, sum1, 1);
      sum0 += __shfl_xor_sync(0xffffffffu, sum0, 2); sum1 += __shfl_xor_sync(0xffffffffu, sum1, 2);
      const float mu0 = sum0 * (1.0f / 80.0f), mu1 = sum1 * (1.0f / 80.0f);
      float q0 = 0.f, q1 = 0.f;
#pragma unroll
      for (int j = 0; j < 10; j++) {
        float d;
        d = bf_lo(res[2 * j]) - mu0; q0 = fmaf(d, d, q0);
        d = bf_hi(res[2 * j]) - mu0; q0 = fmaf(d, d, q0);
        d = bf_lo(res[2 * j + 1]) - mu1; q1 = fmaf(d, d, q1);
        d = bf_hi(res[2 * j + 1]) - mu1; q1 = fmaf(d, d, q1);
      }
      q0 += __shfl_xor_sync(0xffffffffu, q0, 1); q1 += __shfl_xor_sync(0xffffffffu, q1, 1);
      q0 += __shfl_xor_sync(0xffffffffu, q0, 2); q1 += __shfl_xor_sync(0xffffffffu, q1, 2);
      if (c4 == 0) {
        g_stats[row0 * 8 + j_blk] = make_float2(mu0, q0);
        g_stats[(row0 + 8) * 8 + j_blk] = make_float2(mu1, q1);
      }
      fence_proxy_async();
      named_bar_sync(1 + wg, 128);
      if (leader) {
        tma_store_2d(&tmHs, stg80_base, n0, m_blk * 128 + wg * 64);
        bulk_commit();
        bulk_wait_all();
        fence_proxy_async_all();
        flag_signal(&g_flag[16 + m_blk]);
      }
      TS(2, 5);
    }
    {
      pdl_wait();
      {
        float* cs_s = reinterpret_cast<float*>(smem_raw + (sbase - smem_u32(smem_raw)) + KC_CS);
        for (int i = tid; i < 384; i += 256) cs_s[i] = g_cs[(i >= 192 ? FF - 192 : 0) + j_blk * 192 + i];
        named_bar_sync(3, 256);
      }
      flag_wait(&g_flag[16 + m_blk], 16);
      float mb[2], iv[2];
#pragma unroll
      for (int h = 0; h < 2; h++) {
        const float4* sp = reinterpret_cast<const float4*>(g_stats + (row0 + 8 * h) * 8);
        const float4 p0 = sp[0], p1 = sp[1], p2 = sp[2], p3 = sp[3];
        const float mean = (((p0.x + p0.z) + (p1.x + p1.z)) + ((p2.x + p2.z) + (p3.x + p3.z))) * 0.125f;
        float m2 = ((p0.y + p0.w) + (p1.y + p1.w)) + ((p2.y + p2.w) + (p3.y + p3.w));
        float dd = 0.f, d;
        d = p0.x - mean; dd = fmaf(d, d, dd); d = p0.z - mean; dd = fmaf(d, d, dd);
        d = p1.x - mean; dd = fmaf(d, d, dd); d = p1.z - mean; dd = fmaf(d, d, dd);
        d = p2.x - mean; dd = fmaf(d, d, dd); d = p2.z - mean; dd = fmaf(d, d, dd);
        d = p3.x - mean; dd = fmaf(d, d, dd); d = p3.z - mean; dd = fmaf(d, d, dd);
        m2 = fmaf(dd, 80.0f, m2);
        const float var_b = bf16_round(m2 * (1.0f / DM));
        const float den = bf16_round(sqrtf(bf16_round(var_b + 1e-5f)));
        iv[h] = __frcp_rn(den);
        mb[h] = bf16_round(mean);
      }
      float accg[96], accu[96];
#pragma unroll
      for (int i = 0; i < 96; i++) { accg[i] = 0.f; accu[i] = 0.f; }
      TS(3, 3);
      if (wg == 0) glu_mainloop<0>(accg, accu, sbase, bar2, leader);
      else glu_mainloop<1>(accg, accu, sbase, bar2, leader);
      wgmma_wait<0>();
      fence_regs(accg); fence_regs(accu);
      release_stage(barD + 8, leader);
      TS(3, 4);
      const uint32_t stg = sbase + KC_STAGING + wg * 24576 + (wwarp * 16 + g) * 128 + c4 * 4;
      const float* csg = reinterpret_cast<const float*>(smem_raw + (sbase - smem_u32(smem_raw)) + KC_CS) + c4 * 2;
      const float nm0 = -mb[0] * iv[0], nm1 = -mb[1] * iv[1];
#pragma unroll
      for (int sl = 0; sl < 3; sl++) {
        float2 cgv[4], cuv[4];
#pragma unroll
        for (int jj = 0; jj < 8; jj++) {
          const int j = sl * 8 + jj;
          if ((jj & 3) == 0) {
#pragma unroll
            for (int q = 0; q < 4; q++) {
              cgv[q] = *reinterpret_cast<const float2*>(csg + (j + q) * 8);
              cuv[q] = *reinterpret_cast<const float2*>(csg + 192 + (j + q) * 8);
            }
          }
          const float2 cg = cgv[jj & 3], cu = cuv[jj & 3];
          const float r0 = fmaxf(fmaf(accg[4 * j], iv[0], nm0 * cg.x), 0.f) * fmaf(accu[4 * j], iv[0], nm0 * cu.x);
          const float r1 = fmaxf(fmaf(accg[4 * j + 1], iv[0], nm0 * cg.y), 0.f) * fmaf(accu[4 * j + 1], iv[0], nm0 * cu.y);
          const float r2 = fmaxf(fmaf(accg[4 * j + 2], iv[1], nm1 * cg.x), 0.f) * fmaf(accu[4 * j + 2], iv[1], nm1 * cu.x);
          const float r3 = fmaxf(fmaf(accg[4 * j + 3], iv[1], nm1 * cg.y), 0.f) * fmaf(accu[4 * j + 3], iv[1], nm1 * cu.y);
          const uint32_t a0 = stg + sl * 8192 + ((jj ^ g) << 4);
          st_shared_b32(a0, pack_bf16(r0, r1));
          st_shared_b32(a0 + 1024, pack_bf16(r2, r3));
        }
        fence_proxy_async();
        named_bar_sync(1 + wg, 128);
        if (leader) {
          tma_store_2d(&tmHHs, sbase + KC_STAGING + wg * 24576 + sl * 8192, j_blk * 192 + sl * 64, m_blk * 128 + wg * 64);
          bulk_commit();
        }
      }
      TS(3, 7);
      if (leader) {
        bulk_wait_all();
        TS(3, 8);
        fence_proxy_async_all();
        flag_signal(&g_flag[32 + m_blk]);
      }
      TS(3, 9);
    }
    {
      uint32_t res[20];
#pragma unroll
      for (int j = 0; j < 10; j++) {
        res[2 * j] = *reinterpret_cast<const uint32_t*>(g_h + (size_t)row0 * DM + n0 + j * 8 + c4 * 2);
        res[2 * j + 1] = *reinterpret_cast<const uint32_t*>(g_h + (size_t)(row0 + 8) * DM + n0 + j * 8 + c4 * 2);
      }
      float acc0[32], acc1[8];
#pragma unroll
      for (int i = 0; i < 32; i++) acc0[i] = 0.f;
#pragma unroll
      for (int i = 0; i < 8; i++) acc1[i] = 0.f;
      mbar_wait(bar3, 0);
      TS(4, 3);
      if (wg == 0) res_mainloop<24, KC_NST3, 0>(acc0, acc1, sbase, bar3, leader);
      else res_mainloop<24, KC_NST3, 1>(acc0, acc1, sbase, bar3, leader);
      wgmma_wait<0>();
      fence_regs(acc0); fence_regs(acc1);
      TS(4, 4);
#pragma unroll
      for (int j = 0; j < 10; j++) {
        const uint32_t a01 = j < 8 ? pack_bf16(acc0[4 * j], acc0[4 * j + 1]) : pack_bf16(acc1[4 * (j - 8)], acc1[4 * (j - 8) + 1]);
        const uint32_t a23 = j < 8 ? pack_bf16(acc0[4 * j + 2], acc0[4 * j + 3]) : pack_bf16(acc1[4 * (j - 8) + 2], acc1[4 * (j - 8) + 3]);
        st_shared_b32(stg80 + j * 16, pack_bf16(bf_lo(res[2 * j]) + bf_lo(a01), bf_hi(res[2 * j]) + bf_hi(a01)));
        st_shared_b32(stg80 + 8 * 160 + j * 16, pack_bf16(bf_lo(res[2 * j + 1]) + bf_lo(a23), bf_hi(res[2 * j + 1]) + bf_hi(a23)));
      }
      fence_proxy_async();
      named_bar_sync(1 + wg, 128);
      if (leader) {
        tma_store_2d(&tmOut, stg80_base, n0, m_blk * 128 + wg * 64);
        bulk_commit();
        bulk_wait_read();
      }
      TS(4, 5);
    }
  }
  __syncwarp();
  cluster_sync_relaxed();
  TS(4, 6);
}

constexpr int AT_THREADS = 512;
constexpr int AT_WGS = AT_THREADS / 128;
#define AT_CHUNK_MASK 3
#define AT_STAGGER 0
constexpr int AT_KV_BYTES = IMG_HEAD_ELEMS * 2;
constexpr int AT_SMEM = 2 * AT_KV_BYTES + 256 + 1024;
constexpr int AT_CHUNKS = 8;

__device__ __forceinline__ float exp2_poly(float x) {
  const float u = __saturatef(fmaf(x, 1.0f / 64.0f, 62.0f / 64.0f));
  const float MAGIC = 12582912.0f - 62.0f;
  const float r = fmaf(u, 64.0f, MAGIC);
  const float q = MAGIC - r;
  const float fr = fmaf(u, 64.0f, q);
  float p = fmaf(fr, 0.009570102207362652f, 0.05591785907745361f);
  p = fmaf(p, fr, 0.240247443318367f);
  p = fmaf(p, fr, 0.6931217908859253f);
  p = fmaf(p, fr, 0.9999992847442627f);
  return __uint_as_float(__float_as_uint(p) + (__float_as_uint(r) << 23));
}
#define AT_VARIANT 0
#define AT_POLY_MOD 8
__device__ __forceinline__ bool use_poly(int e) {
  return (e % AT_POLY_MOD) == 1;
}

struct AttnState {
  uint32_t qa0, qa1, qa2, qa3, qa4, qa5;
  float M0, M1;
};

__device__ __forceinline__ bool attn_exp_fast(const float (&s)[32], uint32_t (&p)[16]) {
#pragma unroll
  for (int j = 0; j < 16; j++) {
    const float e0 = use_poly(2 * j) ? exp2_poly(s[2 * j]) : ex2(s[2 * j]);
    const float e1 = use_poly(2 * j + 1) ? exp2_poly(s[2 * j + 1]) : ex2(s[2 * j + 1]);
    p[j] = pack_bf16(e0, e1);
  }
  uint32_t acc_or = 0;
#pragma unroll
  for (int j = 0; j < 16; j++) acc_or |= p[j];
  return __any_sync(0xffffffffu, (acc_or & 0x40004000u) != 0);
}
__device__ __forceinline__ void attn_exp_exact(const float (&s)[32], uint32_t (&p)[16], float (&o)[12], AttnState& st, bool first, int c4) {
  float mx0 = fmaxf(s[0], s[1]), mx1 = fmaxf(s[2], s[3]);
#pragma unroll
  for (int j = 1; j < 8; j++) {
    mx0 = fmaxf(mx0, fmaxf(s[4 * j], s[4 * j + 1]));
    mx1 = fmaxf(mx1, fmaxf(s[4 * j + 2], s[4 * j + 3]));
  }
  mx0 = fmaxf(mx0, __shfl_xor_sync(0xffffffffu, mx0, 1));
  mx1 = fmaxf(mx1, __shfl_xor_sync(0xffffffffu, mx1, 1));
  mx0 = fmaxf(mx0, __shfl_xor_sync(0xffffffffu, mx0, 2));
  mx1 = fmaxf(mx1, __shfl_xor_sync(0xffffffffu, mx1, 2));
  float d0 = mx0 + 7.0f, d1 = mx1 + 7.0f;
  if (!first) { d0 = fmaxf(d0, 0.f); d1 = fmaxf(d1, 0.f); }
  const float T0 = st.M0 + d0, T1 = st.M1 + d1;
  const float h0 = bf16_round(T0), h1 = bf16_round(T1);
  const float i0 = bf16_round(T0 - h0), i1 = bf16_round(T1 - h1);
  const float l0 = bf16_round((T0 - h0) - i0), l1 = bf16_round((T1 - h1) - i1);
  const float N0 = (h0 + i0) + l0, N1 = (h1 + i1) + l1;
  d0 = N0 - st.M0; d1 = N1 - st.M1;
  st.M0 = N0; st.M1 = N1;
  if (c4 == 2) { st.qa4 = pack_bf16(-h0, -i0); st.qa5 = pack_bf16(-h1, -i1); }
  if (c4 == 3) { st.qa4 = pack_bf16(-l0, 0.f); st.qa5 = pack_bf16(-l1, 0.f); }
  if (!first) {
    const float al0 = ex2(-d0), al1 = ex2(-d1);
#pragma unroll
    for (int j = 0; j < 3; j++) {
      o[4 * j] *= al0; o[4 * j + 1] *= al0;
      o[4 * j + 2] *= al1; o[4 * j + 3] *= al1;
    }
  }
#pragma unroll
  for (int j = 0; j < 8; j++) {
    p[2 * j] = pack_bf16(ex2(s[4 * j] - d0), ex2(s[4 * j + 1] - d0));
    p[2 * j + 1] = pack_bf16(ex2(s[4 * j + 2] - d1), ex2(s[4 * j + 3] - d1));
  }
}
__device__ __forceinline__ void attn_step(float (&s)[32], const uint32_t (&pp)[16], uint32_t (&pn)[16], float (&o)[12], AttnState& st,
                                          uint32_t k_addr, uint32_t v_addr_prev, int keep, int c4, int wgdbg = 0, int tdbg = 0) {
  PH(wgdbg, tdbg, 0);
  const uint64_t dk = make_desc(k_addr, 128, 384, 0);
  const uint64_t dv_prev = make_desc(v_addr_prev, 384, 128, 0);
  wgmma_fence();
  wgmma_rs_n64(s, st.qa0, st.qa1, st.qa2, st.qa3, dk, 0);
  wgmma_rs_n64(s, st.qa4, st.qa5, 0u, 0u, dk + 16, 1);
  wgmma_commit();
#pragma unroll
  for (int kk = 0; kk < 4; kk++) wgmma_rs_n24_tb(o, pp[4 * kk], pp[4 * kk + 1], pp[4 * kk + 2], pp[4 * kk + 3], dv_prev + kk * 48, kk == 0 ? keep : 1);
  wgmma_commit();
  wgmma_wait<1>();
  fence_regs(s);
  PH(wgdbg, tdbg, 1);
  const bool redo = attn_exp_fast(s, pn);
  PH(wgdbg, tdbg, 2);
  wgmma_wait<0>();
  fence_regs(o);
  if (redo) attn_exp_exact(s, pn, o, st, false, c4);
}

__global__ void __launch_bounds__(AT_THREADS, 1) attn_kernel(const bf16* __restrict__ wo, const bf16* __restrict__ wgt, const bf16* __restrict__ wup, const bf16* __restrict__ wdn) {
  extern __shared__ uint8_t smem_raw[];
  const uint32_t sbase = (smem_u32(smem_raw) + 1023u) & ~1023u;
  const uint32_t sK = sbase, sV = sbase + AT_KV_BYTES;
  const uint32_t sBar = sV + AT_KV_BYTES;
  const int tid = threadIdx.x, warp = tid >> 5, lane = tid & 31;
  const int head = blockIdx.x >> 2, quarter = blockIdx.x & 3;
  if (blockIdx.x >= 128) {
    pdl_launch();
    const int b = blockIdx.x - 128;
    const bf16* w = (b >> 1) ? wup : wgt;
    const int cgrp = tid % 96, rgrp = tid / 96;
    float acc[8];
#pragma unroll
    for (int i = 0; i < 8; i++) acc[i] = 0.f;
    float* red = reinterpret_cast<float*>(smem_raw);
    if (rgrp < 5) {
      const uint4* src = reinterpret_cast<const uint4*>(w + (size_t)(rgrp * 128) * FF + (b & 1) * 768 + cgrp * 8);
#pragma unroll 8
      for (int r = 0; r < 128; r++) {
        const uint4 v = __ldg(src + (size_t)r * (FF / 8));
        acc[0] += bf_lo(v.x); acc[1] += bf_hi(v.x); acc[2] += bf_lo(v.y); acc[3] += bf_hi(v.y);
        acc[4] += bf_lo(v.z); acc[5] += bf_hi(v.z); acc[6] += bf_lo(v.w); acc[7] += bf_hi(v.w);
      }
#pragma unroll
      for (int i = 0; i < 8; i++) red[rgrp * 768 + cgrp * 8 + i] = acc[i];
    }
    __syncthreads();
    pdl_wait();
    for (int c = tid; c < 768; c += AT_THREADS)
      g_cs[(b >> 1) * FF + (b & 1) * 768 + c] = ((red[c] + red[768 + c]) + (red[1536 + c] + red[2304 + c])) + red[3072 + c];
    if (b == 0 && tid < 16) g_flag[tid] = 0;
    if (b == 0 && tid < 8) g_flag[48 + tid] = 0;
    return;
  }
  TS(1, 0);
  if (tid == 0) {
    for (int i = 0; i < AT_CHUNKS; i++) mbar_init(sBar + 8 * i, 1);
    fence_mbar_init();
  }
  pdl_launch();
  if (tid == 32) {
    prefetch_l2(reinterpret_cast<const uint8_t*>(wo) + blockIdx.x * 6400, 6400);
    prefetch_l2(reinterpret_cast<const uint8_t*>(wgt) + blockIdx.x * 15360, 15360);
    prefetch_l2(reinterpret_cast<const uint8_t*>(wup) + blockIdx.x * 15360, 15360);
    prefetch_l2(reinterpret_cast<const uint8_t*>(wdn) + blockIdx.x * 15360, 15360);
  }
  __syncthreads();
  TS(1, 1);
  pdl_wait();
  TS(1, 2);
  if (tid == 0) {
    const uint8_t* kg = reinterpret_cast<const uint8_t*>(g_img + (size_t)(32 + head) * IMG_HEAD_ELEMS);
    const uint8_t* vg = reinterpret_cast<const uint8_t*>(g_img + (size_t)(64 + head) * IMG_HEAD_ELEMS);
    constexpr int CB = AT_KV_BYTES / AT_CHUNKS;
    for (int i = 0; i < AT_CHUNKS; i++) {
      mbar_expect_tx(sBar + 8 * i, 2 * CB);
      bulk_g2s(sK + i * CB, kg + i * CB, CB, sBar + 8 * i);
      bulk_g2s(sV + i * CB, vg + i * CB, CB, sBar + 8 * i);
    }
  }
  const int wg = warp >> 2, wwarp = warp & 3;
  const int g = lane >> 2, c4 = lane & 3;
  const uint64_t dk_base = make_desc(sK, 128, 384, 0);
  const uint64_t dv_base = make_desc(sV, 384, 128, 0);

#pragma unroll 1
  for (int rep = 0; rep < 8 / AT_WGS; rep++) {
    const int row0 = quarter * 512 + (rep * AT_WGS + wg) * 64 + wwarp * 16 + g;
    AttnState st;
    {
      const bf16* q0 = g_img + (size_t)head * IMG_HEAD_ELEMS + (size_t)(row0 >> 3) * 192 + g * 8 + c4 * 2;
      const bf16* q1 = q0 + 192;
      st.qa0 = *reinterpret_cast<const uint32_t*>(q0);
      st.qa1 = *reinterpret_cast<const uint32_t*>(q1);
      st.qa2 = *reinterpret_cast<const uint32_t*>(q0 + 64);
      st.qa3 = *reinterpret_cast<const uint32_t*>(q1 + 64);
      st.qa4 = *reinterpret_cast<const uint32_t*>(q0 + 128);
      st.qa5 = *reinterpret_cast<const uint32_t*>(q1 + 128);
    }
    float o[12];
    float s[32];
    uint32_t pa[16], pb[16];
    st.M0 = st.M1 = 0.f;
    if (rep == 0) mbar_wait(sBar, 0);
    wgmma_fence();
    wgmma_rs_n64(s, st.qa0, st.qa1, st.qa2, st.qa3, dk_base, 0);
    wgmma_rs_n64(s, st.qa4, st.qa5, 0u, 0u, dk_base + 16, 1);
    wgmma_commit();
    wgmma_wait<0>();
    fence_regs(s);
    attn_exp_exact(s, pa, o, st, true, c4);
    attn_step(s, pa, pb, o, st, sK + 3072, sV, 0, c4);
#pragma unroll 1
    for (int tt = 1; tt < 16; tt++) {
      if (rep == 0 && !(tt & 1)) mbar_wait(sBar + 8 * (tt >> 1), 0);
      attn_step(s, pb, pa, o, st, sK + tt * 6144, sV + tt * 6144 - 3072, 1, c4, wg, rep * 32 + tt * 2);
      attn_step(s, pa, pb, o, st, sK + tt * 6144 + 3072, sV + tt * 6144, 1, c4, wg, rep * 32 + tt * 2 + 1);
    }
    wgmma_fence();
#pragma unroll
    for (int kk = 0; kk < 4; kk++) wgmma_rs_n24_tb(o, pb[4 * kk], pb[4 * kk + 1], pb[4 * kk + 2], pb[4 * kk + 3], dv_base + 31 * 192 + kk * 48, 1);
    wgmma_commit();
    wgmma_wait<0>();
    fence_regs(o);
    TS(1, 3 + rep);
    const float l0 = __shfl_sync(0xffffffffu, o[8], (lane & ~3) | 2);
    const float l1 = __shfl_sync(0xffffffffu, o[10], (lane & ~3) | 2);
    const float i0 = 1.0f / l0, i1 = 1.0f / l1;
    bf16* o0 = g_o + (size_t)row0 * DM + head * DH;
    bf16* o1 = o0 + 8 * DM;
#pragma unroll
    for (int j = 0; j < 3; j++) {
      if (j < 2 || c4 < 2) {
        *reinterpret_cast<uint32_t*>(o0 + j * 8 + c4 * 2) = pack_bf16(o[4 * j] * i0, o[4 * j + 1] * i0);
        *reinterpret_cast<uint32_t*>(o1 + j * 8 + c4 * 2) = pack_bf16(o[4 * j + 2] * i1, o[4 * j + 3] * i1);
      }
    }
  }
}

typedef CUresult (*EncodeTiledFn)(CUtensorMap*, CUtensorMapDataType, cuuint32_t, void*, const cuuint64_t*, const cuuint64_t*,
                                  const cuuint32_t*, const cuuint32_t*, CUtensorMapInterleave, CUtensorMapSwizzle,
                                  CUtensorMapL2promotion, CUtensorMapFloatOOBfill);

static void make_map(EncodeTiledFn fn, CUtensorMap* tm, const void* ptr, uint64_t rows, uint64_t cols, uint32_t box_rows,
                     uint32_t box_cols, CUtensorMapSwizzle sw) {
  cuuint64_t dims[2] = {cols, rows};
  cuuint64_t strides[1] = {cols * 2};
  cuuint32_t box[2] = {box_cols, box_rows};
  cuuint32_t es[2] = {1, 1};
  fn(tm, CU_TENSOR_MAP_DATA_TYPE_BFLOAT16, 2, const_cast<void*>(ptr), dims, strides, box, es, CU_TENSOR_MAP_INTERLEAVE_NONE, sw,
     CU_TENSOR_MAP_L2_PROMOTION_L2_256B, CU_TENSOR_MAP_FLOAT_OOB_FILL_NONE);
}

template <typename... KArgs, typename... Args>
static void launch(void (*kern)(KArgs...), int grid, int block, int smem, int cluster, bool pdl, Args... args) {
  cudaLaunchConfig_t cfg = {};
  cfg.gridDim = dim3(grid);
  cfg.blockDim = dim3(block);
  cfg.dynamicSmemBytes = smem;
  cfg.stream = cudaStreamPerThread;
  cudaLaunchAttribute at[2];
  int n = 0;
  if (cluster > 1) {
    at[n].id = cudaLaunchAttributeClusterDimension;
    at[n].val.clusterDim.x = cluster; at[n].val.clusterDim.y = 1; at[n].val.clusterDim.z = 1;
    n++;
  }
  if (pdl) {
    at[n].id = cudaLaunchAttributeProgrammaticStreamSerialization;
    at[n].val.programmaticStreamSerializationAllowed = 1;
    n++;
  }
  cfg.attrs = at;
  cfg.numAttrs = n;
  cudaLaunchKernelEx(&cfg, kern, KArgs(args)...);
}

extern "C" void kernel_launch(void* const* d_in, const int* in_sizes, int n_in, void* d_out, int out_size) {
  const bf16* x = (const bf16*)d_in[0];
  const bf16* wqkv = (const bf16*)d_in[1];
  const bf16* wo = (const bf16*)d_in[2];
  const bf16* wg = (const bf16*)d_in[4];
  const bf16* wu = (const bf16*)d_in[5];
  const bf16* wd = (const bf16*)d_in[6];
  bf16* out = (bf16*)d_out;

  static EncodeTiledFn enc = nullptr;
  static void *p_o = nullptr, *p_h = nullptr, *p_hh = nullptr;
  if (!enc) {
    void* fn = nullptr;
    cudaDriverEntryPointQueryResult qr;
    cudaGetDriverEntryPoint("cuTensorMapEncodeTiled", &fn, cudaEnableDefault, &qr);
    enc = (EncodeTiledFn)fn;
    cudaGetSymbolAddress(&p_o, g_o);
    cudaGetSymbolAddress(&p_h, g_h);
    cudaGetSymbolAddress(&p_hh, g_hh);
    cudaFuncSetAttribute(qkv_kernel, cudaFuncAttributeMaxDynamicSharedMemorySize, KA_SMEM);
    cudaFuncSetAttribute(mlp_kernel, cudaFuncAttributeMaxDynamicSharedMemorySize, KC_SMEM);
    cudaFuncSetAttribute(attn_kernel, cudaFuncAttributeMaxDynamicSharedMemorySize, AT_SMEM);
  }
  CUtensorMap tm_wqkv, tm_wg, tm_wu, tm_wo64, tm_wo16, tm_wd64, tm_wd16, tm_o, tm_h, tm_hh, tm_hhs, tm_xn, tm_hs, tm_out;
  make_map(enc, &tm_wqkv, wqkv, DM, 3 * DM, 32, 64, CU_TENSOR_MAP_SWIZZLE_128B);
  make_map(enc, &tm_wg, wg, DM, FF, 32, 64, CU_TENSOR_MAP_SWIZZLE_128B);
  make_map(enc, &tm_wu, wu, DM, FF, 32, 64, CU_TENSOR_MAP_SWIZZLE_128B);
  make_map(enc, &tm_wo64, wo, DM, DM, 32, 64, CU_TENSOR_MAP_SWIZZLE_128B);
  make_map(enc, &tm_wo16, wo, DM, DM, 32, 16, CU_TENSOR_MAP_SWIZZLE_32B);
  make_map(enc, &tm_wd64, wd, FF, DM, 32, 64, CU_TENSOR_MAP_SWIZZLE_128B);
  make_map(enc, &tm_wd16, wd, FF, DM, 32, 16, CU_TENSOR_MAP_SWIZZLE_32B);
  make_map(enc, &tm_o, p_o, SEQ, DM, 128, 64, CU_TENSOR_MAP_SWIZZLE_128B);
  make_map(enc, &tm_h, p_h, SEQ, DM, 128, 32, CU_TENSOR_MAP_SWIZZLE_64B);
  make_map(enc, &tm_hh, p_hh, SEQ, FF, 128, 64, CU_TENSOR_MAP_SWIZZLE_128B);
  make_map(enc, &tm_hhs, p_hh, SEQ, FF, 64, 64, CU_TENSOR_MAP_SWIZZLE_128B);
  make_map(enc, &tm_xn, x, SEQ, DM, 128, 32, CU_TENSOR_MAP_SWIZZLE_64B);
  make_map(enc, &tm_hs, p_h, SEQ, DM, 64, 80, CU_TENSOR_MAP_SWIZZLE_NONE);
  make_map(enc, &tm_out, out, SEQ, DM, 64, 80, CU_TENSOR_MAP_SWIZZLE_NONE);

  launch(qkv_kernel, 128, GT, KA_SMEM, 2, false, tm_xn, tm_wqkv, x, wqkv);
  launch(attn_kernel, 132, AT_THREADS, AT_SMEM, 1, true, wo, wg, wu, wd);
  launch(mlp_kernel, 128, GT, KC_SMEM, 2, true, tm_o, tm_wo64, tm_wo16, tm_h, tm_wg, tm_wu, tm_hhs, tm_hh, tm_wd64, tm_wd16, tm_hs, tm_out, x);
}
```

```cpp
#include <cuda_runtime.h>
#include <cuda_bf16.h>
#include <cuda.h>
#include <stdint.h>

typedef __nv_bfloat16 bf16;
#define FLAGV 0

constexpr int SEQ = 2048, DM = 640, NH = 32, DH = 20, FF = 1536;
constexpr float ATT_SCALE_LOG2E = 0.22360679774997896f * 1.4426950408889634f;
constexpr int IMG_HEAD_ELEMS = (SEQ / 8) * 192;

__device__ __align__(1024) bf16 g_img[3 * NH * IMG_HEAD_ELEMS];
__device__ __align__(1024) bf16 g_o[SEQ * DM];
__device__ __align__(1024) bf16 g_h[SEQ * DM];
__device__ float2 g_stats[SEQ * 8];
__device__ float g_cs[2 * FF];
__device__ int g_flag[4 * 16];
__device__ float2 g_rs[SEQ];
__device__ __align__(1024) bf16 g_hh[SEQ * FF];

#define TS(k, i)
#define PH(w, t, i)
__device__ __forceinline__ uint32_t smem_u32(const void* p) { return (uint32_t)__cvta_generic_to_shared(p); }
__device__ __forceinline__ void mbar_init(uint32_t bar, uint32_t cnt) {
  asm volatile("mbarrier.init.shared::cta.b64 [%0], %1;" ::"r"(bar), "r"(cnt) : "memory");
}
__device__ __forceinline__ void mbar_expect_tx(uint32_t bar, uint32_t bytes) {
  asm volatile("mbarrier.arrive.expect_tx.shared::cta.b64 _, [%0], %1;" ::"r"(bar), "r"(bytes) : "memory");
}
__device__ __forceinline__ void mbar_arrive(uint32_t bar) {
  asm volatile("mbarrier.arrive.shared::cta.b64 _, [%0];" ::"r"(bar) : "memory");
}
__device__ __forceinline__ void mbar_arrive_cluster(uint32_t bar, uint32_t cta) {
  asm volatile(
      "{\n.reg .b32 r;\nmapa.shared::cluster.u32 r, %0, %1;\n"
      "mbarrier.arrive.shared::cluster.b64 _, [r];\n}\n" ::"r"(bar), "r"(cta)
      : "memory");
}
__device__ __forceinline__ void mbar_wait(uint32_t bar, uint32_t parity) {
  asm volatile(
      "{\n.reg .pred p;\nLAB_WAIT:\n"
      "mbarrier.try_wait.parity.shared::cta.b64 p, [%0], %1;\n"
      "@p bra DONE;\nbra LAB_WAIT;\nDONE:\n}\n" ::"r"(bar), "r"(parity)
      : "memory");
}
__device__ __forceinline__ void mbar_wait_cluster(uint32_t bar, uint32_t parity) {
  asm volatile(
      "{\n.reg .pred p;\nLAB_WAIT:\n"
      "mbarrier.try_wait.parity.acquire.cluster.shared::cta.b64 p, [%0], %1;\n"
      "@p bra DONE;\nbra LAB_WAIT;\nDONE:\n}\n" ::"r"(bar), "r"(parity)
      : "memory");
}
__device__ __forceinline__ void fence_mbar_init() { asm volatile("fence.mbarrier_init.release.cluster;" ::: "memory"); }
__device__ __forceinline__ void fence_proxy_async() { asm volatile("fence.proxy.async.shared::cta;" ::: "memory"); }
__device__ __forceinline__ void cluster_sync_all() {
  asm volatile("barrier.cluster.arrive.release.aligned;\nbarrier.cluster.wait.acquire.aligned;" ::: "memory");
}
__device__ __forceinline__ void cluster_sync_relaxed() {
  asm volatile("barrier.cluster.arrive.relaxed.aligned;\nbarrier.cluster.wait.aligned;" ::: "memory");
}
__device__ __forceinline__ void named_bar_sync(int id, int n) { asm volatile("bar.sync %0, %1;" ::"r"(id), "r"(n) : "memory"); }
__device__ __forceinline__ bool wg_any(bool pred, int id) {
  uint32_t r;
  asm volatile("{\n.reg .pred p, q;\nsetp.ne.u32 p, %1, 0;\nbar.red.or.pred q, %2, 128, p;\nselp.u32 %0, 1, 0, q;\n}\n" : "=r"(r) : "r"((uint32_t)pred), "r"(id) : "memory");
  return r != 0;
}
__device__ __forceinline__ void fence_proxy_async_all() { asm volatile("fence.proxy.async;" ::: "memory"); }
__device__ __forceinline__ void flag_signal(int* f) {
  __threadfence();
  atomicAdd(f, 1);
}
__device__ __forceinline__ void flag_wait(const int* f, int target) {
  int v;
  unsigned spins = 0;
  do {
    asm volatile("ld.acquire.gpu.global.s32 %0, [%1];" : "=r"(v) : "l"(f) : "memory");
    if (++spins > (1u << 24)) __trap();
  } while (v < target);
}
__device__ __forceinline__ void pdl_launch() { asm volatile("griddepcontrol.launch_dependents;" ::: "memory"); }
__device__ __forceinline__ void pdl_wait() { asm volatile("griddepcontrol.wait;" ::: "memory"); }

__device__ __forceinline__ void tma_load_2d(uint32_t dst, const CUtensorMap* tm, int c0, int c1, uint32_t bar) {
  asm volatile(
      "cp.async.bulk.tensor.2d.shared::cluster.global.mbarrier::complete_tx::bytes [%0], [%1, {%3, %4}], [%2];" ::"r"(dst),
      "l"((uint64_t)tm), "r"(bar), "r"(c0), "r"(c1)
      : "memory");
}
__device__ __forceinline__ void tma_load_2d_mc(uint32_t dst, const CUtensorMap* tm, int c0, int c1, uint32_t bar, uint16_t mask) {
  asm volatile(
      "cp.async.bulk.tensor.2d.shared::cluster.global.mbarrier::complete_tx::bytes.multicast::cluster [%0], [%1, {%3, %4}], [%2], %5;" ::"r"(dst),
      "l"((uint64_t)tm), "r"(bar), "r"(c0), "r"(c1), "h"(mask)
      : "memory");
}
__device__ __forceinline__ void bulk_g2s(uint32_t dst, const void* src, uint32_t bytes, uint32_t bar) {
  asm volatile("cp.async.bulk.shared::cluster.global.mbarrier::complete_tx::bytes [%0], [%1], %2, [%3];" ::"r"(dst), "l"(src),
               "r"(bytes), "r"(bar)
               : "memory");
}
__device__ __forceinline__ void bulk_s2g(void* dst, uint32_t src, uint32_t bytes) {
  asm volatile("cp.async.bulk.global.shared::cta.bulk_group [%0], [%1], %2;" ::"l"(dst), "r"(src), "r"(bytes) : "memory");
}
__device__ __forceinline__ void tma_store_2d(const CUtensorMap* tm, uint32_t src, int c0, int c1) {
  asm volatile("cp.async.bulk.tensor.2d.global.shared::cta.bulk_group [%0, {%2, %3}], [%1];" ::"l"((uint64_t)tm), "r"(src), "r"(c0), "r"(c1) : "memory");
}
__device__ __forceinline__ void bulk_commit() { asm volatile("cp.async.bulk.commit_group;" ::: "memory"); }
__device__ __forceinline__ void bulk_wait_read() { asm volatile("cp.async.bulk.wait_group.read 0;" ::: "memory"); }
__device__ __forceinline__ void prefetch_l2(const void* p, uint32_t bytes) {
  asm volatile("cp.async.bulk.prefetch.L2.global [%0], %1;" ::"l"(p), "r"(bytes) : "memory");
}
__device__ __forceinline__ void bulk_wait_all() { asm volatile("cp.async.bulk.wait_group 0;" ::: "memory"); }
__device__ __forceinline__ void st_shared_b32(uint32_t addr, uint32_t v) { asm volatile("st.shared.b32 [%0], %1;" ::"r"(addr), "r"(v) : "memory"); }
__device__ __forceinline__ void st_shared_v2(uint32_t addr, uint32_t a, uint32_t b) { asm volatile("st.shared.v2.b32 [%0], {%1, %2};" ::"r"(addr), "r"(a), "r"(b) : "memory"); }
__device__ __forceinline__ void prefetch_tmap(const CUtensorMap* tm) {
  asm volatile("prefetch.tensormap [%0];" ::"l"((uint64_t)tm) : "memory");
}
__device__ __forceinline__ void wgmma_fence() { asm volatile("wgmma.fence.sync.aligned;" ::: "memory"); }
__device__ __forceinline__ void wgmma_commit() { asm volatile("wgmma.commit_group.sync.aligned;" ::: "memory"); }
template <int N>
__device__ __forceinline__ void wgmma_wait() { asm volatile("wgmma.wait_group.sync.aligned %0;" ::"n"(N) : "memory"); }

template <int N>
__device__ __forceinline__ void fence_regs(float (&r)[N]) {
#pragma unroll
  for (int i = 0; i < N; i++) asm volatile("" : "+f"(r[i])::"memory");
}
template <int N>
__device__ __forceinline__ void fence_regs(uint32_t (&r)[N]) {
#pragma unroll
  for (int i = 0; i < N; i++) asm volatile("" : "+r"(r[i])::"memory");
}
__device__ __forceinline__ uint64_t make_desc(uint32_t addr, uint32_t lbo, uint32_t sbo, uint32_t layout) {
  return (uint64_t)((addr & 0x3FFFF) >> 4) | ((uint64_t)((lbo & 0x3FFFF) >> 4) << 16) | ((uint64_t)((sbo & 0x3FFFF) >> 4) << 32) |
         ((uint64_t)layout << 62);
}
__device__ __forceinline__ uint32_t pack_bf16(float lo, float hi) {
  uint32_t r;
  asm("cvt.rn.bf16x2.f32 %0, %1, %2;" : "=r"(r) : "f"(hi), "f"(lo));
  return r;
}
__device__ __forceinline__ float bf16_round(float x) { return __bfloat162float(__float2bfloat16_rn(x)); }
__device__ __forceinline__ float bf_lo(uint32_t u) { return __uint_as_float(u << 16); }
__device__ __forceinline__ float bf_hi(uint32_t u) { return __uint_as_float(u & 0xffff0000u); }
__device__ __forceinline__ float ex2(float x) {
  float y;
  asm("ex2.approx.ftz.f32 %0, %1;" : "=f"(y) : "f"(x));
  return y;
}

__device__ __forceinline__ void wgmma_ss_n240_tb(float (&d)[120], uint64_t descA, uint64_t descB, int scaleD) {
  asm volatile("{\n.reg .pred p;\nsetp.ne.b32 p, %122, 0;\n"
    "wgmma.mma_async.sync.aligned.m64n240k16.f32.bf16.bf16 {%0, %1, %2, %3, %4, %5, %6, %7, %8, %9, %10, %11, %12, %13, %14, %15, %16, %17, %18, %19, %20, %21, %22, %23, %24, %25, %26, %27, %28, %29, %30, %31, %32, %33, %34, %35, %36, %37, %38, %39, %40, %41, %42, %43, %44, %45, %46, %47, %48, %49, %50, %51, %52, %53, %54, %55, %56, %57, %58, %59, %60, %61, %62, %63, %64, %65, %66, %67, %68, %69, %70, %71, %72, %73, %74, %75, %76, %77, %78, %79, %80, %81, %82, %83, %84, %85, %86, %87, %88, %89, %90, %91, %92, %93, %94, %95, %96, %97, %98, %99, %100, %101, %102, %103, %104, %105, %106, %107, %108, %109, %110, %111, %112, %113, %114, %115, %116, %117, %118, %119}, %120, %121, p, 1, 1, 0, 1;\n}\n"
    : "+f"(d[0]), "+f"(d[1]), "+f"(d[2]), "+f"(d[3]), "+f"(d[4]), "+f"(d[5]), "+f"(d[6]), "+f"(d[7]), "+f"(d[8]), "+f"(d[9]), "+f"(d[10]), "+f"(d[11]), "+f"(d[12]), "+f"(d[13]), "+f"(d[14]), "+f"(d[15]), "+f"(d[16]), "+f"(d[17]), "+f"(d[18]), "+f"(d[19]), "+f"(d[20]), "+f"(d[21]), "+f"(d[22]), "+f"(d[23]), "+f"(d[24]), "+f"(d[25]), "+f"(d[26]), "+f"(d[27]), "+f"(d[28]), "+f"(d[29]), "+f"(d[30]), "+f"(d[31]), "+f"(d[32]), "+f"(d[33]), "+f"(d[34]), "+f"(d[35]), "+f"(d[36]), "+f"(d[37]), "+f"(d[38]), "+f"(d[39]), "+f"(d[40]), "+f"(d[41]), "+f"(d[42]), "+f"(d[43]), "+f"(d[44]), "+f"(d[45]), "+f"(d[46]), "+f"(d[47]), "+f"(d[48]), "+f"(d[49]), "+f"(d[50]), "+f"(d[51]), "+f"(d[52]), "+f"(d[53]), "+f"(d[54]), "+f"(d[55]), "+f"(d[56]), "+f"(d[57]), "+f"(d[58]), "+f"(d[59]), "+f"(d[60]), "+f"(d[61]), "+f"(d[62]), "+f"(d[63]), "+f"(d[64]), "+f"(d[65]), "+f"(d[66]), "+f"(d[67]), "+f"(d[68]), "+f"(d[69]), "+f"(d[70]), "+f"(d[71]), "+f"(d[72]), "+f"(d[73]), "+f"(d[74]), "+f"(d[75]), "+f"(d[76]), "+f"(d[77]), "+f"(d[78]), "+f"(d[79]), "+f"(d[80]), "+f"(d[81]), "+f"(d[82]), "+f"(d[83]), "+f"(d[84]), "+f"(d[85]), "+f"(d[86]), "+f"(d[87]), "+f"(d[88]), "+f"(d[89]), "+f"(d[90]), "+f"(d[91]), "+f"(d[92]), "+f"(d[93]), "+f"(d[94]), "+f"(d[95]), "+f"(d[96]), "+f"(d[97]), "+f"(d[98]), "+f"(d[99]), "+f"(d[100]), "+f"(d[101]), "+f"(d[102]), "+f"(d[103]), "+f"(d[104]), "+f"(d[105]), "+f"(d[106]), "+f"(d[107]), "+f"(d[108]), "+f"(d[109]), "+f"(d[110]), "+f"(d[111]), "+f"(d[112]), "+f"(d[113]), "+f"(d[114]), "+f"(d[115]), "+f"(d[116]), "+f"(d[117]), "+f"(d[118]), "+f"(d[119])
    : "l"(descA), "l"(descB), "r"(scaleD));
}
__device__ __forceinline__ void wgmma_ss_n192_tb(float (&d)[96], uint64_t descA, uint64_t descB, int scaleD) {
  asm volatile("{\n.reg .pred p;\nsetp.ne.b32 p, %98, 0;\n"
    "wgmma.mma_async.sync.aligned.m64n192k16.f32.bf16.bf16 {%0, %1, %2, %3, %4, %5, %6, %7, %8, %9, %10, %11, %12, %13, %14, %15, %16, %17, %18, %19, %20, %21, %22, %23, %24, %25, %26, %27, %28, %29, %30, %31, %32, %33, %34, %35, %36, %37, %38, %39, %40, %41, %42, %43, %44, %45, %46, %47, %48, %49, %50, %51, %52, %53, %54, %55, %56, %57, %58, %59, %60, %61, %62, %63, %64, %65, %66, %67, %68, %69, %70, %71, %72, %73, %74, %75, %76, %77, %78, %79, %80, %81, %82, %83, %84, %85, %86, %87, %88, %89, %90, %91, %92, %93, %94, %95}, %96, %97, p, 1, 1, 0, 1;\n}\n"
    : "+f"(d[0]), "+f"(d[1]), "+f"(d[2]), "+f"(d[3]), "+f"(d[4]), "+f"(d[5]), "+f"(d[6]), "+f"(d[7]), "+f"(d[8]), "+f"(d[9]), "+f"(d[10]), "+f"(d[11]), "+f"(d[12]), "+f"(d[13]), "+f"(d[14]), "+f"(d[15]), "+f"(d[16]), "+f"(d[17]), "+f"(d[18]), "+f"(d[19]), "+f"(d[20]), "+f"(d[21]), "+f"(d[22]), "+f"(d[23]), "+f"(d[24]), "+f"(d[25]), "+f"(d[26]), "+f"(d[27]), "+f"(d[28]), "+f"(d[29]), "+f"(d[30]), "+f"(d[31]), "+f"(d[32]), "+f"(d[33]), "+f"(d[34]), "+f"(d[35]), "+f"(d[36]), "+f"(d[37]), "+f"(d[38]), "+f"(d[39]), "+f"(d[40]), "+f"(d[41]), "+f"(d[42]), "+f"(d[43]), "+f"(d[44]), "+f"(d[45]), "+f"(d[46]), "+f"(d[47]), "+f"(d[48]), "+f"(d[49]), "+f"(d[50]), "+f"(d[51]), "+f"(d[52]), "+f"(d[53]), "+f"(d[54]), "+f"(d[55]), "+f"(d[56]), "+f"(d[57]), "+f"(d[58]), "+f"(d[59]), "+f"(d[60]), "+f"(d[61]), "+f"(d[62]), "+f"(d[63]), "+f"(d[64]), "+f"(d[65]), "+f"(d[66]), "+f"(d[67]), "+f"(d[68]), "+f"(d[69]), "+f"(d[70]), "+f"(d[71]), "+f"(d[72]), "+f"(d[73]), "+f"(d[74]), "+f"(d[75]), "+f"(d[76]), "+f"(d[77]), "+f"(d[78]), "+f"(d[79]), "+f"(d[80]), "+f"(d[81]), "+f"(d[82]), "+f"(d[83]), "+f"(d[84]), "+f"(d[85]), "+f"(d[86]), "+f"(d[87]), "+f"(d[88]), "+f"(d[89]), "+f"(d[90]), "+f"(d[91]), "+f"(d[92]), "+f"(d[93]), "+f"(d[94]), "+f"(d[95])
    : "l"(descA), "l"(descB), "r"(scaleD));
}
__device__ __forceinline__ void wgmma_ss_n64_tb(float (&d)[32], uint64_t descA, uint64_t descB, int scaleD) {
  asm volatile("{\n.reg .pred p;\nsetp.ne.b32 p, %34, 0;\n"
    "wgmma.mma_async.sync.aligned.m64n64k16.f32.bf16.bf16 {%0, %1, %2, %3, %4, %5, %6, %7, %8, %9, %10, %11, %12, %13, %14, %15, %16, %17, %18, %19, %20, %21, %22, %23, %24, %25, %26, %27, %28, %29, %30, %31}, %32, %33, p, 1, 1, 0, 1;\n}\n"
    : "+f"(d[0]), "+f"(d[1]), "+f"(d[2]), "+f"(d[3]), "+f"(d[4]), "+f"(d[5]), "+f"(d[6]), "+f"(d[7]), "+f"(d[8]), "+f"(d[9]), "+f"(d[10]), "+f"(d[11]), "+f"(d[12]), "+f"(d[13]), "+f"(d[14]), "+f"(d[15]), "+f"(d[16]), "+f"(d[17]), "+f"(d[18]), "+f"(d[19]), "+f"(d[20]), "+f"(d[21]), "+f"(d[22]), "+f"(d[23]), "+f"(d[24]), "+f"(d[25]), "+f"(d[26]), "+f"(d[27]), "+f"(d[28]), "+f"(d[29]), "+f"(d[30]), "+f"(d[31])
    : "l"(descA), "l"(descB), "r"(scaleD));
}
__device__ __forceinline__ void wgmma_ss_n16_tb(float (&d)[8], uint64_t descA, uint64_t descB, int scaleD) {
  asm volatile("{\n.reg .pred p;\nsetp.ne.b32 p, %10, 0;\n"
    "wgmma.mma_async.sync.aligned.m64n16k16.f32.bf16.bf16 {%0, %1, %2, %3, %4, %5, %6, %7}, %8, %9, p, 1, 1, 0, 1;\n}\n"
    : "+f"(d[0]), "+f"(d[1]), "+f"(d[2]), "+f"(d[3]), "+f"(d[4]), "+f"(d[5]), "+f"(d[6]), "+f"(d[7])
    : "l"(descA), "l"(descB), "r"(scaleD));
}
__device__ __forceinline__ void wgmma_rs_n128(float (&d)[64], uint32_t a0, uint32_t a1, uint32_t a2, uint32_t a3, uint64_t descB, int scaleD) {
  asm volatile("{\n.reg .pred p;\nsetp.ne.b32 p, %69, 0;\n"
    "wgmma.mma_async.sync.aligned.m64n128k16.f32.bf16.bf16 {%0, %1, %2, %3, %4, %5, %6, %7, %8, %9, %10, %11, %12, %13, %14, %15, %16, %17, %18, %19, %20, %21, %22, %23, %24, %25, %26, %27, %28, %29, %30, %31, %32, %33, %34, %35, %36, %37, %38, %39, %40, %41, %42, %43, %44, %45, %46, %47, %48, %49, %50, %51, %52, %53, %54, %55, %56, %57, %58, %59, %60, %61, %62, %63}, {%64, %65, %66, %67}, %68, p, 1, 1, 0;\n}\n"
    : "+f"(d[0]), "+f"(d[1]), "+f"(d[2]), "+f"(d[3]), "+f"(d[4]), "+f"(d[5]), "+f"(d[6]), "+f"(d[7]), "+f"(d[8]), "+f"(d[9]), "+f"(d[10]), "+f"(d[11]), "+f"(d[12]), "+f"(d[13]), "+f"(d[14]), "+f"(d[15]), "+f"(d[16]), "+f"(d[17]), "+f"(d[18]), "+f"(d[19]), "+f"(d[20]), "+f"(d[21]), "+f"(d[22]), "+f"(d[23]), "+f"(d[24]), "+f"(d[25]), "+f"(d[26]), "+f"(d[27]), "+f"(d[28]), "+f"(d[29]), "+f"(d[30]), "+f"(d[31]), "+f"(d[32]), "+f"(d[33]), "+f"(d[34]), "+f"(d[35]), "+f"(d[36]), "+f"(d[37]), "+f"(d[38]), "+f"(d[39]), "+f"(d[40]), "+f"(d[41]), "+f"(d[42]), "+f"(d[43]), "+f"(d[44]), "+f"(d[45]), "+f"(d[46]), "+f"(d[47]), "+f"(d[48]), "+f"(d[49]), "+f"(d[50]), "+f"(d[51]), "+f"(d[52]), "+f"(d[53]), "+f"(d[54]), "+f"(d[55]), "+f"(d[56]), "+f"(d[57]), "+f"(d[58]), "+f"(d[59]), "+f"(d[60]), "+f"(d[61]), "+f"(d[62]), "+f"(d[63])
    : "r"(a0), "r"(a1), "r"(a2), "r"(a3), "l"(descB), "r"(scaleD));
}
__device__ __forceinline__ void wgmma_rs_n64(float (&d)[32], uint32_t a0, uint32_t a1, uint32_t a2, uint32_t a3, uint64_t descB, int scaleD) {
  asm volatile("{\n.reg .pred p;\nsetp.ne.b32 p, %37, 0;\n"
    "wgmma.mma_async.sync.aligned.m64n64k16.f32.bf16.bf16 {%0, %1, %2, %3, %4, %5, %6, %7, %8, %9, %10, %11, %12, %13, %14, %15, %16, %17, %18, %19, %20, %21, %22, %23, %24, %25, %26, %27, %28, %29, %30, %31}, {%32, %33, %34, %35}, %36, p, 1, 1, 0;\n}\n"
    : "+f"(d[0]), "+f"(d[1]), "+f"(d[2]), "+f"(d[3]), "+f"(d[4]), "+f"(d[5]), "+f"(d[6]), "+f"(d[7]), "+f"(d[8]), "+f"(d[9]), "+f"(d[10]), "+f"(d[11]), "+f"(d[12]), "+f"(d[13]), "+f"(d[14]), "+f"(d[15]), "+f"(d[16]), "+f"(d[17]), "+f"(d[18]), "+f"(d[19]), "+f"(d[20]), "+f"(d[21]), "+f"(d[22]), "+f"(d[23]), "+f"(d[24]), "+f"(d[25]), "+f"(d[26]), "+f"(d[27]), "+f"(d[28]), "+f"(d[29]), "+f"(d[30]), "+f"(d[31])
    : "r"(a0), "r"(a1), "r"(a2), "r"(a3), "l"(descB), "r"(scaleD));
}
__device__ __forceinline__ void wgmma_rs_n24_tb(float (&d)[12], uint32_t a0, uint32_t a1, uint32_t a2, uint32_t a3, uint64_t descB, int scaleD) {
  asm volatile("{\n.reg .pred p;\nsetp.ne.b32 p, %17, 0;\n"
    "wgmma.mma_async.sync.aligned.m64n24k16.f32.bf16.bf16 {%0, %1, %2, %3, %4, %5, %6, %7, %8, %9, %10, %11}, {%12, %13, %14, %15}, %16, p, 1, 1, 1;\n}\n"
    : "+f"(d[0]), "+f"(d[1]), "+f"(d[2]), "+f"(d[3]), "+f"(d[4]), "+f"(d[5]), "+f"(d[6]), "+f"(d[7]), "+f"(d[8]), "+f"(d[9]), "+f"(d[10]), "+f"(d[11])
    : "r"(a0), "r"(a1), "r"(a2), "r"(a3), "l"(descB), "r"(scaleD));
}

constexpr int GT = 384;

__device__ __forceinline__ void release_stage(uint32_t bar, bool leader) {
  if (leader) {
    mbar_arrive_cluster(bar, 0);
    mbar_arrive_cluster(bar, 1);
  }
}

__device__ __forceinline__ float2 ln_row_stats(const bf16* __restrict__ xin, int l16) {
  const uint4* src = reinterpret_cast<const uint4*>(xin);
  uint4 v[5];
#pragma unroll
  for (int j = 0; j < 5; j++) v[j] = __ldg(src + j * 16 + l16);
  float s0 = 0.f, s1 = 0.f, s2 = 0.f, s3 = 0.f;
#pragma unroll
  for (int j = 0; j < 5; j++) {
    s0 += bf_lo(v[j].x) + bf_hi(v[j].x);
    s1 += bf_lo(v[j].y) + bf_hi(v[j].y);
    s2 += bf_lo(v[j].z) + bf_hi(v[j].z);
    s3 += bf_lo(v[j].w) + bf_hi(v[j].w);
  }
  float mean = (s0 + s1) + (s2 + s3);
#pragma unroll
  for (int o = 1; o < 16; o <<= 1) mean += __shfl_xor_sync(0xffffffffu, mean, o);
  mean *= (1.0f / DM);
  s0 = s1 = s2 = s3 = 0.f;
#pragma unroll
  for (int j = 0; j < 5; j++) {
    float d;
    d = bf_lo(v[j].x) - mean; s0 = fmaf(d, d, s0);
    d = bf_hi(v[j].x) - mean; s1 = fmaf(d, d, s1);
    d = bf_lo(v[j].y) - mean; s2 = fmaf(d, d, s2);
    d = bf_hi(v[j].y) - mean; s3 = fmaf(d, d, s3);
    d = bf_lo(v[j].z) - mean; s0 = fmaf(d, d, s0);
    d = bf_hi(v[j].z) - mean; s1 = fmaf(d, d, s1);
    d = bf_lo(v[j].w) - mean; s2 = fmaf(d, d, s2);
    d = bf_hi(v[j].w) - mean; s3 = fmaf(d, d, s3);
  }
  float sq = (s0 + s1) + (s2 + s3);
#pragma unroll
  for (int o = 1; o < 16; o <<= 1) sq += __shfl_xor_sync(0xffffffffu, sq, o);
  const float var_b = bf16_round(sq * (1.0f / DM));
  const float den = bf16_round(sqrtf(bf16_round(var_b + 1e-5f)));
  return make_float2(bf16_round(mean), __frcp_rn(den));
}

constexpr int LG_STAGES = 5;
constexpr int QKV_STAGE = 8192 + 4 * 4096;
constexpr int GLU_STAGE = 8192 + 6 * 4096;

template <int WG>
__device__ __forceinline__ void qkv_mainloop(float (&acc)[120], uint32_t sbase, uint32_t sBar, bool leader) {
  constexpr int STAGE_BYTES = QKV_STAGE, NST = LG_STAGES;
  const uint64_t da_base = make_desc(sbase + WG * 4096, 16, 512, 2);
  const uint64_t db_base = make_desc(sbase + 8192, 4096, 1024, 1);
#pragma unroll 1
  for (int r = 0; r < 20 / NST; r++) {
#pragma unroll
    for (int s = 0; s < NST; s++) {
      mbar_wait(sBar + 8 * s, r & 1);
      wgmma_fence();
#pragma unroll
      for (int ks = 0; ks < 2; ks++)
        wgmma_ss_n240_tb(acc, da_base + (uint64_t)((s * STAGE_BYTES + ks * 32) >> 4), db_base + (uint64_t)((s * STAGE_BYTES + ks * 2048) >> 4), 1);
      wgmma_commit();
      wgmma_wait<1>();
      release_stage(sBar + 8 * (NST + (s + NST - 1) % NST), leader && (s > 0 || r > 0));
    }
  }
}
template <int WG>
__device__ __forceinline__ void glu_mainloop(float (&accg)[96], float (&accu)[96], uint32_t sbase, uint32_t sBar, bool leader) {
  constexpr int STAGE_BYTES = GLU_STAGE, NST = LG_STAGES;
  const uint64_t da_base = make_desc(sbase + WG * 4096, 16, 512, 2);
  const uint64_t db_base = make_desc(sbase + 8192, 4096, 1024, 1);
#pragma unroll 1
  for (int r = 0; r < 20 / NST; r++) {
#pragma unroll
    for (int s = 0; s < NST; s++) {
      mbar_wait(sBar + 8 * s, r & 1);
      wgmma_fence();
#pragma unroll
      for (int ks = 0; ks < 2; ks++) {
        const uint64_t da = da_base + (uint64_t)((s * STAGE_BYTES + ks * 32) >> 4);
        wgmma_ss_n192_tb(accg, da, db_base + (uint64_t)((s * STAGE_BYTES + ks * 2048) >> 4), 1);
        wgmma_ss_n192_tb(accu, da, db_base + (uint64_t)((s * STAGE_BYTES + 3 * 4096 + ks * 2048) >> 4), 1);
      }
      wgmma_commit();
      wgmma_wait<1>();
      release_stage(sBar + 8 * (NST + (s + NST - 1) % NST), leader && (s > 0 || r > 0));
    }
  }
}
constexpr int RG_STAGE_BYTES = 16384 + 8192 + 2048;
template <int NKB, int NST, int WG>
__device__ __forceinline__ void res_mainloop(float (&acc0)[32], float (&acc1)[8], uint32_t sbase, uint32_t sBar, bool leader) {
  const uint64_t da_base = make_desc(sbase + WG * 8192, 16, 1024, 1);
  const uint64_t db0_base = make_desc(sbase + 16384, 8192, 1024, 1);
  const uint64_t db1_base = make_desc(sbase + 16384 + 8192, 2048, 256, 3);
#pragma unroll 1
  for (int r = 0; r < NKB / NST; r++) {
#pragma unroll
    for (int s = 0; s < NST; s++) {
      const uint64_t so = (uint64_t)(s * (RG_STAGE_BYTES >> 4));
      mbar_wait(sBar + 8 * s, r & 1);
      wgmma_fence();
#pragma unroll
      for (int ks = 0; ks < 4; ks++) {
        wgmma_ss_n64_tb(acc0, da_base + so + ks * 2, db0_base + so + ks * 128, 1);
        wgmma_ss_n16_tb(acc1, da_base + so + ks * 2, db1_base + so + ks * 32, 1);
      }
      wgmma_commit();
      wgmma_wait<1>();
      release_stage(sBar + 8 * (NST + (s + NST - 1) % NST), leader && (s > 0 || r > 0));
    }
  }
}

constexpr int KA_CS = LG_STAGES * QKV_STAGE + 128;
constexpr int KA_SMEM = KA_CS + 1024 + 3072 + 1024;

__global__ void __launch_bounds__(GT, 1)
qkv_kernel(const __grid_constant__ CUtensorMap tmA, const __grid_constant__ CUtensorMap tmB, const bf16* __restrict__ x,
           const bf16* __restrict__ wqkv) {
  constexpr int STAGE_BYTES = QKV_STAGE, NST = LG_STAGES, NKB = 20;
  extern __shared__ uint8_t smem_raw[];
  const uint32_t sbase = (smem_u32(smem_raw) + 1023u) & ~1023u;
  const uint32_t sBar = sbase + NST * STAGE_BYTES;
  const int tid = threadIdx.x, warp = tid >> 5, lane = tid & 31;
  const int rank = blockIdx.x & 1;
  const int pair = blockIdx.x >> 1;
  const int n_blk = pair & 7;
  const int m_blk = (pair >> 3) * 2 + rank;
  TS(0, 0);
  if (tid == 256) {
    prefetch_tmap(&tmA);
    prefetch_tmap(&tmB);
  }
  if (tid == 0) {
    for (int s = 0; s < NST; s++) {
      mbar_init(sBar + 8 * s, 1);
      mbar_init(sBar + 8 * (NST + s), 6);
    }
    fence_mbar_init();
    if (blockIdx.x < 32) g_flag[16 + blockIdx.x] = 0;
  }
  pdl_launch();
  cluster_sync_all();

  if (warp >= 8) {
    asm volatile("setmaxnreg.dec.sync.aligned.u32 64;");
    if (warp >= 9) {
      float* red = reinterpret_cast<float*>(smem_raw + (sbase - smem_u32(smem_raw)) + KA_CS + 1024);
      if (warp == 11) {
        named_bar_sync(5, 288);
        if (lane == 0) {
          flag_signal(&g_flag[m_blk]);
          flag_wait(&g_flag[m_blk], 8);
        }
        __syncwarp();
        float2* rs_s = reinterpret_cast<float2*>(red + 480);
#pragma unroll
        for (int r = 0; r < 4; r++) rs_s[r * 32 + lane] = g_rs[m_blk * 128 + r * 32 + lane];
      } else {
        const int t64 = tid - 288;
        const int cc = t64 % 30, rg = t64 / 30;
        float a[8];
#pragma unroll
        for (int i = 0; i < 8; i++) a[i] = 0.f;
#pragma unroll 1
        for (int kb = 0; kb < NKB; kb++) {
          const int s = kb % NST;
          mbar_wait(sBar + 8 * s, (kb / NST) & 1);
          if (rg < 2) {
            const uint32_t base = sbase + s * STAGE_BYTES + 8192 + (cc >> 3) * 4096 + rg * 2048;
#pragma unroll
            for (int h = 0; h < 2; h++) {
              uint4 v[8];
#pragma unroll
              for (int r = 0; r < 8; r++)
                asm volatile("ld.shared.v4.b32 {%0, %1, %2, %3}, [%4];" : "=r"(v[r].x), "=r"(v[r].y), "=r"(v[r].z), "=r"(v[r].w)
                             : "r"(base + (h * 8 + r) * 128 + (((cc & 7) ^ r) << 4)));
#pragma unroll
              for (int r = 0; r < 8; r++) {
                a[0] += bf_lo(v[r].x); a[1] += bf_hi(v[r].x); a[2] += bf_lo(v[r].y); a[3] += bf_hi(v[r].y);
                a[4] += bf_lo(v[r].z); a[5] += bf_hi(v[r].z); a[6] += bf_lo(v[r].w); a[7] += bf_hi(v[r].w);
              }
            }
          }
          named_bar_sync(4, 64);
          release_stage(sBar + 8 * (NST + s), t64 == 0);
        }
        if (rg < 2) {
#pragma unroll
          for (int i = 0; i < 8; i++) red[rg * 240 + cc * 8 + i] = a[i];
        }
        named_bar_sync(4, 64);
        float* cs_s = reinterpret_cast<float*>(smem_raw + (sbase - smem_u32(smem_raw)) + KA_CS);
        for (int c = t64; c < 240; c += 64) cs_s[c] = red[c] + red[240 + c];
      }
      named_bar_sync(6, 352);
    }
    if (tid == 256) {
      auto issue_b = [&](int kb) {
        const int s = kb % NST;
        const uint32_t full = sBar + 8 * s;
        mbar_expect_tx(full, STAGE_BYTES);
        const uint32_t dst = sbase + s * STAGE_BYTES + 8192;
#pragma unroll
        for (int j = 0; j < 2; j++) {
          const int sl = rank * 2 + j;
          tma_load_2d_mc(dst + sl * 4096, &tmB, n_blk * 240 + sl * 64, kb * 32, full, (uint16_t)3);
        }
      };
      for (int kb = 0; kb < NKB; kb++) {
        const int s = kb % NST;
        if (kb >= NST) mbar_wait(sBar + 8 * (NST + s), ((kb / NST) & 1) ^ 1);
        issue_b(kb);
        tma_load_2d(sbase + s * STAGE_BYTES, &tmA, kb * 32, m_blk * 128, sBar + 8 * s);
      }
    }
  } else {
    asm volatile("setmaxnreg.inc.sync.aligned.u32 216;");
    const int wg = __shfl_sync(0xffffffffu, warp >> 2, 0);
    const int wwarp = warp & 3;
    {
      const int row = m_blk * 128 + n_blk * 16 + warp * 2 + (lane >> 4);
      const float2 rs = ln_row_stats(x + (size_t)row * DM, lane & 15);
      if ((lane & 15) == 0) g_rs[row] = rs;
      asm volatile("bar.arrive 5, 288;" ::: "memory");
    }
    TS(0, 1);
    mbar_wait(sBar, 0);
    TS(0, 3);
    float acc[120];
#pragma unroll
    for (int i = 0; i < 120; i++) acc[i] = 0.f;
    if (wg == 0) qkv_mainloop<0>(acc, sbase, sBar, (tid & 127) == 0);
    else qkv_mainloop<1>(acc, sbase, sBar, (tid & 127) == 0);
    wgmma_wait<0>();
    fence_regs(acc);
    TS(0, 4);
    const int g = lane >> 2, c4 = lane & 3;
    float* cs_s = reinterpret_cast<float*>(smem_raw + (sbase - smem_u32(smem_raw)) + KA_CS);
    named_bar_sync(6, 352);
    TS(0, 7);
    const float2* rs_s = reinterpret_cast<const float2*>(smem_raw + (sbase - smem_u32(smem_raw)) + KA_CS + 1024 + 1920);
    const float2 rs0 = rs_s[wg * 64 + wwarp * 16 + g], rs1 = rs_s[wg * 64 + wwarp * 16 + g + 8];
    const uint32_t stg = sbase + wg * (12 * 3072) + (wwarp * 2) * 384 + g * 16;
    const int hbase = n_blk * 12;
    float2 ccv[10];
#pragma unroll
    for (int j = 0; j < 30; j++) {
      if (j % 10 == 0) {
#pragma unroll
        for (int jj = 0; jj < 10; jj++) ccv[jj] = *reinterpret_cast<const float2*>(cs_s + (j + jj) * 8 + c4 * 2);
      }
      const int cb = (j * 8) % 20;
      const int hb = (j * 8) / 20;
      int d = cb + c4 * 2;
      int hl = hb;
      if (cb == 16 && c4 >= 2) { d -= 20; hl += 1; }
      const uint32_t a0 = stg + hl * 3072 + (d >> 3) * 128 + (d & 7) * 2;
      const int hg = hbase + hl;
      const float sc = hg < 32 ? ATT_SCALE_LOG2E : 1.0f;
      const float2 cc = ccv[j % 10];
      const float i0 = rs0.y * sc, i1 = rs1.y * sc;
      st_shared_b32(a0, pack_bf16(fmaf(-rs0.x, cc.x, acc[4 * j]) * i0, fmaf(-rs0.x, cc.y, acc[4 * j + 1]) * i0));
      st_shared_b32(a0 + 384, pack_bf16(fmaf(-rs1.x, cc.x, acc[4 * j + 2]) * i1, fmaf(-rs1.x, cc.y, acc[4 * j + 3]) * i1));
      if (d == 18) {
        const uint32_t pad0 = hg < 32 ? 0u : (hg < 64 ? 0x3f803f80u : 0x00003f80u);
        const uint32_t pad1 = (hg >= 32 && hg < 64) ? 0x00003f80u : 0u;
        st_shared_v2(a0 + 4, pad0, pad1);
        st_shared_v2(a0 + 388, pad0, pad1);
      }
      if (j == 0) TS(0, 15);
      if (j == 4) TS(0, 2);
      if (j % 10 == 9) {
        TS(0, 9 + (j / 10) * 2);
        fence_proxy_async();
        named_bar_sync(1 + wg, 128);
        TS(0, 10 + (j / 10) * 2);
        if ((tid & 127) < 4) {
          const int hs = (j / 10) * 4 + (tid & 127);
          bf16* dst = g_img + (size_t)(hbase + hs) * IMG_HEAD_ELEMS + (size_t)(m_blk * 16 + wg * 8) * 192;
          bulk_s2g(dst, sbase + wg * (12 * 3072) + hs * 3072, 3072);
          bulk_commit();
        }
      }
    }
    TS(0, 8);
    if ((tid & 127) < 4) bulk_wait_read();
  }
  __syncwarp();
  TS(0, 5);
  cluster_sync_relaxed();
  TS(0, 6);
}

constexpr int KC_NST1 = 5, KC_NST3 = 6;
constexpr int KC_STAGING = 160 * 1024;
constexpr int KC_BAR = KC_STAGING + 48 * 1024;
constexpr int KC_CS = KC_BAR + 512;
constexpr int KC_SMEM = KC_CS + 1536 + 1024;

__global__ void __launch_bounds__(GT, 1)
mlp_kernel(const __grid_constant__ CUtensorMap tmO, const __grid_constant__ CUtensorMap tmWo64, const __grid_constant__ CUtensorMap tmWo16,
           const __grid_constant__ CUtensorMap tmH, const __grid_constant__ CUtensorMap tmWg, const __grid_constant__ CUtensorMap tmWu,
           const __grid_constant__ CUtensorMap tmHHs, const __grid_constant__ CUtensorMap tmHH, const __grid_constant__ CUtensorMap tmWd64,
           const __grid_constant__ CUtensorMap tmWd16, const __grid_constant__ CUtensorMap tmHs, const __grid_constant__ CUtensorMap tmOut,
           const bf16* __restrict__ x) {
  extern __shared__ uint8_t smem_raw[];
  const uint32_t sbase = (smem_u32(smem_raw) + 1023u) & ~1023u;
  const uint32_t bar1 = sbase + KC_BAR;
  const uint32_t bar2 = bar1 + 128;
  const uint32_t bar3 = bar2 + 128;
  const uint32_t barD = bar3 + 128;
  const int tid = threadIdx.x, warp = tid >> 5, lane = tid & 31;
  const int rank = blockIdx.x & 1;
  const int pair = blockIdx.x >> 1;
  const int j_blk = pair & 7;
  const int m_blk = (pair >> 3) * 2 + rank;
  const int n0 = j_blk * 80;
  TS(2, 0);
  if (tid == 256) {
    prefetch_tmap(&tmO); prefetch_tmap(&tmWo64); prefetch_tmap(&tmWo16); prefetch_tmap(&tmH); prefetch_tmap(&tmWg);
    prefetch_tmap(&tmWu); prefetch_tmap(&tmHHs); prefetch_tmap(&tmHH); prefetch_tmap(&tmWd64); prefetch_tmap(&tmWd16);
    prefetch_tmap(&tmHs); prefetch_tmap(&tmOut);
  }
  if (tid == 0) {
    for (int s = 0; s < 5; s++) {
      mbar_init(bar1 + 8 * s, 1); mbar_init(bar1 + 8 * (5 + s), 4);
      mbar_init(bar2 + 8 * s, 1); mbar_init(bar2 + 8 * (5 + s), 4);
    }
    for (int s = 0; s < 6; s++) { mbar_init(bar3 + 8 * s, 1); mbar_init(bar3 + 8 * (6 + s), 4); }
    mbar_init(barD, 4); mbar_init(barD + 8, 4);
    fence_mbar_init();
  }
  cluster_sync_all();

  if (warp >= 8) {
    asm volatile("setmaxnreg.dec.sync.aligned.u32 40;");
    if (tid == 256) {
      auto issue_b80 = [&](const CUtensorMap* t64, const CUtensorMap* t16, uint32_t bars, int nst, int kb) {
        const int s = kb % nst;
        const uint32_t full = bars + 8 * s;
        const uint32_t st = sbase + s * RG_STAGE_BYTES;
        mbar_expect_tx(full, RG_STAGE_BYTES);
        tma_load_2d_mc(st + 16384 + rank * 4096, t64, n0, kb * 64 + rank * 32, full, (uint16_t)3);
        tma_load_2d_mc(st + 16384 + 8192 + rank * 1024, t16, n0 + 64, kb * 64 + rank * 32, full, (uint16_t)3);
      };
      for (int kb = 0; kb < KC_NST1; kb++) issue_b80(&tmWo64, &tmWo16, bar1, KC_NST1, kb);
      pdl_wait();
      for (int kb = 0; kb < 10; kb++) {
        const int s = kb % KC_NST1;
        if (kb >= KC_NST1) {
          mbar_wait(bar1 + 8 * (KC_NST1 + s), ((kb / KC_NST1) & 1) ^ 1);
          issue_b80(&tmWo64, &tmWo16, bar1, KC_NST1, kb);
        }
        tma_load_2d(sbase + s * RG_STAGE_BYTES, &tmO, kb * 64, m_blk * 128, bar1 + 8 * s);
      }
      auto issue_bglu = [&](int kb) {
        const int s = kb % LG_STAGES;
        const uint32_t full = bar2 + 8 * s;
        mbar_expect_tx(full, GLU_STAGE);
        const uint32_t dst = sbase + s * GLU_STAGE + 8192;
#pragma unroll
        for (int j = 0; j < 3; j++)
          tma_load_2d_mc(dst + (rank * 3 + j) * 4096, rank == 0 ? &tmWg : &tmWu, j_blk * 192 + j * 64, kb * 32, full, (uint16_t)3);
      };
      mbar_wait(barD, 0);
      for (int kb = 0; kb < LG_STAGES; kb++) issue_bglu(kb);
      flag_wait(&g_flag[16 + m_blk], 16);
      fence_proxy_async_all();
      for (int kb = 0; kb < 20; kb++) {
        const int s = kb % LG_STAGES;
        if (kb >= LG_STAGES) {
          mbar_wait(bar2 + 8 * (LG_STAGES + s), ((kb / LG_STAGES) & 1) ^ 1);
          issue_bglu(kb);
        }
        tma_load_2d(sbase + s * GLU_STAGE, &tmH, kb * 32, m_blk * 128, bar2 + 8 * s);
      }
      mbar_wait(barD + 8, 0);
      for (int kb = 0; kb < KC_NST3; kb++) issue_b80(&tmWd64, &tmWd16, bar3, KC_NST3, kb);
      flag_wait(&g_flag[32 + m_blk], 16);
      fence_proxy_async_all();
      for (int kb = 0; kb < 24; kb++) {
        const int s = kb % KC_NST3;
        if (kb >= KC_NST3) {
          mbar_wait(bar3 + 8 * (KC_NST3 + s), ((kb / KC_NST3) & 1) ^ 1);
          issue_b80(&tmWd64, &tmWd16, bar3, KC_NST3, kb);
        }
        tma_load_2d(sbase + s * RG_STAGE_BYTES, &tmHH, kb * 64, m_blk * 128, bar3 + 8 * s);
      }
    }
  } else {
    asm volatile("setmaxnreg.inc.sync.aligned.u32 232;");
    const int wg = __shfl_sync(0xffffffffu, warp >> 2, 0);
    const int wwarp = warp & 3;
    const int g = lane >> 2, c4 = lane & 3;
    const int row0 = m_blk * 128 + wg * 64 + wwarp * 16 + g;
    const bool leader = (tid & 127) == 0;
    const uint32_t stg80_base = sbase + KC_STAGING + wg * 24576;
    const uint32_t stg80 = stg80_base + (wwarp * 16 + g) * 160 + c4 * 4;
    {
      uint32_t res[20];
#pragma unroll
      for (int j = 0; j < 10; j++) {
        res[2 * j] = __ldg(reinterpret_cast<const uint32_t*>(x + (size_t)row0 * DM + n0 + j * 8 + c4 * 2));
        res[2 * j + 1] = __ldg(reinterpret_cast<const uint32_t*>(x + (size_t)(row0 + 8) * DM + n0 + j * 8 + c4 * 2));
      }
      float acc0[32], acc1[8];
#pragma unroll
      for (int i = 0; i < 32; i++) acc0[i] = 0.f;
#pragma unroll
      for (int i = 0; i < 8; i++) acc1[i] = 0.f;
      TS(2, 1);
      if (wg == 0) res_mainloop<10, KC_NST1, 0>(acc0, acc1, sbase, bar1, leader);
      else res_mainloop<10, KC_NST1, 1>(acc0, acc1, sbase, bar1, leader);
      wgmma_wait<0>();
      fence_regs(acc0); fence_regs(acc1);
      release_stage(barD, leader);
      TS(2, 4);
      float sum0 = 0.f, sum1 = 0.f;
#pragma unroll
      for (int j = 0; j < 10; j++) {
        const uint32_t a01 = j < 8 ? pack_bf16(acc0[4 * j], acc0[4 * j + 1]) : pack_bf16(acc1[4 * (j - 8)], acc1[4 * (j - 8) + 1]);
        const uint32_t a23 = j < 8 ? pack_bf16(acc0[4 * j + 2], acc0[4 * j + 3]) : pack_bf16(acc1[4 * (j - 8) + 2], acc1[4 * (j - 8) + 3]);
        res[2 * j] = pack_bf16(bf_lo(res[2 * j]) + bf_lo(a01), bf_hi(res[2 * j]) + bf_hi(a01));
        res[2 * j + 1] = pack_bf16(bf_lo(res[2 * j + 1]) + bf_lo(a23), bf_hi(res[2 * j + 1]) + bf_hi(a23));
        st_shared_b32(stg80 + j * 16, res[2 * j]);
        st_shared_b32(stg80 + 8 * 160 + j * 16, res[2 * j + 1]);
        sum0 += bf_lo(res[2 * j]) + bf_hi(res[2 * j]);
        sum1 += bf_lo(res[2 * j + 1]) + bf_hi(res[2 * j + 1]);
      }
      sum0 += __shfl_xor_sync(0xffffffffu, sum0, 1); sum1 += __shfl_xor_sync(0xffffffffu, sum1, 1);
      sum0 += __shfl_xor_sync(0xffffffffu, sum0, 2); sum1 += __shfl_xor_sync(0xffffffffu, sum1, 2);
      const float mu0 = sum0 * (1.0f / 80.0f), mu1 = sum1 * (1.0f / 80.0f);
      float q0 = 0.f, q1 = 0.f;
#pragma unroll
      for (int j = 0; j < 10; j++) {
        float d;
        d = bf_lo(res[2 * j]) - mu0; q0 = fmaf(d, d, q0);
        d = bf_hi(res[2 * j]) - mu0; q0 = fmaf(d, d, q0);
        d = bf_lo(res[2 * j + 1]) - mu1; q1 = fmaf(d, d, q1);
        d = bf_hi(res[2 * j + 1]) - mu1; q1 = fmaf(d, d, q1);
      }
      q0 += __shfl_xor_sync(0xffffffffu, q0, 1); q1 += __shfl_xor_sync(0xffffffffu, q1, 1);
      q0 += __shfl_xor_sync(0xffffffffu, q0, 2); q1 += __shfl_xor_sync(0xffffffffu, q1, 2);
      if (c4 == 0) {
        g_stats[row0 * 8 + j_blk] = make_float2(mu0, q0);
        g_stats[(row0 + 8) * 8 + j_blk] = make_float2(mu1, q1);
      }
      fence_proxy_async();
      named_bar_sync(1 + wg, 128);
      if (leader) {
        tma_store_2d(&tmHs, stg80_base, n0, m_blk * 128 + wg * 64);
        bulk_commit();
        bulk_wait_all();
        fence_proxy_async_all();
        flag_signal(&g_flag[16 + m_blk]);
      }
      TS(2, 5);
    }
    {
      pdl_wait();
      {
        float* cs_s = reinterpret_cast<float*>(smem_raw + (sbase - smem_u32(smem_raw)) + KC_CS);
        for (int i = tid; i < 384; i += 256) cs_s[i] = g_cs[(i >= 192 ? FF - 192 : 0) + j_blk * 192 + i];
        named_bar_sync(3, 256);
      }
      flag_wait(&g_flag[16 + m_blk], 16);
      float mb[2], iv[2];
#pragma unroll
      for (int h = 0; h < 2; h++) {
        const float4* sp = reinterpret_cast<const float4*>(g_stats + (row0 + 8 * h) * 8);
        const float4 p0 = sp[0], p1 = sp[1], p2 = sp[2], p3 = sp[3];
        const float mean = (((p0.x + p0.z) + (p1.x + p1.z)) + ((p2.x + p2.z) + (p3.x + p3.z))) * 0.125f;
        float m2 = ((p0.y + p0.w) + (p1.y + p1.w)) + ((p2.y + p2.w) + (p3.y + p3.w));
        float dd = 0.f, d;
        d = p0.x - mean; dd = fmaf(d, d, dd); d = p0.z - mean; dd = fmaf(d, d, dd);
        d = p1.x - mean; dd = fmaf(d, d, dd); d = p1.z - mean; dd = fmaf(d, d, dd);
        d = p2.x - mean; dd = fmaf(d, d, dd); d = p2.z - mean; dd = fmaf(d, d, dd);
        d = p3.x - mean; dd = fmaf(d, d, dd); d = p3.z - mean; dd = fmaf(d, d, dd);
        m2 = fmaf(dd, 80.0f, m2);
        const float var_b = bf16_round(m2 * (1.0f / DM));
        const float den = bf16_round(sqrtf(bf16_round(var_b + 1e-5f)));
        iv[h] = __frcp_rn(den);
        mb[h] = bf16_round(mean);
      }
      float accg[96], accu[96];
#pragma unroll
      for (int i = 0; i < 96; i++) { accg[i] = 0.f; accu[i] = 0.f; }
      TS(3, 3);
      if (wg == 0) glu_mainloop<0>(accg, accu, sbase, bar2, leader);
      else glu_mainloop<1>(accg, accu, sbase, bar2, leader);
      wgmma_wait<0>();
      fence_regs(accg); fence_regs(accu);
      release_stage(barD + 8, leader);
      TS(3, 4);
      const uint32_t stg = sbase + KC_STAGING + wg * 24576 + (wwarp * 16 + g) * 128 + c4 * 4;
      const float* csg = reinterpret_cast<const float*>(smem_raw + (sbase - smem_u32(smem_raw)) + KC_CS) + c4 * 2;
      const float nm0 = -mb[0] * iv[0], nm1 = -mb[1] * iv[1];
#pragma unroll
      for (int sl = 0; sl < 3; sl++) {
        float2 cgv[4], cuv[4];
#pragma unroll
        for (int jj = 0; jj < 8; jj++) {
          const int j = sl * 8 + jj;
          if ((jj & 3) == 0) {
#pragma unroll
            for (int q = 0; q < 4; q++) {
              cgv[q] = *reinterpret_cast<const float2*>(csg + (j + q) * 8);
              cuv[q] = *reinterpret_cast<const float2*>(csg + 192 + (j + q) * 8);
            }
          }
          const float2 cg = cgv[jj & 3], cu = cuv[jj & 3];
          const float r0 = fmaxf(fmaf(accg[4 * j], iv[0], nm0 * cg.x), 0.f) * fmaf(accu[4 * j], iv[0], nm0 * cu.x);
          const float r1 = fmaxf(fmaf(accg[4 * j + 1], iv[0], nm0 * cg.y), 0.f) * fmaf(accu[4 * j + 1], iv[0], nm0 * cu.y);
          const float r2 = fmaxf(fmaf(accg[4 * j + 2], iv[1], nm1 * cg.x), 0.f) * fmaf(accu[4 * j + 2], iv[1], nm1 * cu.x);
          const float r3 = fmaxf(fmaf(accg[4 * j + 3], iv[1], nm1 * cg.y), 0.f) * fmaf(accu[4 * j + 3], iv[1], nm1 * cu.y);
          const uint32_t a0 = stg + sl * 8192 + ((jj ^ g) << 4);
          st_shared_b32(a0, pack_bf16(r0, r1));
          st_shared_b32(a0 + 1024, pack_bf16(r2, r3));
        }
        fence_proxy_async();
        named_bar_sync(1 + wg, 128);
        if (leader) {
          tma_store_2d(&tmHHs, sbase + KC_STAGING + wg * 24576 + sl * 8192, j_blk * 192 + sl * 64, m_blk * 128 + wg * 64);
          bulk_commit();
        }
      }
      TS(3, 7);
      if (leader) {
        bulk_wait_all();
        TS(3, 8);
        fence_proxy_async_all();
        flag_signal(&g_flag[32 + m_blk]);
      }
      TS(3, 9);
    }
    {
      uint32_t res[20];
#pragma unroll
      for (int j = 0; j < 10; j++) {
        res[2 * j] = *reinterpret_cast<const uint32_t*>(g_h + (size_t)row0 * DM + n0 + j * 8 + c4 * 2);
        res[2 * j + 1] = *reinterpret_cast<const uint32_t*>(g_h + (size_t)(row0 + 8) * DM + n0 + j * 8 + c4 * 2);
      }
      float acc0[32], acc1[8];
#pragma unroll
      for (int i = 0; i < 32; i++) acc0[i] = 0.f;
#pragma unroll
      for (int i = 0; i < 8; i++) acc1[i] = 0.f;
      mbar_wait(bar3, 0);
      TS(4, 3);
      if (wg == 0) res_mainloop<24, KC_NST3, 0>(acc0, acc1, sbase, bar3, leader);
      else res_mainloop<24, KC_NST3, 1>(acc0, acc1, sbase, bar3, leader);
      wgmma_wait<0>();
      fence_regs(acc0); fence_regs(acc1);
      TS(4, 4);
#pragma unroll
      for (int j = 0; j < 10; j++) {
        const uint32_t a01 = j < 8 ? pack_bf16(acc0[4 * j], acc0[4 * j + 1]) : pack_bf16(acc1[4 * (j - 8)], acc1[4 * (j - 8) + 1]);
        const uint32_t a23 = j < 8 ? pack_bf16(acc0[4 * j + 2], acc0[4 * j + 3]) : pack_bf16(acc1[4 * (j - 8) + 2], acc1[4 * (j - 8) + 3]);
        st_shared_b32(stg80 + j * 16, pack_bf16(bf_lo(res[2 * j]) + bf_lo(a01), bf_hi(res[2 * j]) + bf_hi(a01)));
        st_shared_b32(stg80 + 8 * 160 + j * 16, pack_bf16(bf_lo(res[2 * j + 1]) + bf_lo(a23), bf_hi(res[2 * j + 1]) + bf_hi(a23)));
      }
      fence_proxy_async();
      named_bar_sync(1 + wg, 128);
      if (leader) {
        tma_store_2d(&tmOut, stg80_base, n0, m_blk * 128 + wg * 64);
        bulk_commit();
        bulk_wait_read();
      }
      TS(4, 5);
    }
  }
  __syncwarp();
  cluster_sync_relaxed();
  TS(4, 6);
}

constexpr int AT_THREADS = 512;
constexpr int AT_WGS = AT_THREADS / 128;
#define AT_CHUNK_MASK 3
#define AT_STAGGER 0
constexpr int AT_KV_BYTES = IMG_HEAD_ELEMS * 2;
constexpr int AT_SMEM = 2 * AT_KV_BYTES + 256 + 1024;
constexpr int AT_CHUNKS = 8;

__device__ __forceinline__ float exp2_poly(float x) {
  const float u = __saturatef(fmaf(x, 1.0f / 64.0f, 62.0f / 64.0f));
  const float MAGIC = 12582912.0f - 62.0f;
  const float r = fmaf(u, 64.0f, MAGIC);
  const float q = MAGIC - r;
  const float fr = fmaf(u, 64.0f, q);
  float p = fmaf(fr, 0.009570102207362652f, 0.05591785907745361f);
  p = fmaf(p, fr, 0.240247443318367f);
  p = fmaf(p, fr, 0.6931217908859253f);
  p = fmaf(p, fr, 0.9999992847442627f);
  return __uint_as_float(__float_as_uint(p) + (__float_as_uint(r) << 23));
}
#define AT_VARIANT 0
#define AT_POLY_MOD 8
__device__ __forceinline__ bool use_poly(int e) {
  return (e % AT_POLY_MOD) == 1;
}

struct AttnState {
  uint32_t qa0, qa1, qa2, qa3, qa4, qa5;
  float M0, M1;
};

__device__ __forceinline__ bool attn_exp_fast(const float (&s)[32], uint32_t (&p)[16]) {
#pragma unroll
  for (int j = 0; j < 16; j++) {
    const float e0 = use_poly(2 * j) ? exp2_poly(s[2 * j]) : ex2(s[2 * j]);
    const float e1 = use_poly(2 * j + 1) ? exp2_poly(s[2 * j + 1]) : ex2(s[2 * j + 1]);
    p[j] = pack_bf16(e0, e1);
  }
  uint32_t acc_or = 0;
#pragma unroll
  for (int j = 0; j < 16; j++) acc_or |= p[j];
  return __any_sync(0xffffffffu, (acc_or & 0x40004000u) != 0);
}
__device__ __forceinline__ void attn_exp_exact(const float (&s)[32], uint32_t (&p)[16], float (&o)[12], AttnState& st, bool first, int c4) {
  float mx0 = fmaxf(s[0], s[1]), mx1 = fmaxf(s[2], s[3]);
#pragma unroll
  for (int j = 1; j < 8; j++) {
    mx0 = fmaxf(mx0, fmaxf(s[4 * j], s[4 * j + 1]));
    mx1 = fmaxf(mx1, fmaxf(s[4 * j + 2], s[4 * j + 3]));
  }
  mx0 = fmaxf(mx0, __shfl_xor_sync(0xffffffffu, mx0, 1));
  mx1 = fmaxf(mx1, __shfl_xor_sync(0xffffffffu, mx1, 1));
  mx0 = fmaxf(mx0, __shfl_xor_sync(0xffffffffu, mx0, 2));
  mx1 = fmaxf(mx1, __shfl_xor_sync(0xffffffffu, mx1, 2));
  float d0 = mx0 + 7.0f, d1 = mx1 + 7.0f;
  if (!first) { d0 = fmaxf(d0, 0.f); d1 = fmaxf(d1, 0.f); }
  const float T0 = st.M0 + d0, T1 = st.M1 + d1;
  const float h0 = bf16_round(T0), h1 = bf16_round(T1);
  const float i0 = bf16_round(T0 - h0), i1 = bf16_round(T1 - h1);
  const float l0 = bf16_round((T0 - h0) - i0), l1 = bf16_round((T1 - h1) - i1);
  const float N0 = (h0 + i0) + l0, N1 = (h1 + i1) + l1;
  d0 = N0 - st.M0; d1 = N1 - st.M1;
  st.M0 = N0; st.M1 = N1;
  if (c4 == 2) { st.qa4 = pack_bf16(-h0, -i0); st.qa5 = pack_bf16(-h1, -i1); }
  if (c4 == 3) { st.qa4 = pack_bf16(-l0, 0.f); st.qa5 = pack_bf16(-l1, 0.f); }
  if (!first) {
    const float al0 = ex2(-d0), al1 = ex2(-d1);
#pragma unroll
    for (int j = 0; j < 3; j++) {
      o[4 * j] *= al0; o[4 * j + 1] *= al0;
      o[4 * j + 2] *= al1; o[4 * j + 3] *= al1;
    }
  }
#pragma unroll
  for (int j = 0; j < 8; j++) {
    p[2 * j] = pack_bf16(ex2(s[4 * j] - d0), ex2(s[4 * j + 1] - d0));
    p[2 * j + 1] = pack_bf16(ex2(s[4 * j + 2] - d1), ex2(s[4 * j + 3] - d1));
  }
}
__device__ __forceinline__ void attn_step(float (&s)[32], const uint32_t (&pp)[16], uint32_t (&pn)[16], float (&o)[12], AttnState& st,
                                          uint32_t k_addr, uint32_t v_addr_prev, int keep, int c4, int wgdbg = 0, int tdbg = 0) {
  PH(wgdbg, tdbg, 0);
  const uint64_t dk = make_desc(k_addr, 128, 384, 0);
  const uint64_t dv_prev = make_desc(v_addr_prev, 384, 128, 0);
  wgmma_fence();
  wgmma_rs_n64(s, st.qa0, st.qa1, st.qa2, st.qa3, dk, 0);
  wgmma_rs_n64(s, st.qa4, st.qa5, 0u, 0u, dk + 16, 1);
  wgmma_commit();
#pragma unroll
  for (int kk = 0; kk < 4; kk++) wgmma_rs_n24_tb(o, pp[4 * kk], pp[4 * kk + 1], pp[4 * kk + 2], pp[4 * kk + 3], dv_prev + kk * 48, kk == 0 ? keep : 1);
  wgmma_commit();
  wgmma_wait<1>();
  fence_regs(s);
  PH(wgdbg, tdbg, 1);
  const bool redo = attn_exp_fast(s, pn);
  PH(wgdbg, tdbg, 2);
  wgmma_wait<0>();
  fence_regs(o);
  if (redo) attn_exp_exact(s, pn, o, st, false, c4);
}

__global__ void __launch_bounds__(AT_THREADS, 1) attn_kernel(const bf16* __restrict__ wo, const bf16* __restrict__ wgt, const bf16* __restrict__ wup, const bf16* __restrict__ wdn) {
  extern __shared__ uint8_t smem_raw[];
  const uint32_t sbase = (smem_u32(smem_raw) + 1023u) & ~1023u;
  const uint32_t sK = sbase, sV = sbase + AT_KV_BYTES;
  const uint32_t sBar = sV + AT_KV_BYTES;
  const int tid = threadIdx.x, warp = tid >> 5, lane = tid & 31;
  const int head = blockIdx.x >> 2, quarter = blockIdx.x & 3;
  if (blockIdx.x >= 128) {
    pdl_launch();
    const int b = blockIdx.x - 128;
    const bf16* w = (b >> 1) ? wup : wgt;
    const int cgrp = tid % 96, rgrp = tid / 96;
    float acc[8];
#pragma unroll
    for (int i = 0; i < 8; i++) acc[i] = 0.f;
    float* red = reinterpret_cast<float*>(smem_raw);
    if (rgrp < 5) {
      const uint4* src = reinterpret_cast<const uint4*>(w + (size_t)(rgrp * 128) * FF + (b & 1) * 768 + cgrp * 8);
#pragma unroll 8
      for (int r = 0; r < 128; r++) {
        const uint4 v = __ldg(src + (size_t)r * (FF / 8));
        acc[0] += bf_lo(v.x); acc[1] += bf_hi(v.x); acc[2] += bf_lo(v.y); acc[3] += bf_hi(v.y);
        acc[4] += bf_lo(v.z); acc[5] += bf_hi(v.z); acc[6] += bf_lo(v.w); acc[7] += bf_hi(v.w);
      }
#pragma unroll
      for (int i = 0; i < 8; i++) red[rgrp * 768 + cgrp * 8 + i] = acc[i];
    }
    __syncthreads();
    pdl_wait();
    for (int c = tid; c < 768; c += AT_THREADS)
      g_cs[(b >> 1) * FF + (b & 1) * 768 + c] = ((red[c] + red[768 + c]) + (red[1536 + c] + red[2304 + c])) + red[3072 + c];
    if (b == 0 && tid < 16) g_flag[tid] = 0;
    return;
  }
  TS(1, 0);
  if (tid == 0) {
    for (int i = 0; i < AT_CHUNKS; i++) mbar_init(sBar + 8 * i, 1);
    fence_mbar_init();
  }
  pdl_launch();
  if (tid == 32) {
    prefetch_l2(reinterpret_cast<const uint8_t*>(wo) + blockIdx.x * 6400, 6400);
    prefetch_l2(reinterpret_cast<const uint8_t*>(wgt) + blockIdx.x * 15360, 15360);
    prefetch_l2(reinterpret_cast<const uint8_t*>(wup) + blockIdx.x * 15360, 15360);
    prefetch_l2(reinterpret_cast<const uint8_t*>(wdn) + blockIdx.x * 15360, 15360);
  }
  __syncthreads();
  TS(1, 1);
  pdl_wait();
  TS(1, 2);
  if (tid == 0) {
    const uint8_t* kg = reinterpret_cast<const uint8_t*>(g_img + (size_t)(32 + head) * IMG_HEAD_ELEMS);
    const uint8_t* vg = reinterpret_cast<const uint8_t*>(g_img + (size_t)(64 + head) * IMG_HEAD_ELEMS);
    constexpr int CB = AT_KV_BYTES / AT_CHUNKS;
    for (int i = 0; i < AT_CHUNKS; i++) {
      mbar_expect_tx(sBar + 8 * i, 2 * CB);
      bulk_g2s(sK + i * CB, kg + i * CB, CB, sBar + 8 * i);
      bulk_g2s(sV + i * CB, vg + i * CB, CB, sBar + 8 * i);
    }
  }
  const int wg = warp >> 2, wwarp = warp & 3;
  const int g = lane >> 2, c4 = lane & 3;
  const uint64_t dk_base = make_desc(sK, 128, 384, 0);
  const uint64_t dv_base = make_desc(sV, 384, 128, 0);

#pragma unroll 1
  for (int rep = 0; rep < 8 / AT_WGS; rep++) {
    const int row0 = quarter * 512 + (rep * AT_WGS + wg) * 64 + wwarp * 16 + g;
    AttnState st;
    {
      const bf16* q0 = g_img + (size_t)head * IMG_HEAD_ELEMS + (size_t)(row0 >> 3) * 192 + g * 8 + c4 * 2;
      const bf16* q1 = q0 + 192;
      st.qa0 = *reinterpret_cast<const uint32_t*>(q0);
      st.qa1 = *reinterpret_cast<const uint32_t*>(q1);
      st.qa2 = *reinterpret_cast<const uint32_t*>(q0 + 64);
      st.qa3 = *reinterpret_cast<const uint32_t*>(q1 + 64);
      st.qa4 = *reinterpret_cast<const uint32_t*>(q0 + 128);
      st.qa5 = *reinterpret_cast<const uint32_t*>(q1 + 128);
    }
    float o[12];
    float s[32];
    uint32_t pa[16], pb[16];
    st.M0 = st.M1 = 0.f;
    if (rep == 0) mbar_wait(sBar, 0);
    wgmma_fence();
    wgmma_rs_n64(s, st.qa0, st.qa1, st.qa2, st.qa3, dk_base, 0);
    wgmma_rs_n64(s, st.qa4, st.qa5, 0u, 0u, dk_base + 16, 1);
    wgmma_commit();
    wgmma_wait<0>();
    fence_regs(s);
    attn_exp_exact(s, pa, o, st, true, c4);
    attn_step(s, pa, pb, o, st, sK + 3072, sV, 0, c4);
#pragma unroll 1
    for (int tt = 1; tt < 16; tt++) {
      if (rep == 0 && !(tt & 1)) mbar_wait(sBar + 8 * (tt >> 1), 0);
      attn_step(s, pb, pa, o, st, sK + tt * 6144, sV + tt * 6144 - 3072, 1, c4, wg, rep * 32 + tt * 2);
      attn_step(s, pa, pb, o, st, sK + tt * 6144 + 3072, sV + tt * 6144, 1, c4, wg, rep * 32 + tt * 2 + 1);
    }
    wgmma_fence();
#pragma unroll
    for (int kk = 0; kk < 4; kk++) wgmma_rs_n24_tb(o, pb[4 * kk], pb[4 * kk + 1], pb[4 * kk + 2], pb[4 * kk + 3], dv_base + 31 * 192 + kk * 48, 1);
    wgmma_commit();
    wgmma_wait<0>();
    fence_regs(o);
    TS(1, 3 + rep);
    const float l0 = __shfl_sync(0xffffffffu, o[8], (lane & ~3) | 2);
    const float l1 = __shfl_sync(0xffffffffu, o[10], (lane & ~3) | 2);
    const float i0 = 1.0f / l0, i1 = 1.0f / l1;
    bf16* o0 = g_o + (size_t)row0 * DM + head * DH;
    bf16* o1 = o0 + 8 * DM;
#pragma unroll
    for (int j = 0; j < 3; j++) {
      if (j < 2 || c4 < 2) {
        *reinterpret_cast<uint32_t*>(o0 + j * 8 + c4 * 2) = pack_bf16(o[4 * j] * i0, o[4 * j + 1] * i0);
        *reinterpret_cast<uint32_t*>(o1 + j * 8 + c4 * 2) = pack_bf16(o[4 * j + 2] * i1, o[4 * j + 3] * i1);
      }
    }
  }
}

typedef CUresult (*EncodeTiledFn)(CUtensorMap*, CUtensorMapDataType, cuuint32_t, void*, const cuuint64_t*, const cuuint64_t*,
                                  const cuuint32_t*, const cuuint32_t*, CUtensorMapInterleave, CUtensorMapSwizzle,
                                  CUtensorMapL2promotion, CUtensorMapFloatOOBfill);

static void make_map(EncodeTiledFn fn, CUtensorMap* tm, const void* ptr, uint64_t rows, uint64_t cols, uint32_t box_rows,
                     uint32_t box_cols, CUtensorMapSwizzle sw) {
  cuuint64_t dims[2] = {cols, rows};
  cuuint64_t strides[1] = {cols * 2};
  cuuint32_t box[2] = {box_cols, box_rows};
  cuuint32_t es[2] = {1, 1};
  fn(tm, CU_TENSOR_MAP_DATA_TYPE_BFLOAT16, 2, const_cast<void*>(ptr), dims, strides, box, es, CU_TENSOR_MAP_INTERLEAVE_NONE, sw,
     CU_TENSOR_MAP_L2_PROMOTION_L2_256B, CU_TENSOR_MAP_FLOAT_OOB_FILL_NONE);
}

template <typename... KArgs, typename... Args>
static void launch(void (*kern)(KArgs...), int grid, int block, int smem, int cluster, bool pdl, Args... args) {
  cudaLaunchConfig_t cfg = {};
  cfg.gridDim = dim3(grid);
  cfg.blockDim = dim3(block);
  cfg.dynamicSmemBytes = smem;
  cfg.stream = cudaStreamPerThread;
  cudaLaunchAttribute at[2];
  int n = 0;
  if (cluster > 1) {
    at[n].id = cudaLaunchAttributeClusterDimension;
    at[n].val.clusterDim.x = cluster; at[n].val.clusterDim.y = 1; at[n].val.clusterDim.z = 1;
    n++;
  }
  if (pdl) {
    at[n].id = cudaLaunchAttributeProgrammaticStreamSerialization;
    at[n].val.programmaticStreamSerializationAllowed = 1;
    n++;
  }
  cfg.attrs = at;
  cfg.numAttrs = n;
  cudaLaunchKernelEx(&cfg, kern, KArgs(args)...);
}

extern "C" void kernel_launch(void* const* d_in, const int* in_sizes, int n_in, void* d_out, int out_size) {
  const bf16* x = (const bf16*)d_in[0];
  const bf16* wqkv = (const bf16*)d_in[1];
  const bf16* wo = (const bf16*)d_in[2];
  const bf16* wg = (const bf16*)d_in[4];
  const bf16* wu = (const bf16*)d_in[5];
  const bf16* wd = (const bf16*)d_in[6];
  bf16* out = (bf16*)d_out;

  static EncodeTiledFn enc = nullptr;
  static void *p_o = nullptr, *p_h = nullptr, *p_hh = nullptr;
  if (!enc) {
    void* fn = nullptr;
    cudaDriverEntryPointQueryResult qr;
    cudaGetDriverEntryPoint("cuTensorMapEncodeTiled", &fn, cudaEnableDefault, &qr);
    enc = (EncodeTiledFn)fn;
    cudaGetSymbolAddress(&p_o, g_o);
    cudaGetSymbolAddress(&p_h, g_h);
    cudaGetSymbolAddress(&p_hh, g_hh);
    cudaFuncSetAttribute(qkv_kernel, cudaFuncAttributeMaxDynamicSharedMemorySize, KA_SMEM);
    cudaFuncSetAttribute(mlp_kernel, cudaFuncAttributeMaxDynamicSharedMemorySize, KC_SMEM);
    cudaFuncSetAttribute(attn_kernel, cudaFuncAttributeMaxDynamicSharedMemorySize, AT_SMEM);
  }
  CUtensorMap tm_wqkv, tm_wg, tm_wu, tm_wo64, tm_wo16, tm_wd64, tm_wd16, tm_o, tm_h, tm_hh, tm_hhs, tm_xn, tm_hs, tm_out;
  make_map(enc, &tm_wqkv, wqkv, DM, 3 * DM, 32, 64, CU_TENSOR_MAP_SWIZZLE_128B);
  make_map(enc, &tm_wg, wg, DM, FF, 32, 64, CU_TENSOR_MAP_SWIZZLE_128B);
  make_map(enc, &tm_wu, wu, DM, FF, 32, 64, CU_TENSOR_MAP_SWIZZLE_128B);
  make_map(enc, &tm_wo64, wo, DM, DM, 32, 64, CU_TENSOR_MAP_SWIZZLE_128B);
  make_map(enc, &tm_wo16, wo, DM, DM, 32, 16, CU_TENSOR_MAP_SWIZZLE_32B);
  make_map(enc, &tm_wd64, wd, FF, DM, 32, 64, CU_TENSOR_MAP_SWIZZLE_128B);
  make_map(enc, &tm_wd16, wd, FF, DM, 32, 16, CU_TENSOR_MAP_SWIZZLE_32B);
  make_map(enc, &tm_o, p_o, SEQ, DM, 128, 64, CU_TENSOR_MAP_SWIZZLE_128B);
  make_map(enc, &tm_h, p_h, SEQ, DM, 128, 32, CU_TENSOR_MAP_SWIZZLE_64B);
  make_map(enc, &tm_hh, p_hh, SEQ, FF, 128, 64, CU_TENSOR_MAP_SWIZZLE_128B);
  make_map(enc, &tm_hhs, p_hh, SEQ, FF, 64, 64, CU_TENSOR_MAP_SWIZZLE_128B);
  make_map(enc, &tm_xn, x, SEQ, DM, 128, 32, CU_TENSOR_MAP_SWIZZLE_64B);
  make_map(enc, &tm_hs, p_h, SEQ, DM, 64, 80, CU_TENSOR_MAP_SWIZZLE_NONE);
  make_map(enc, &tm_out, out, SEQ, DM, 64, 80, CU_TENSOR_MAP_SWIZZLE_NONE);

  launch(qkv_kernel, 128, GT, KA_SMEM, 2, false, tm_xn, tm_wqkv, x, wqkv);
  launch(attn_kernel, 132, AT_THREADS, AT_SMEM, 1, true, wo, wg, wu, wd);
  launch(mlp_kernel, 128, GT, KC_SMEM, 2, true, tm_o, tm_wo64, tm_wo16, tm_h, tm_wg, tm_wu, tm_hhs, tm_hh, tm_wd64, tm_wd16, tm_hs, tm_out, x);
}
```

```cpp
#include <cuda_runtime.h>
#include <cuda_bf16.h>
#include <cuda.h>
#include <stdint.h>

typedef __nv_bfloat16 bf16;
#define FLAGV 0

constexpr int SEQ = 2048, DM = 640, NH = 32, DH = 20, FF = 1536;
constexpr float ATT_SCALE_LOG2E = 0.22360679774997896f * 1.4426950408889634f;
constexpr int IMG_HEAD_ELEMS = (SEQ / 8) * 192;

__device__ __align__(1024) bf16 g_img[3 * NH * IMG_HEAD_ELEMS];
__device__ __align__(1024) bf16 g_o[SEQ * DM];
__device__ __align__(1024) bf16 g_h[SEQ * DM];
__device__ __align__(1024) bf16 g_xn[SEQ * DM];
__device__ float2 g_stats[SEQ * 8];
__device__ float g_cs[2 * FF];
__device__ int g_flag[3 * 16];
__device__ __align__(1024) bf16 g_hh[SEQ * FF];

#define TS(k, i)
#define PH(w, t, i)
__device__ __forceinline__ uint32_t smem_u32(const void* p) { return (uint32_t)__cvta_generic_to_shared(p); }
__device__ __forceinline__ void mbar_init(uint32_t bar, uint32_t cnt) {
  asm volatile("mbarrier.init.shared::cta.b64 [%0], %1;" ::"r"(bar), "r"(cnt) : "memory");
}
__device__ __forceinline__ void mbar_expect_tx(uint32_t bar, uint32_t bytes) {
  asm volatile("mbarrier.arrive.expect_tx.shared::cta.b64 _, [%0], %1;" ::"r"(bar), "r"(bytes) : "memory");
}
__device__ __forceinline__ void mbar_arrive(uint32_t bar) {
  asm volatile("mbarrier.arrive.shared::cta.b64 _, [%0];" ::"r"(bar) : "memory");
}
__device__ __forceinline__ void mbar_arrive_cluster(uint32_t bar, uint32_t cta) {
  asm volatile(
      "{\n.reg .b32 r;\nmapa.shared::cluster.u32 r, %0, %1;\n"
      "mbarrier.arrive.shared::cluster.b64 _, [r];\n}\n" ::"r"(bar), "r"(cta)
      : "memory");
}
__device__ __forceinline__ void mbar_wait(uint32_t bar, uint32_t parity) {
  asm volatile(
      "{\n.reg .pred p;\nLAB_WAIT:\n"
      "mbarrier.try_wait.parity.shared::cta.b64 p, [%0], %1;\n"
      "@p bra DONE;\nbra LAB_WAIT;\nDONE:\n}\n" ::"r"(bar), "r"(parity)
      : "memory");
}
__device__ __forceinline__ void mbar_wait_cluster(uint32_t bar, uint32_t parity) {
  asm volatile(
      "{\n.reg .pred p;\nLAB_WAIT:\n"
      "mbarrier.try_wait.parity.acquire.cluster.shared::cta.b64 p, [%0], %1;\n"
      "@p bra DONE;\nbra LAB_WAIT;\nDONE:\n}\n" ::"r"(bar), "r"(parity)
      : "memory");
}
__device__ __forceinline__ void fence_mbar_init() { asm volatile("fence.mbarrier_init.release.cluster;" ::: "memory"); }
__device__ __forceinline__ void fence_proxy_async() { asm volatile("fence.proxy.async.shared::cta;" ::: "memory"); }
__device__ __forceinline__ void cluster_sync_all() {
  asm volatile("barrier.cluster.arrive.release.aligned;\nbarrier.cluster.wait.acquire.aligned;" ::: "memory");
}
__device__ __forceinline__ void cluster_sync_relaxed() {
  asm volatile("barrier.cluster.arrive.relaxed.aligned;\nbarrier.cluster.wait.aligned;" ::: "memory");
}
__device__ __forceinline__ void named_bar_sync(int id, int n) { asm volatile("bar.sync %0, %1;" ::"r"(id), "r"(n) : "memory"); }
__device__ __forceinline__ bool wg_any(bool pred, int id) {
  uint32_t r;
  asm volatile("{\n.reg .pred p, q;\nsetp.ne.u32 p, %1, 0;\nbar.red.or.pred q, %2, 128, p;\nselp.u32 %0, 1, 0, q;\n}\n" : "=r"(r) : "r"((uint32_t)pred), "r"(id) : "memory");
  return r != 0;
}
__device__ __forceinline__ void fence_proxy_async_all() { asm volatile("fence.proxy.async;" ::: "memory"); }
__device__ __forceinline__ void flag_signal(int* f) {
  __threadfence();
  atomicAdd(f, 1);
}
__device__ __forceinline__ void flag_wait(const int* f, int target) {
  int v;
  unsigned spins = 0;
  do {
    asm volatile("ld.acquire.gpu.global.s32 %0, [%1];" : "=r"(v) : "l"(f) : "memory");
    if (++spins > (1u << 24)) __trap();
  } while (v < target);
}
__device__ __forceinline__ void pdl_launch() { asm volatile("griddepcontrol.launch_dependents;" ::: "memory"); }
__device__ __forceinline__ void pdl_wait() { asm volatile("griddepcontrol.wait;" ::: "memory"); }

__device__ __forceinline__ void tma_load_2d(uint32_t dst, const CUtensorMap* tm, int c0, int c1, uint32_t bar) {
  asm volatile(
      "cp.async.bulk.tensor.2d.shared::cluster.global.mbarrier::complete_tx::bytes [%0], [%1, {%3, %4}], [%2];" ::"r"(dst),
      "l"((uint64_t)tm), "r"(bar), "r"(c0), "r"(c1)
      : "memory");
}
__device__ __forceinline__ void tma_load_2d_mc(uint32_t dst, const CUtensorMap* tm, int c0, int c1, uint32_t bar, uint16_t mask) {
  asm volatile(
      "cp.async.bulk.tensor.2d.shared::cluster.global.mbarrier::complete_tx::bytes.multicast::cluster [%0], [%1, {%3, %4}], [%2], %5;" ::"r"(dst),
      "l"((uint64_t)tm), "r"(bar), "r"(c0), "r"(c1), "h"(mask)
      : "memory");
}
__device__ __forceinline__ void bulk_g2s(uint32_t dst, const void* src, uint32_t bytes, uint32_t bar) {
  asm volatile("cp.async.bulk.shared::cluster.global.mbarrier::complete_tx::bytes [%0], [%1], %2, [%3];" ::"r"(dst), "l"(src),
               "r"(bytes), "r"(bar)
               : "memory");
}
__device__ __forceinline__ void bulk_s2g(void* dst, uint32_t src, uint32_t bytes) {
  asm volatile("cp.async.bulk.global.shared::cta.bulk_group [%0], [%1], %2;" ::"l"(dst), "r"(src), "r"(bytes) : "memory");
}
__device__ __forceinline__ void tma_store_2d(const CUtensorMap* tm, uint32_t src, int c0, int c1) {
  asm volatile("cp.async.bulk.tensor.2d.global.shared::cta.bulk_group [%0, {%2, %3}], [%1];" ::"l"((uint64_t)tm), "r"(src), "r"(c0), "r"(c1) : "memory");
}
__device__ __forceinline__ void bulk_commit() { asm volatile("cp.async.bulk.commit_group;" ::: "memory"); }
__device__ __forceinline__ void bulk_wait_read() { asm volatile("cp.async.bulk.wait_group.read 0;" ::: "memory"); }
__device__ __forceinline__ void prefetch_l2(const void* p, uint32_t bytes) {
  asm volatile("cp.async.bulk.prefetch.L2.global [%0], %1;" ::"l"(p), "r"(bytes) : "memory");
}
__device__ __forceinline__ void bulk_wait_all() { asm volatile("cp.async.bulk.wait_group 0;" ::: "memory"); }
__device__ __forceinline__ void st_shared_b32(uint32_t addr, uint32_t v) { asm volatile("st.shared.b32 [%0], %1;" ::"r"(addr), "r"(v) : "memory"); }
__device__ __forceinline__ void st_shared_v2(uint32_t addr, uint32_t a, uint32_t b) { asm volatile("st.shared.v2.b32 [%0], {%1, %2};" ::"r"(addr), "r"(a), "r"(b) : "memory"); }
__device__ __forceinline__ void prefetch_tmap(const CUtensorMap* tm) {
  asm volatile("prefetch.tensormap [%0];" ::"l"((uint64_t)tm) : "memory");
}
__device__ __forceinline__ void wgmma_fence() { asm volatile("wgmma.fence.sync.aligned;" ::: "memory"); }
__device__ __forceinline__ void wgmma_commit() { asm volatile("wgmma.commit_group.sync.aligned;" ::: "memory"); }
template <int N>
__device__ __forceinline__ void wgmma_wait() { asm volatile("wgmma.wait_group.sync.aligned %0;" ::"n"(N) : "memory"); }

template <int N>
__device__ __forceinline__ void fence_regs(float (&r)[N]) {
#pragma unroll
  for (int i = 0; i < N; i++) asm volatile("" : "+f"(r[i])::"memory");
}
template <int N>
__device__ __forceinline__ void fence_regs(uint32_t (&r)[N]) {
#pragma unroll
  for (int i = 0; i < N; i++) asm volatile("" : "+r"(r[i])::"memory");
}
__device__ __forceinline__ uint64_t make_desc(uint32_t addr, uint32_t lbo, uint32_t sbo, uint32_t layout) {
  return (uint64_t)((addr & 0x3FFFF) >> 4) | ((uint64_t)((lbo & 0x3FFFF) >> 4) << 16) | ((uint64_t)((sbo & 0x3FFFF) >> 4) << 32) |
         ((uint64_t)layout << 62);
}
__device__ __forceinline__ uint32_t pack_bf16(float lo, float hi) {
  uint32_t r;
  asm("cvt.rn.bf16x2.f32 %0, %1, %2;" : "=r"(r) : "f"(hi), "f"(lo));
  return r;
}
__device__ __forceinline__ float bf16_round(float x) { return __bfloat162float(__float2bfloat16_rn(x)); }
__device__ __forceinline__ float bf_lo(uint32_t u) { return __uint_as_float(u << 16); }
__device__ __forceinline__ float bf_hi(uint32_t u) { return __uint_as_float(u & 0xffff0000u); }
__device__ __forceinline__ float ex2(float x) {
  float y;
  asm("ex2.approx.ftz.f32 %0, %1;" : "=f"(y) : "f"(x));
  return y;
}

__device__ __forceinline__ void wgmma_ss_n240_tb(float (&d)[120], uint64_t descA, uint64_t descB, int scaleD) {
  asm volatile("{\n.reg .pred p;\nsetp.ne.b32 p, %122, 0;\n"
    "wgmma.mma_async.sync.aligned.m64n240k16.f32.bf16.bf16 {%0, %1, %2, %3, %4, %5, %6, %7, %8, %9, %10, %11, %12, %13, %14, %15, %16, %17, %18, %19, %20, %21, %22, %23, %24, %25, %26, %27, %28, %29, %30, %31, %32, %33, %34, %35, %36, %37, %38, %39, %40, %41, %42, %43, %44, %45, %46, %47, %48, %49, %50, %51, %52, %53, %54, %55, %56, %57, %58, %59, %60, %61, %62, %63, %64, %65, %66, %67, %68, %69, %70, %71, %72, %73, %74, %75, %76, %77, %78, %79, %80, %81, %82, %83, %84, %85, %86, %87, %88, %89, %90, %91, %92, %93, %94, %95, %96, %97, %98, %99, %100, %101, %102, %103, %104, %105, %106, %107, %108, %109, %110, %111, %112, %113, %114, %115, %116, %117, %118, %119}, %120, %121, p, 1, 1, 0, 1;\n}\n"
    : "+f"(d[0]), "+f"(d[1]), "+f"(d[2]), "+f"(d[3]), "+f"(d[4]), "+f"(d[5]), "+f"(d[6]), "+f"(d[7]), "+f"(d[8]), "+f"(d[9]), "+f"(d[10]), "+f"(d[11]), "+f"(d[12]), "+f"(d[13]), "+f"(d[14]), "+f"(d[15]), "+f"(d[16]), "+f"(d[17]), "+f"(d[18]), "+f"(d[19]), "+f"(d[20]), "+f"(d[21]), "+f"(d[22]), "+f"(d[23]), "+f"(d[24]), "+f"(d[25]), "+f"(d[26]), "+f"(d[27]), "+f"(d[28]), "+f"(d[29]), "+f"(d[30]), "+f"(d[31]), "+f"(d[32]), "+f"(d[33]), "+f"(d[34]), "+f"(d[35]), "+f"(d[36]), "+f"(d[37]), "+f"(d[38]), "+f"(d[39]), "+f"(d[40]), "+f"(d[41]), "+f"(d[42]), "+f"(d[43]), "+f"(d[44]), "+f"(d[45]), "+f"(d[46]), "+f"(d[47]), "+f"(d[48]), "+f"(d[49]), "+f"(d[50]), "+f"(d[51]), "+f"(d[52]), "+f"(d[53]), "+f"(d[54]), "+f"(d[55]), "+f"(d[56]), "+f"(d[57]), "+f"(d[58]), "+f"(d[59]), "+f"(d[60]), "+f"(d[61]), "+f"(d[62]), "+f"(d[63]), "+f"(d[64]), "+f"(d[65]), "+f"(d[66]), "+f"(d[67]), "+f"(d[68]), "+f"(d[69]), "+f"(d[70]), "+f"(d[71]), "+f"(d[72]), "+f"(d[73]), "+f"(d[74]), "+f"(d[75]), "+f"(d[76]), "+f"(d[77]), "+f"(d[78]), "+f"(d[79]), "+f"(d[80]), "+f"(d[81]), "+f"(d[82]), "+f"(d[83]), "+f"(d[84]), "+f"(d[85]), "+f"(d[86]), "+f"(d[87]), "+f"(d[88]), "+f"(d[89]), "+f"(d[90]), "+f"(d[91]), "+f"(d[92]), "+f"(d[93]), "+f"(d[94]), "+f"(d[95]), "+f"(d[96]), "+f"(d[97]), "+f"(d[98]), "+f"(d[99]), "+f"(d[100]), "+f"(d[101]), "+f"(d[102]), "+f"(d[103]), "+f"(d[104]), "+f"(d[105]), "+f"(d[106]), "+f"(d[107]), "+f"(d[108]), "+f"(d[109]), "+f"(d[110]), "+f"(d[111]), "+f"(d[112]), "+f"(d[113]), "+f"(d[114]), "+f"(d[115]), "+f"(d[116]), "+f"(d[117]), "+f"(d[118]), "+f"(d[119])
    : "l"(descA), "l"(descB), "r"(scaleD));
}
__device__ __forceinline__ void wgmma_ss_n192_tb(float (&d)[96], uint64_t descA, uint64_t descB, int scaleD) {
  asm volatile("{\n.reg .pred p;\nsetp.ne.b32 p, %98, 0;\n"
    "wgmma.mma_async.sync.aligned.m64n192k16.f32.bf16.bf16 {%0, %1, %2, %3, %4, %5, %6, %7, %8, %9, %10, %11, %12, %13, %14, %15, %16, %17, %18, %19, %20, %21, %22, %23, %24, %25, %26, %27, %28, %29, %30, %31, %32, %33, %34, %35, %36, %37, %38, %39, %40, %41, %42, %43, %44, %45, %46, %47, %48, %49, %50, %51, %52, %53, %54, %55, %56, %57, %58, %59, %60, %61, %62, %63, %64, %65, %66, %67, %68, %69, %70, %71, %72, %73, %74, %75, %76, %77, %78, %79, %80, %81, %82, %83, %84, %85, %86, %87, %88, %89, %90, %91, %92, %93, %94, %95}, %96, %97, p, 1, 1, 0, 1;\n}\n"
    : "+f"(d[0]), "+f"(d[1]), "+f"(d[2]), "+f"(d[3]), "+f"(d[4]), "+f"(d[5]), "+f"(d[6]), "+f"(d[7]), "+f"(d[8]), "+f"(d[9]), "+f"(d[10]), "+f"(d[11]), "+f"(d[12]), "+f"(d[13]), "+f"(d[14]), "+f"(d[15]), "+f"(d[16]), "+f"(d[17]), "+f"(d[18]), "+f"(d[19]), "+f"(d[20]), "+f"(d[21]), "+f"(d[22]), "+f"(d[23]), "+f"(d[24]), "+f"(d[25]), "+f"(d[26]), "+f"(d[27]), "+f"(d[28]), "+f"(d[29]), "+f"(d[30]), "+f"(d[31]), "+f"(d[32]), "+f"(d[33]), "+f"(d[34]), "+f"(d[35]), "+f"(d[36]), "+f"(d[37]), "+f"(d[38]), "+f"(d[39]), "+f"(d[40]), "+f"(d[41]), "+f"(d[42]), "+f"(d[43]), "+f"(d[44]), "+f"(d[45]), "+f"(d[46]), "+f"(d[47]), "+f"(d[48]), "+f"(d[49]), "+f"(d[50]), "+f"(d[51]), "+f"(d[52]), "+f"(d[53]), "+f"(d[54]), "+f"(d[55]), "+f"(d[56]), "+f"(d[57]), "+f"(d[58]), "+f"(d[59]), "+f"(d[60]), "+f"(d[61]), "+f"(d[62]), "+f"(d[63]), "+f"(d[64]), "+f"(d[65]), "+f"(d[66]), "+f"(d[67]), "+f"(d[68]), "+f"(d[69]), "+f"(d[70]), "+f"(d[71]), "+f"(d[72]), "+f"(d[73]), "+f"(d[74]), "+f"(d[75]), "+f"(d[76]), "+f"(d[77]), "+f"(d[78]), "+f"(d[79]), "+f"(d[80]), "+f"(d[81]), "+f"(d[82]), "+f"(d[83]), "+f"(d[84]), "+f"(d[85]), "+f"(d[86]), "+f"(d[87]), "+f"(d[88]), "+f"(d[89]), "+f"(d[90]), "+f"(d[91]), "+f"(d[92]), "+f"(d[93]), "+f"(d[94]), "+f"(d[95])
    : "l"(descA), "l"(descB), "r"(scaleD));
}
__device__ __forceinline__ void wgmma_ss_n64_tb(float (&d)[32], uint64_t descA, uint64_t descB, int scaleD) {
  asm volatile("{\n.reg .pred p;\nsetp.ne.b32 p, %34, 0;\n"
    "wgmma.mma_async.sync.aligned.m64n64k16.f32.bf16.bf16 {%0, %1, %2, %3, %4, %5, %6, %7, %8, %9, %10, %11, %12, %13, %14, %15, %16, %17, %18, %19, %20, %21, %22, %23, %24, %25, %26, %27, %28, %29, %30, %31}, %32, %33, p, 1, 1, 0, 1;\n}\n"
    : "+f"(d[0]), "+f"(d[1]), "+f"(d[2]), "+f"(d[3]), "+f"(d[4]), "+f"(d[5]), "+f"(d[6]), "+f"(d[7]), "+f"(d[8]), "+f"(d[9]), "+f"(d[10]), "+f"(d[11]), "+f"(d[12]), "+f"(d[13]), "+f"(d[14]), "+f"(d[15]), "+f"(d[16]), "+f"(d[17]), "+f"(d[18]), "+f"(d[19]), "+f"(d[20]), "+f"(d[21]), "+f"(d[22]), "+f"(d[23]), "+f"(d[24]), "+f"(d[25]), "+f"(d[26]), "+f"(d[27]), "+f"(d[28]), "+f"(d[29]), "+f"(d[30]), "+f"(d[31])
    : "l"(descA), "l"(descB), "r"(scaleD));
}
__device__ __forceinline__ void wgmma_ss_n16_tb(float (&d)[8], uint64_t descA, uint64_t descB, int scaleD) {
  asm volatile("{\n.reg .pred p;\nsetp.ne.b32 p, %10, 0;\n"
    "wgmma.mma_async.sync.aligned.m64n16k16.f32.bf16.bf16 {%0, %1, %2, %3, %4, %5, %6, %7}, %8, %9, p, 1, 1, 0, 1;\n}\n"
    : "+f"(d[0]), "+f"(d[1]), "+f"(d[2]), "+f"(d[3]), "+f"(d[4]), "+f"(d[5]), "+f"(d[6]), "+f"(d[7])
    : "l"(descA), "l"(descB), "r"(scaleD));
}
__device__ __forceinline__ void wgmma_rs_n128(float (&d)[64], uint32_t a0, uint32_t a1, uint32_t a2, uint32_t a3, uint64_t descB, int scaleD) {
  asm volatile("{\n.reg .pred p;\nsetp.ne.b32 p, %69, 0;\n"
    "wgmma.mma_async.sync.aligned.m64n128k16.f32.bf16.bf16 {%0, %1, %2, %3, %4, %5, %6, %7, %8, %9, %10, %11, %12, %13, %14, %15, %16, %17, %18, %19, %20, %21, %22, %23, %24, %25, %26, %27, %28, %29, %30, %31, %32, %33, %34, %35, %36, %37, %38, %39, %40, %41, %42, %43, %44, %45, %46, %47, %48, %49, %50, %51, %52, %53, %54, %55, %56, %57, %58, %59, %60, %61, %62, %63}, {%64, %65, %66, %67}, %68, p, 1, 1, 0;\n}\n"
    : "+f"(d[0]), "+f"(d[1]), "+f"(d[2]), "+f"(d[3]), "+f"(d[4]), "+f"(d[5]), "+f"(d[6]), "+f"(d[7]), "+f"(d[8]), "+f"(d[9]), "+f"(d[10]), "+f"(d[11]), "+f"(d[12]), "+f"(d[13]), "+f"(d[14]), "+f"(d[15]), "+f"(d[16]), "+f"(d[17]), "+f"(d[18]), "+f"(d[19]), "+f"(d[20]), "+f"(d[21]), "+f"(d[22]), "+f"(d[23]), "+f"(d[24]), "+f"(d[25]), "+f"(d[26]), "+f"(d[27]), "+f"(d[28]), "+f"(d[29]), "+f"(d[30]), "+f"(d[31]), "+f"(d[32]), "+f"(d[33]), "+f"(d[34]), "+f"(d[35]), "+f"(d[36]), "+f"(d[37]), "+f"(d[38]), "+f"(d[39]), "+f"(d[40]), "+f"(d[41]), "+f"(d[42]), "+f"(d[43]), "+f"(d[44]), "+f"(d[45]), "+f"(d[46]), "+f"(d[47]), "+f"(d[48]), "+f"(d[49]), "+f"(d[50]), "+f"(d[51]), "+f"(d[52]), "+f"(d[53]), "+f"(d[54]), "+f"(d[55]), "+f"(d[56]), "+f"(d[57]), "+f"(d[58]), "+f"(d[59]), "+f"(d[60]), "+f"(d[61]), "+f"(d[62]), "+f"(d[63])
    : "r"(a0), "r"(a1), "r"(a2), "r"(a3), "l"(descB), "r"(scaleD));
}
__device__ __forceinline__ void wgmma_rs_n64(float (&d)[32], uint32_t a0, uint32_t a1, uint32_t a2, uint32_t a3, uint64_t descB, int scaleD) {
  asm volatile("{\n.reg .pred p;\nsetp.ne.b32 p, %37, 0;\n"
    "wgmma.mma_async.sync.aligned.m64n64k16.f32.bf16.bf16 {%0, %1, %2, %3, %4, %5, %6, %7, %8, %9, %10, %11, %12, %13, %14, %15, %16, %17, %18, %19, %20, %21, %22, %23, %24, %25, %26, %27, %28, %29, %30, %31}, {%32, %33, %34, %35}, %36, p, 1, 1, 0;\n}\n"
    : "+f"(d[0]), "+f"(d[1]), "+f"(d[2]), "+f"(d[3]), "+f"(d[4]), "+f"(d[5]), "+f"(d[6]), "+f"(d[7]), "+f"(d[8]), "+f"(d[9]), "+f"(d[10]), "+f"(d[11]), "+f"(d[12]), "+f"(d[13]), "+f"(d[14]), "+f"(d[15]), "+f"(d[16]), "+f"(d[17]), "+f"(d[18]), "+f"(d[19]), "+f"(d[20]), "+f"(d[21]), "+f"(d[22]), "+f"(d[23]), "+f"(d[24]), "+f"(d[25]), "+f"(d[26]), "+f"(d[27]), "+f"(d[28]), "+f"(d[29]), "+f"(d[30]), "+f"(d[31])
    : "r"(a0), "r"(a1), "r"(a2), "r"(a3), "l"(descB), "r"(scaleD));
}
__device__ __forceinline__ void wgmma_rs_n24_tb(float (&d)[12], uint32_t a0, uint32_t a1, uint32_t a2, uint32_t a3, uint64_t descB, int scaleD) {
  asm volatile("{\n.reg .pred p;\nsetp.ne.b32 p, %17, 0;\n"
    "wgmma.mma_async.sync.aligned.m64n24k16.f32.bf16.bf16 {%0, %1, %2, %3, %4, %5, %6, %7, %8, %9, %10, %11}, {%12, %13, %14, %15}, %16, p, 1, 1, 1;\n}\n"
    : "+f"(d[0]), "+f"(d[1]), "+f"(d[2]), "+f"(d[3]), "+f"(d[4]), "+f"(d[5]), "+f"(d[6]), "+f"(d[7]), "+f"(d[8]), "+f"(d[9]), "+f"(d[10]), "+f"(d[11])
    : "r"(a0), "r"(a1), "r"(a2), "r"(a3), "l"(descB), "r"(scaleD));
}

constexpr int GT = 384;

__device__ __forceinline__ void release_stage(uint32_t bar, bool leader) {
  if (leader) {
    mbar_arrive_cluster(bar, 0);
    mbar_arrive_cluster(bar, 1);
  }
}

__device__ __forceinline__ void ln_row(const bf16* __restrict__ xin, bf16* __restrict__ xout, int l16) {
  const uint4* src = reinterpret_cast<const uint4*>(xin);
  uint4 v[5];
#pragma unroll
  for (int j = 0; j < 5; j++) v[j] = __ldg(src + j * 16 + l16);
  float s0 = 0.f, s1 = 0.f, s2 = 0.f, s3 = 0.f;
#pragma unroll
  for (int j = 0; j < 5; j++) {
    s0 += bf_lo(v[j].x) + bf_hi(v[j].x);
    s1 += bf_lo(v[j].y) + bf_hi(v[j].y);
    s2 += bf_lo(v[j].z) + bf_hi(v[j].z);
    s3 += bf_lo(v[j].w) + bf_hi(v[j].w);
  }
  float mean = (s0 + s1) + (s2 + s3);
#pragma unroll
  for (int o = 1; o < 16; o <<= 1) mean += __shfl_xor_sync(0xffffffffu, mean, o);
  mean *= (1.0f / DM);
  s0 = s1 = s2 = s3 = 0.f;
#pragma unroll
  for (int j = 0; j < 5; j++) {
    float d;
    d = bf_lo(v[j].x) - mean; s0 = fmaf(d, d, s0);
    d = bf_hi(v[j].x) - mean; s1 = fmaf(d, d, s1);
    d = bf_lo(v[j].y) - mean; s2 = fmaf(d, d, s2);
    d = bf_hi(v[j].y) - mean; s3 = fmaf(d, d, s3);
    d = bf_lo(v[j].z) - mean; s0 = fmaf(d, d, s0);
    d = bf_hi(v[j].z) - mean; s1 = fmaf(d, d, s1);
    d = bf_lo(v[j].w) - mean; s2 = fmaf(d, d, s2);
    d = bf_hi(v[j].w) - mean; s3 = fmaf(d, d, s3);
  }
  float sq = (s0 + s1) + (s2 + s3);
#pragma unroll
  for (int o = 1; o < 16; o <<= 1) sq += __shfl_xor_sync(0xffffffffu, sq, o);
  const float var_b = bf16_round(sq * (1.0f / DM));
  const float den = bf16_round(sqrtf(bf16_round(var_b + 1e-5f)));
  const float iv = __frcp_rn(den);
  const float mb = bf16_round(mean);
  uint4* dst = reinterpret_cast<uint4*>(xout);
#pragma unroll
  for (int j = 0; j < 5; j++) {
    uint4 w;
    uint32_t t;
    t = pack_bf16(bf_lo(v[j].x) - mb, bf_hi(v[j].x) - mb); w.x = pack_bf16(bf_lo(t) * iv, bf_hi(t) * iv);
    t = pack_bf16(bf_lo(v[j].y) - mb, bf_hi(v[j].y) - mb); w.y = pack_bf16(bf_lo(t) * iv, bf_hi(t) * iv);
    t = pack_bf16(bf_lo(v[j].z) - mb, bf_hi(v[j].z) - mb); w.z = pack_bf16(bf_lo(t) * iv, bf_hi(t) * iv);
    t = pack_bf16(bf_lo(v[j].w) - mb, bf_hi(v[j].w) - mb); w.w = pack_bf16(bf_lo(t) * iv, bf_hi(t) * iv);
    dst[j * 16 + l16] = w;
  }
}

constexpr int LG_STAGES = 5;
constexpr int QKV_STAGE = 8192 + 4 * 4096;
constexpr int GLU_STAGE = 8192 + 6 * 4096;

template <int WG>
__device__ __forceinline__ void qkv_mainloop(float (&acc)[120], uint32_t sbase, uint32_t sBar, bool leader) {
  constexpr int STAGE_BYTES = QKV_STAGE, NST = LG_STAGES;
  const uint64_t da_base = make_desc(sbase + WG * 4096, 16, 512, 2);
  const uint64_t db_base = make_desc(sbase + 8192, 4096, 1024, 1);
#pragma unroll 1
  for (int r = 0; r < 20 / NST; r++) {
#pragma unroll
    for (int s = 0; s < NST; s++) {
      mbar_wait(sBar + 8 * s, r & 1);
      wgmma_fence();
#pragma unroll
      for (int ks = 0; ks < 2; ks++)
        wgmma_ss_n240_tb(acc, da_base + (uint64_t)((s * STAGE_BYTES + ks * 32) >> 4), db_base + (uint64_t)((s * STAGE_BYTES + ks * 2048) >> 4), 1);
      wgmma_commit();
      wgmma_wait<1>();
      release_stage(sBar + 8 * (NST + (s + NST - 1) % NST), leader && (s > 0 || r > 0));
    }
  }
}
template <int WG>
__device__ __forceinline__ void glu_mainloop(float (&accg)[96], float (&accu)[96], uint32_t sbase, uint32_t sBar, bool leader) {
  constexpr int STAGE_BYTES = GLU_STAGE, NST = LG_STAGES;
  const uint64_t da_base = make_desc(sbase + WG * 4096, 16, 512, 2);
  const uint64_t db_base = make_desc(sbase + 8192, 4096, 1024, 1);
#pragma unroll 1
  for (int r = 0; r < 20 / NST; r++) {
#pragma unroll
    for (int s = 0; s < NST; s++) {
      mbar_wait(sBar + 8 * s, r & 1);
      wgmma_fence();
#pragma unroll
      for (int ks = 0; ks < 2; ks++) {
        const uint64_t da = da_base + (uint64_t)((s * STAGE_BYTES + ks * 32) >> 4);
        wgmma_ss_n192_tb(accg, da, db_base + (uint64_t)((s * STAGE_BYTES + ks * 2048) >> 4), 1);
        wgmma_ss_n192_tb(accu, da, db_base + (uint64_t)((s * STAGE_BYTES + 3 * 4096 + ks * 2048) >> 4), 1);
      }
      wgmma_commit();
      wgmma_wait<1>();
      release_stage(sBar + 8 * (NST + (s + NST - 1) % NST), leader && (s > 0 || r > 0));
    }
  }
}
constexpr int RG_STAGE_BYTES = 16384 + 8192 + 2048;
template <int NKB, int NST, int WG>
__device__ __forceinline__ void res_mainloop(float (&acc0)[32], float (&acc1)[8], uint32_t sbase, uint32_t sBar, bool leader) {
  const uint64_t da_base = make_desc(sbase + WG * 8192, 16, 1024, 1);
  const uint64_t db0_base = make_desc(sbase + 16384, 8192, 1024, 1);
  const uint64_t db1_base = make_desc(sbase + 16384 + 8192, 2048, 256, 3);
#pragma unroll 1
  for (int r = 0; r < NKB / NST; r++) {
#pragma unroll
    for (int s = 0; s < NST; s++) {
      const uint64_t so = (uint64_t)(s * (RG_STAGE_BYTES >> 4));
      mbar_wait(sBar + 8 * s, r & 1);
      wgmma_fence();
#pragma unroll
      for (int ks = 0; ks < 4; ks++) {
        wgmma_ss_n64_tb(acc0, da_base + so + ks * 2, db0_base + so + ks * 128, 1);
        wgmma_ss_n16_tb(acc1, da_base + so + ks * 2, db1_base + so + ks * 32, 1);
      }
      wgmma_commit();
      wgmma_wait<1>();
      release_stage(sBar + 8 * (NST + (s + NST - 1) % NST), leader && (s > 0 || r > 0));
    }
  }
}

constexpr int KA_SMEM = LG_STAGES * QKV_STAGE + 128 + 1024;

__global__ void __launch_bounds__(GT, 1)
qkv_kernel(const __grid_constant__ CUtensorMap tmA, const __grid_constant__ CUtensorMap tmB, const bf16* __restrict__ x) {
  constexpr int STAGE_BYTES = QKV_STAGE, NST = LG_STAGES, NKB = 20;
  extern __shared__ uint8_t smem_raw[];
  const uint32_t sbase = (smem_u32(smem_raw) + 1023u) & ~1023u;
  const uint32_t sBar = sbase + NST * STAGE_BYTES;
  const int tid = threadIdx.x, warp = tid >> 5, lane = tid & 31;
  const int rank = blockIdx.x & 1;
  const int pair = blockIdx.x >> 1;
  const int n_blk = pair & 7;
  const int m_blk = (pair >> 3) * 2 + rank;
  TS(0, 0);
  if (tid == 256) {
    prefetch_tmap(&tmA);
    prefetch_tmap(&tmB);
  }
  if (tid == 0) {
    for (int s = 0; s < NST; s++) {
      mbar_init(sBar + 8 * s, 1);
      mbar_init(sBar + 8 * (NST + s), 4);
    }
    fence_mbar_init();
    if (blockIdx.x < 32) g_flag[16 + blockIdx.x] = 0;
  }
  pdl_launch();
  cluster_sync_all();

  if (warp >= 8) {
    asm volatile("setmaxnreg.dec.sync.aligned.u32 40;");
    if (warp == 9) {
      named_bar_sync(5, 288);
      if (lane == 0) flag_signal(&g_flag[m_blk]);
    }
    if (tid == 256) {
      auto issue_b = [&](int kb) {
        const int s = kb % NST;
        const uint32_t full = sBar + 8 * s;
        mbar_expect_tx(full, STAGE_BYTES);
        const uint32_t dst = sbase + s * STAGE_BYTES + 8192;
#pragma unroll
        for (int j = 0; j < 2; j++) {
          const int sl = rank * 2 + j;
          tma_load_2d_mc(dst + sl * 4096, &tmB, n_blk * 240 + sl * 64, kb * 32, full, (uint16_t)3);
        }
      };
      for (int kb = 0; kb < NST; kb++) issue_b(kb);
      flag_wait(&g_flag[m_blk], 8);
      fence_proxy_async_all();
      for (int kb = 0; kb < NKB; kb++) {
        const int s = kb % NST;
        if (kb >= NST) {
          mbar_wait(sBar + 8 * (NST + s), ((kb / NST) & 1) ^ 1);
          issue_b(kb);
        }
        tma_load_2d(sbase + s * STAGE_BYTES, &tmA, kb * 32, m_blk * 128, sBar + 8 * s);
      }
    }
  } else {
    asm volatile("setmaxnreg.inc.sync.aligned.u32 232;");
    const int wg = __shfl_sync(0xffffffffu, warp >> 2, 0);
    const int wwarp = warp & 3;
    {
      const int row = m_blk * 128 + n_blk * 16 + warp * 2 + (lane >> 4);
      ln_row(x + (size_t)row * DM, g_xn + (size_t)row * DM, lane & 15);
      asm volatile("bar.arrive 5, 288;" ::: "memory");
    }
    TS(0, 1);
    mbar_wait(sBar, 0);
    TS(0, 3);
    float acc[120];
#pragma unroll
    for (int i = 0; i < 120; i++) acc[i] = 0.f;
    if (wg == 0) qkv_mainloop<0>(acc, sbase, sBar, (tid & 127) == 0);
    else qkv_mainloop<1>(acc, sbase, sBar, (tid & 127) == 0);
    wgmma_wait<0>();
    fence_regs(acc);
    TS(0, 4);
    named_bar_sync(3, 256);
    const int g = lane >> 2, c4 = lane & 3;
    const uint32_t stg = sbase + wg * (12 * 3072) + (wwarp * 2) * 384 + g * 16;
    const int hbase = n_blk * 12;
#pragma unroll
    for (int j = 0; j < 30; j++) {
      const int cb = (j * 8) % 20;
      const int hb = (j * 8) / 20;
      int d = cb + c4 * 2;
      int hl = hb;
      if (cb == 16 && c4 >= 2) { d -= 20; hl += 1; }
      const uint32_t a0 = stg + hl * 3072 + (d >> 3) * 128 + (d & 7) * 2;
      const int hg = hbase + hl;
      const float sc = hg < 32 ? ATT_SCALE_LOG2E : 1.0f;
      st_shared_b32(a0, pack_bf16(acc[4 * j] * sc, acc[4 * j + 1] * sc));
      st_shared_b32(a0 + 384, pack_bf16(acc[4 * j + 2] * sc, acc[4 * j + 3] * sc));
      if (d == 18) {
        const uint32_t pad0 = hg < 32 ? 0u : (hg < 64 ? 0x3f803f80u : 0x00003f80u);
        const uint32_t pad1 = (hg >= 32 && hg < 64) ? 0x00003f80u : 0u;
        st_shared_v2(a0 + 4, pad0, pad1);
        st_shared_v2(a0 + 388, pad0, pad1);
      }
      if (j % 10 == 9) {
        fence_proxy_async();
        named_bar_sync(1 + wg, 128);
        if ((tid & 127) < 4) {
          const int hs = (j / 10) * 4 + (tid & 127);
          bf16* dst = g_img + (size_t)(hbase + hs) * IMG_HEAD_ELEMS + (size_t)(m_blk * 16 + wg * 8) * 192;
          bulk_s2g(dst, sbase + wg * (12 * 3072) + hs * 3072, 3072);
          bulk_commit();
        }
      }
    }
    if ((tid & 127) < 4) bulk_wait_read();
  }
  __syncwarp();
  TS(0, 5);
  cluster_sync_relaxed();
  TS(0, 6);
}

constexpr int KC_NST1 = 5, KC_NST3 = 6;
constexpr int KC_STAGING = 160 * 1024;
constexpr int KC_BAR = KC_STAGING + 48 * 1024;
constexpr int KC_CS = KC_BAR + 512;
constexpr int KC_SMEM = KC_CS + 1536 + 1024;

__global__ void __launch_bounds__(GT, 1)
mlp_kernel(const __grid_constant__ CUtensorMap tmO, const __grid_constant__ CUtensorMap tmWo64, const __grid_constant__ CUtensorMap tmWo16,
           const __grid_constant__ CUtensorMap tmH, const __grid_constant__ CUtensorMap tmWg, const __grid_constant__ CUtensorMap tmWu,
           const __grid_constant__ CUtensorMap tmHHs, const __grid_constant__ CUtensorMap tmHH, const __grid_constant__ CUtensorMap tmWd64,
           const __grid_constant__ CUtensorMap tmWd16, const __grid_constant__ CUtensorMap tmHs, const __grid_constant__ CUtensorMap tmOut,
           const bf16* __restrict__ x) {
  extern __shared__ uint8_t smem_raw[];
  const uint32_t sbase = (smem_u32(smem_raw) + 1023u) & ~1023u;
  const uint32_t bar1 = sbase + KC_BAR;
  const uint32_t bar2 = bar1 + 128;
  const uint32_t bar3 = bar2 + 128;
  const uint32_t barD = bar3 + 128;
  const int tid = threadIdx.x, warp = tid >> 5, lane = tid & 31;
  const int rank = blockIdx.x & 1;
  const int pair = blockIdx.x >> 1;
  const int j_blk = pair & 7;
  const int m_blk = (pair >> 3) * 2 + rank;
  const int n0 = j_blk * 80;
  TS(2, 0);
  if (tid == 256) {
    prefetch_tmap(&tmO); prefetch_tmap(&tmWo64); prefetch_tmap(&tmWo16); prefetch_tmap(&tmH); prefetch_tmap(&tmWg);
    prefetch_tmap(&tmWu); prefetch_tmap(&tmHHs); prefetch_tmap(&tmHH); prefetch_tmap(&tmWd64); prefetch_tmap(&tmWd16);
    prefetch_tmap(&tmHs); prefetch_tmap(&tmOut);
  }
  if (tid == 0) {
    for (int s = 0; s < 5; s++) {
      mbar_init(bar1 + 8 * s, 1); mbar_init(bar1 + 8 * (5 + s), 4);
      mbar_init(bar2 + 8 * s, 1); mbar_init(bar2 + 8 * (5 + s), 4);
    }
    for (int s = 0; s < 6; s++) { mbar_init(bar3 + 8 * s, 1); mbar_init(bar3 + 8 * (6 + s), 4); }
    mbar_init(barD, 4); mbar_init(barD + 8, 4);
    fence_mbar_init();
  }
  cluster_sync_all();

  if (warp >= 8) {
    asm volatile("setmaxnreg.dec.sync.aligned.u32 40;");
    if (tid == 256) {
      auto issue_b80 = [&](const CUtensorMap* t64, const CUtensorMap* t16, uint32_t bars, int nst, int kb) {
        const int s = kb % nst;
        const uint32_t full = bars + 8 * s;
        const uint32_t st = sbase + s * RG_STAGE_BYTES;
        mbar_expect_tx(full, RG_STAGE_BYTES);
        tma_load_2d_mc(st + 16384 + rank * 4096, t64, n0, kb * 64 + rank * 32, full, (uint16_t)3);
        tma_load_2d_mc(st + 16384 + 8192 + rank * 1024, t16, n0 + 64, kb * 64 + rank * 32, full, (uint16_t)3);
      };
      for (int kb = 0; kb < KC_NST1; kb++) issue_b80(&tmWo64, &tmWo16, bar1, KC_NST1, kb);
      pdl_wait();
      for (int kb = 0; kb < 10; kb++) {
        const int s = kb % KC_NST1;
        if (kb >= KC_NST1) {
          mbar_wait(bar1 + 8 * (KC_NST1 + s), ((kb / KC_NST1) & 1) ^ 1);
          issue_b80(&tmWo64, &tmWo16, bar1, KC_NST1, kb);
        }
        tma_load_2d(sbase + s * RG_STAGE_BYTES, &tmO, kb * 64, m_blk * 128, bar1 + 8 * s);
      }
      auto issue_bglu = [&](int kb) {
        const int s = kb % LG_STAGES;
        const uint32_t full = bar2 + 8 * s;
        mbar_expect_tx(full, GLU_STAGE);
        const uint32_t dst = sbase + s * GLU_STAGE + 8192;
#pragma unroll
        for (int j = 0; j < 3; j++)
          tma_load_2d_mc(dst + (rank * 3 + j) * 4096, rank == 0 ? &tmWg : &tmWu, j_blk * 192 + j * 64, kb * 32, full, (uint16_t)3);
      };
      mbar_wait(barD, 0);
      for (int kb = 0; kb < LG_STAGES; kb++) issue_bglu(kb);
      flag_wait(&g_flag[16 + m_blk], 16);
      fence_proxy_async_all();
      for (int kb = 0; kb < 20; kb++) {
        const int s = kb % LG_STAGES;
        if (kb >= LG_STAGES) {
          mbar_wait(bar2 + 8 * (LG_STAGES + s), ((kb / LG_STAGES) & 1) ^ 1);
          issue_bglu(kb);
        }
        tma_load_2d(sbase + s * GLU_STAGE, &tmH, kb * 32, m_blk * 128, bar2 + 8 * s);
      }
      mbar_wait(barD + 8, 0);
      for (int kb = 0; kb < KC_NST3; kb++) issue_b80(&tmWd64, &tmWd16, bar3, KC_NST3, kb);
      flag_wait(&g_flag[32 + m_blk], 16);
      fence_proxy_async_all();
      for (int kb = 0; kb < 24; kb++) {
        const int s = kb % KC_NST3;
        if (kb >= KC_NST3) {
          mbar_wait(bar3 + 8 * (KC_NST3 + s), ((kb / KC_NST3) & 1) ^ 1);
          issue_b80(&tmWd64, &tmWd16, bar3, KC_NST3, kb);
        }
        tma_load_2d(sbase + s * RG_STAGE_BYTES, &tmHH, kb * 64, m_blk * 128, bar3 + 8 * s);
      }
    }
  } else {
    asm volatile("setmaxnreg.inc.sync.aligned.u32 232;");
    const int wg = __shfl_sync(0xffffffffu, warp >> 2, 0);
    const int wwarp = warp & 3;
    const int g = lane >> 2, c4 = lane & 3;
    const int row0 = m_blk * 128 + wg * 64 + wwarp * 16 + g;
    const bool leader = (tid & 127) == 0;
    const uint32_t stg80_base = sbase + KC_STAGING + wg * 24576;
    const uint32_t stg80 = stg80_base + (wwarp * 16 + g) * 160 + c4 * 4;
    {
      uint32_t res[20];
#pragma unroll
      for (int j = 0; j < 10; j++) {
        res[2 * j] = __ldg(reinterpret_cast<const uint32_t*>(x + (size_t)row0 * DM + n0 + j * 8 + c4 * 2));
        res[2 * j + 1] = __ldg(reinterpret_cast<const uint32_t*>(x + (size_t)(row0 + 8) * DM + n0 + j * 8 + c4 * 2));
      }
      float acc0[32], acc1[8];
#pragma unroll
      for (int i = 0; i < 32; i++) acc0[i] = 0.f;
#pragma unroll
      for (int i = 0; i < 8; i++) acc1[i] = 0.f;
      TS(2, 1);
      if (wg == 0) res_mainloop<10, KC_NST1, 0>(acc0, acc1, sbase, bar1, leader);
      else res_mainloop<10, KC_NST1, 1>(acc0, acc1, sbase, bar1, leader);
      wgmma_wait<0>();
      fence_regs(acc0); fence_regs(acc1);
      release_stage(barD, leader);
      TS(2, 4);
      float sum0 = 0.f, sum1 = 0.f;
#pragma unroll
      for (int j = 0; j < 10; j++) {
        const uint32_t a01 = j < 8 ? pack_bf16(acc0[4 * j], acc0[4 * j + 1]) : pack_bf16(acc1[4 * (j - 8)], acc1[4 * (j - 8) + 1]);
        const uint32_t a23 = j < 8 ? pack_bf16(acc0[4 * j + 2], acc0[4 * j + 3]) : pack_bf16(acc1[4 * (j - 8) + 2], acc1[4 * (j - 8) + 3]);
        res[2 * j] = pack_bf16(bf_lo(res[2 * j]) + bf_lo(a01), bf_hi(res[2 * j]) + bf_hi(a01));
        res[2 * j + 1] = pack_bf16(bf_lo(res[2 * j + 1]) + bf_lo(a23), bf_hi(res[2 * j + 1]) + bf_hi(a23));
        st_shared_b32(stg80 + j * 16, res[2 * j]);
        st_shared_b32(stg80 + 8 * 160 + j * 16, res[2 * j + 1]);
        sum0 += bf_lo(res[2 * j]) + bf_hi(res[2 * j]);
        sum1 += bf_lo(res[2 * j + 1]) + bf_hi(res[2 * j + 1]);
      }
      sum0 += __shfl_xor_sync(0xffffffffu, sum0, 1); sum1 += __shfl_xor_sync(0xffffffffu, sum1, 1);
      sum0 += __shfl_xor_sync(0xffffffffu, sum0, 2); sum1 += __shfl_xor_sync(0xffffffffu, sum1, 2);
      const float mu0 = sum0 * (1.0f / 80.0f), mu1 = sum1 * (1.0f / 80.0f);
      float q0 = 0.f, q1 = 0.f;
#pragma unroll
      for (int j = 0; j < 10; j++) {
        float d;
        d = bf_lo(res[2 * j]) - mu0; q0 = fmaf(d, d, q0);
        d = bf_hi(res[2 * j]) - mu0; q0 = fmaf(d, d, q0);
        d = bf_lo(res[2 * j + 1]) - mu1; q1 = fmaf(d, d, q1);
        d = bf_hi(res[2 * j + 1]) - mu1; q1 = fmaf(d, d, q1);
      }
      q0 += __shfl_xor_sync(0xffffffffu, q0, 1); q1 += __shfl_xor_sync(0xffffffffu, q1, 1);
      q0 += __shfl_xor_sync(0xffffffffu, q0, 2); q1 += __shfl_xor_sync(0xffffffffu, q1, 2);
      if (c4 == 0) {
        g_stats[row0 * 8 + j_blk] = make_float2(mu0, q0);
        g_stats[(row0 + 8) * 8 + j_blk] = make_float2(mu1, q1);
      }
      fence_proxy_async();
      named_bar_sync(1 + wg, 128);
      if (leader) {
        tma_store_2d(&tmHs, stg80_base, n0, m_blk * 128 + wg * 64);
        bulk_commit();
        bulk_wait_all();
        fence_proxy_async_all();
        flag_signal(&g_flag[16 + m_blk]);
      }
      TS(2, 5);
    }
    {
      pdl_wait();
      {
        float* cs_s = reinterpret_cast<float*>(smem_raw + (sbase - smem_u32(smem_raw)) + KC_CS);
        for (int i = tid; i < 384; i += 256) cs_s[i] = g_cs[(i >= 192 ? FF - 192 : 0) + j_blk * 192 + i];
        named_bar_sync(3, 256);
      }
      flag_wait(&g_flag[16 + m_blk], 16);
      float mb[2], iv[2];
#pragma unroll
      for (int h = 0; h < 2; h++) {
        const float4* sp = reinterpret_cast<const float4*>(g_stats + (row0 + 8 * h) * 8);
        const float4 p0 = sp[0], p1 = sp[1], p2 = sp[2], p3 = sp[3];
        const float mean = (((p0.x + p0.z) + (p1.x + p1.z)) + ((p2.x + p2.z) + (p3.x + p3.z))) * 0.125f;
        float m2 = ((p0.y + p0.w) + (p1.y + p1.w)) + ((p2.y + p2.w) + (p3.y + p3.w));
        float dd = 0.f, d;
        d = p0.x - mean; dd = fmaf(d, d, dd); d = p0.z - mean; dd = fmaf(d, d, dd);
        d = p1.x - mean; dd = fmaf(d, d, dd); d = p1.z - mean; dd = fmaf(d, d, dd);
        d = p2.x - mean; dd = fmaf(d, d, dd); d = p2.z - mean; dd = fmaf(d, d, dd);
        d = p3.x - mean; dd = fmaf(d, d, dd); d = p3.z - mean; dd = fmaf(d, d, dd);
        m2 = fmaf(dd, 80.0f, m2);
        const float var_b = bf16_round(m2 * (1.0f / DM));
        const float den = bf16_round(sqrtf(bf16_round(var_b + 1e-5f)));
        iv[h] = __frcp_rn(den);
        mb[h] = bf16_round(mean);
      }
      float accg[96], accu[96];
#pragma unroll
      for (int i = 0; i < 96; i++) { accg[i] = 0.f; accu[i] = 0.f; }
      TS(3, 3);
      if (wg == 0) glu_mainloop<0>(accg, accu, sbase, bar2, leader);
      else glu_mainloop<1>(accg, accu, sbase, bar2, leader);
      wgmma_wait<0>();
      fence_regs(accg); fence_regs(accu);
      release_stage(barD + 8, leader);
      TS(3, 4);
      const uint32_t stg = sbase + KC_STAGING + wg * 24576 + (wwarp * 16 + g) * 128 + c4 * 4;
      const float* csg = reinterpret_cast<const float*>(smem_raw + (sbase - smem_u32(smem_raw)) + KC_CS) + c4 * 2;
      const float nm0 = -mb[0] * iv[0], nm1 = -mb[1] * iv[1];
#pragma unroll
      for (int sl = 0; sl < 3; sl++) {
        float2 cgv[4], cuv[4];
#pragma unroll
        for (int jj = 0; jj < 8; jj++) {
          const int j = sl * 8 + jj;
          if ((jj & 3) == 0) {
#pragma unroll
            for (int q = 0; q < 4; q++) {
              cgv[q] = *reinterpret_cast<const float2*>(csg + (j + q) * 8);
              cuv[q] = *reinterpret_cast<const float2*>(csg + 192 + (j + q) * 8);
            }
          }
          const float2 cg = cgv[jj & 3], cu = cuv[jj & 3];
          const float r0 = fmaxf(fmaf(accg[4 * j], iv[0], nm0 * cg.x), 0.f) * fmaf(accu[4 * j], iv[0], nm0 * cu.x);
          const float r1 = fmaxf(fmaf(accg[4 * j + 1], iv[0], nm0 * cg.y), 0.f) * fmaf(accu[4 * j + 1], iv[0], nm0 * cu.y);
          const float r2 = fmaxf(fmaf(accg[4 * j + 2], iv[1], nm1 * cg.x), 0.f) * fmaf(accu[4 * j + 2], iv[1], nm1 * cu.x);
          const float r3 = fmaxf(fmaf(accg[4 * j + 3], iv[1], nm1 * cg.y), 0.f) * fmaf(accu[4 * j + 3], iv[1], nm1 * cu.y);
          const uint32_t a0 = stg + sl * 8192 + ((jj ^ g) << 4);
          st_shared_b32(a0, pack_bf16(r0, r1));
          st_shared_b32(a0 + 1024, pack_bf16(r2, r3));
        }
        fence_proxy_async();
        named_bar_sync(1 + wg, 128);
        if (leader) {
          tma_store_2d(&tmHHs, sbase + KC_STAGING + wg * 24576 + sl * 8192, j_blk * 192 + sl * 64, m_blk * 128 + wg * 64);
          bulk_commit();
        }
      }
      TS(3, 7);
      if (leader) {
        bulk_wait_all();
        TS(3, 8);
        fence_proxy_async_all();
        flag_signal(&g_flag[32 + m_blk]);
      }
      TS(3, 9);
    }
    {
      uint32_t res[20];
#pragma unroll
      for (int j = 0; j < 10; j++) {
        res[2 * j] = *reinterpret_cast<const uint32_t*>(g_h + (size_t)row0 * DM + n0 + j * 8 + c4 * 2);
        res[2 * j + 1] = *reinterpret_cast<const uint32_t*>(g_h + (size_t)(row0 + 8) * DM + n0 + j * 8 + c4 * 2);
      }
      float acc0[32], acc1[8];
#pragma unroll
      for (int i = 0; i < 32; i++) acc0[i] = 0.f;
#pragma unroll
      for (int i = 0; i < 8; i++) acc1[i] = 0.f;
      mbar_wait(bar3, 0);
      TS(4, 3);
      if (wg == 0) res_mainloop<24, KC_NST3, 0>(acc0, acc1, sbase, bar3, leader);
      else res_mainloop<24, KC_NST3, 1>(acc0, acc1, sbase, bar3, leader);
      wgmma_wait<0>();
      fence_regs(acc0); fence_regs(acc1);
      TS(4, 4);
#pragma unroll
      for (int j = 0; j < 10; j++) {
        const uint32_t a01 = j < 8 ? pack_bf16(acc0[4 * j], acc0[4 * j + 1]) : pack_bf16(acc1[4 * (j - 8)], acc1[4 * (j - 8) + 1]);
        const uint32_t a23 = j < 8 ? pack_bf16(acc0[4 * j + 2], acc0[4 * j + 3]) : pack_bf16(acc1[4 * (j - 8) + 2], acc1[4 * (j - 8) + 3]);
        st_shared_b32(stg80 + j * 16, pack_bf16(bf_lo(res[2 * j]) + bf_lo(a01), bf_hi(res[2 * j]) + bf_hi(a01)));
        st_shared_b32(stg80 + 8 * 160 + j * 16, pack_bf16(bf_lo(res[2 * j + 1]) + bf_lo(a23), bf_hi(res[2 * j + 1]) + bf_hi(a23)));
      }
      fence_proxy_async();
      named_bar_sync(1 + wg, 128);
      if (leader) {
        tma_store_2d(&tmOut, stg80_base, n0, m_blk * 128 + wg * 64);
        bulk_commit();
        bulk_wait_read();
      }
      TS(4, 5);
    }
  }
  __syncwarp();
  cluster_sync_relaxed();
  TS(4, 6);
}

constexpr int AT_THREADS = 512;
constexpr int AT_WGS = AT_THREADS / 128;
#define AT_CHUNK_MASK 3
#define AT_STAGGER 0
constexpr int AT_KV_BYTES = IMG_HEAD_ELEMS * 2;
constexpr int AT_SMEM = 2 * AT_KV_BYTES + 256 + 1024;
constexpr int AT_CHUNKS = 8;

__device__ __forceinline__ float exp2_poly(float x) {
  const float u = __saturatef(fmaf(x, 1.0f / 64.0f, 62.0f / 64.0f));
  const float MAGIC = 12582912.0f - 62.0f;
  const float r = fmaf(u, 64.0f, MAGIC);
  const float q = MAGIC - r;
  const float fr = fmaf(u, 64.0f, q);
  float p = fmaf(fr, 0.009570102207362652f, 0.05591785907745361f);
  p = fmaf(p, fr, 0.240247443318367f);
  p = fmaf(p, fr, 0.6931217908859253f);
  p = fmaf(p, fr, 0.9999992847442627f);
  return __uint_as_float(__float_as_uint(p) + (__float_as_uint(r) << 23));
}
#define AT_VARIANT 0
#define AT_POLY_MOD 8
__device__ __forceinline__ bool use_poly(int e) {
  return (e % AT_POLY_MOD) == 1;
}

struct AttnState {
  uint32_t qa0, qa1, qa2, qa3, qa4, qa5;
  float M0, M1;
};

__device__ __forceinline__ bool attn_exp_fast(const float (&s)[32], uint32_t (&p)[16]) {
#pragma unroll
  for (int j = 0; j < 16; j++) {
    const float e0 = use_poly(2 * j) ? exp2_poly(s[2 * j]) : ex2(s[2 * j]);
    const float e1 = use_poly(2 * j + 1) ? exp2_poly(s[2 * j + 1]) : ex2(s[2 * j + 1]);
    p[j] = pack_bf16(e0, e1);
  }
  uint32_t acc_or = 0;
#pragma unroll
  for (int j = 0; j < 16; j++) acc_or |= p[j];
  return __any_sync(0xffffffffu, (acc_or & 0x40004000u) != 0);
}
__device__ __forceinline__ void attn_exp_exact(const float (&s)[32], uint32_t (&p)[16], float (&o)[12], AttnState& st, bool first, int c4) {
  float mx0 = fmaxf(s[0], s[1]), mx1 = fmaxf(s[2], s[3]);
#pragma unroll
  for (int j = 1; j < 8; j++) {
    mx0 = fmaxf(mx0, fmaxf(s[4 * j], s[4 * j + 1]));
    mx1 = fmaxf(mx1, fmaxf(s[4 * j + 2], s[4 * j + 3]));
  }
  mx0 = fmaxf(mx0, __shfl_xor_sync(0xffffffffu, mx0, 1));
  mx1 = fmaxf(mx1, __shfl_xor_sync(0xffffffffu, mx1, 1));
  mx0 = fmaxf(mx0, __shfl_xor_sync(0xffffffffu, mx0, 2));
  mx1 = fmaxf(mx1, __shfl_xor_sync(0xffffffffu, mx1, 2));
  float d0 = mx0 + 7.0f, d1 = mx1 + 7.0f;
  if (!first) { d0 = fmaxf(d0, 0.f); d1 = fmaxf(d1, 0.f); }
  const float T0 = st.M0 + d0, T1 = st.M1 + d1;
  const float h0 = bf16_round(T0), h1 = bf16_round(T1);
  const float i0 = bf16_round(T0 - h0), i1 = bf16_round(T1 - h1);
  const float l0 = bf16_round((T0 - h0) - i0), l1 = bf16_round((T1 - h1) - i1);
  const float N0 = (h0 + i0) + l0, N1 = (h1 + i1) + l1;
  d0 = N0 - st.M0; d1 = N1 - st.M1;
  st.M0 = N0; st.M1 = N1;
  if (c4 == 2) { st.qa4 = pack_bf16(-h0, -i0); st.qa5 = pack_bf16(-h1, -i1); }
  if (c4 == 3) { st.qa4 = pack_bf16(-l0, 0.f); st.qa5 = pack_bf16(-l1, 0.f); }
  if (!first) {
    const float al0 = ex2(-d0), al1 = ex2(-d1);
#pragma unroll
    for (int j = 0; j < 3; j++) {
      o[4 * j] *= al0; o[4 * j + 1] *= al0;
      o[4 * j + 2] *= al1; o[4 * j + 3] *= al1;
    }
  }
#pragma unroll
  for (int j = 0; j < 8; j++) {
    p[2 * j] = pack_bf16(ex2(s[4 * j] - d0), ex2(s[4 * j + 1] - d0));
    p[2 * j + 1] = pack_bf16(ex2(s[4 * j + 2] - d1), ex2(s[4 * j + 3] - d1));
  }
}
__device__ __forceinline__ void attn_step(float (&s)[32], const uint32_t (&pp)[16], uint32_t (&pn)[16], float (&o)[12], AttnState& st,
                                          uint32_t k_addr, uint32_t v_addr_prev, int keep, int c4, int wgdbg = 0, int tdbg = 0) {
  PH(wgdbg, tdbg, 0);
  const uint64_t dk = make_desc(k_addr, 128, 384, 0);
  const uint64_t dv_prev = make_desc(v_addr_prev, 384, 128, 0);
  wgmma_fence();
  wgmma_rs_n64(s, st.qa0, st.qa1, st.qa2, st.qa3, dk, 0);
  wgmma_rs_n64(s, st.qa4, st.qa5, 0u, 0u, dk + 16, 1);
  wgmma_commit();
#pragma unroll
  for (int kk = 0; kk < 4; kk++) wgmma_rs_n24_tb(o, pp[4 * kk], pp[4 * kk + 1], pp[4 * kk + 2], pp[4 * kk + 3], dv_prev + kk * 48, kk == 0 ? keep : 1);
  wgmma_commit();
  wgmma_wait<1>();
  fence_regs(s);
  PH(wgdbg, tdbg, 1);
  const bool redo = attn_exp_fast(s, pn);
  PH(wgdbg, tdbg, 2);
  wgmma_wait<0>();
  fence_regs(o);
  if (redo) attn_exp_exact(s, pn, o, st, false, c4);
}

__global__ void __launch_bounds__(AT_THREADS, 1) attn_kernel(const bf16* __restrict__ wo, const bf16* __restrict__ wgt, const bf16* __restrict__ wup, const bf16* __restrict__ wdn) {
  extern __shared__ uint8_t smem_raw[];
  const uint32_t sbase = (smem_u32(smem_raw) + 1023u) & ~1023u;
  const uint32_t sK = sbase, sV = sbase + AT_KV_BYTES;
  const uint32_t sBar = sV + AT_KV_BYTES;
  const int tid = threadIdx.x, warp = tid >> 5, lane = tid & 31;
  const int head = blockIdx.x >> 2, quarter = blockIdx.x & 3;
  if (blockIdx.x >= 128) {
    pdl_launch();
    const int b = blockIdx.x - 128;
    const bf16* w = (b >> 1) ? wup : wgt;
    const int cgrp = tid % 96, rgrp = tid / 96;
    float acc[8];
#pragma unroll
    for (int i = 0; i < 8; i++) acc[i] = 0.f;
    float* red = reinterpret_cast<float*>(smem_raw);
    if (rgrp < 5) {
      const uint4* src = reinterpret_cast<const uint4*>(w + (size_t)(rgrp * 128) * FF + (b & 1) * 768 + cgrp * 8);
#pragma unroll 8
      for (int r = 0; r < 128; r++) {
        const uint4 v = __ldg(src + (size_t)r * (FF / 8));
        acc[0] += bf_lo(v.x); acc[1] += bf_hi(v.x); acc[2] += bf_lo(v.y); acc[3] += bf_hi(v.y);
        acc[4] += bf_lo(v.z); acc[5] += bf_hi(v.z); acc[6] += bf_lo(v.w); acc[7] += bf_hi(v.w);
      }
#pragma unroll
      for (int i = 0; i < 8; i++) red[rgrp * 768 + cgrp * 8 + i] = acc[i];
    }
    __syncthreads();
    pdl_wait();
    for (int c = tid; c < 768; c += AT_THREADS)
      g_cs[(b >> 1) * FF + (b & 1) * 768 + c] = ((red[c] + red[768 + c]) + (red[1536 + c] + red[2304 + c])) + red[3072 + c];
    if (b == 0 && tid < 16) g_flag[tid] = 0;
    return;
  }
  TS(1, 0);
  if (tid == 0) {
    for (int i = 0; i < AT_CHUNKS; i++) mbar_init(sBar + 8 * i, 1);
    fence_mbar_init();
  }
  pdl_launch();
  if (tid == 32) {
    prefetch_l2(reinterpret_cast<const uint8_t*>(wo) + blockIdx.x * 6400, 6400);
    prefetch_l2(reinterpret_cast<const uint8_t*>(wgt) + blockIdx.x * 15360, 15360);
    prefetch_l2(reinterpret_cast<const uint8_t*>(wup) + blockIdx.x * 15360, 15360);
    prefetch_l2(reinterpret_cast<const uint8_t*>(wdn) + blockIdx.x * 15360, 15360);
  }
  __syncthreads();
  TS(1, 1);
  pdl_wait();
  TS(1, 2);
  if (tid == 0) {
    const uint8_t* kg = reinterpret_cast<const uint8_t*>(g_img + (size_t)(32 + head) * IMG_HEAD_ELEMS);
    const uint8_t* vg = reinterpret_cast<const uint8_t*>(g_img + (size_t)(64 + head) * IMG_HEAD_ELEMS);
    constexpr int CB = AT_KV_BYTES / AT_CHUNKS;
    for (int i = 0; i < AT_CHUNKS; i++) {
      mbar_expect_tx(sBar + 8 * i, 2 * CB);
      bulk_g2s(sK + i * CB, kg + i * CB, CB, sBar + 8 * i);
      bulk_g2s(sV + i * CB, vg + i * CB, CB, sBar + 8 * i);
    }
  }
  const int wg = warp >> 2, wwarp = warp & 3;
  const int g = lane >> 2, c4 = lane & 3;
  const uint64_t dk_base = make_desc(sK, 128, 384, 0);
  const uint64_t dv_base = make_desc(sV, 384, 128, 0);

#pragma unroll 1
  for (int rep = 0; rep < 8 / AT_WGS; rep++) {
    const int row0 = quarter * 512 + (rep * AT_WGS + wg) * 64 + wwarp * 16 + g;
    AttnState st;
    {
      const bf16* q0 = g_img + (size_t)head * IMG_HEAD_ELEMS + (size_t)(row0 >> 3) * 192 + g * 8 + c4 * 2;
      const bf16* q1 = q0 + 192;
      st.qa0 = *reinterpret_cast<const uint32_t*>(q0);
      st.qa1 = *reinterpret_cast<const uint32_t*>(q1);
      st.qa2 = *reinterpret_cast<const uint32_t*>(q0 + 64);
      st.qa3 = *reinterpret_cast<const uint32_t*>(q1 + 64);
      st.qa4 = *reinterpret_cast<const uint32_t*>(q0 + 128);
      st.qa5 = *reinterpret_cast<const uint32_t*>(q1 + 128);
    }
    float o[12];
    float s[32];
    uint32_t pa[16], pb[16];
    st.M0 = st.M1 = 0.f;
    if (rep == 0) mbar_wait(sBar, 0);
    wgmma_fence();
    wgmma_rs_n64(s, st.qa0, st.qa1, st.qa2, st.qa3, dk_base, 0);
    wgmma_rs_n64(s, st.qa4, st.qa5, 0u, 0u, dk_base + 16, 1);
    wgmma_commit();
    wgmma_wait<0>();
    fence_regs(s);
    attn_exp_exact(s, pa, o, st, true, c4);
    attn_step(s, pa, pb, o, st, sK + 3072, sV, 0, c4);
#pragma unroll 1
    for (int tt = 1; tt < 16; tt++) {
      if (rep == 0 && !(tt & 1)) mbar_wait(sBar + 8 * (tt >> 1), 0);
      attn_step(s, pb, pa, o, st, sK + tt * 6144, sV + tt * 6144 - 3072, 1, c4, wg, rep * 32 + tt * 2);
      attn_step(s, pa, pb, o, st, sK + tt * 6144 + 3072, sV + tt * 6144, 1, c4, wg, rep * 32 + tt * 2 + 1);
    }
    wgmma_fence();
#pragma unroll
    for (int kk = 0; kk < 4; kk++) wgmma_rs_n24_tb(o, pb[4 * kk], pb[4 * kk + 1], pb[4 * kk + 2], pb[4 * kk + 3], dv_base + 31 * 192 + kk * 48, 1);
    wgmma_commit();
    wgmma_wait<0>();
    fence_regs(o);
    TS(1, 3 + rep);
    const float l0 = __shfl_sync(0xffffffffu, o[8], (lane & ~3) | 2);
    const float l1 = __shfl_sync(0xffffffffu, o[10], (lane & ~3) | 2);
    const float i0 = 1.0f / l0, i1 = 1.0f / l1;
    bf16* o0 = g_o + (size_t)row0 * DM + head * DH;
    bf16* o1 = o0 + 8 * DM;
#pragma unroll
    for (int j = 0; j < 3; j++) {
      if (j < 2 || c4 < 2) {
        *reinterpret_cast<uint32_t*>(o0 + j * 8 + c4 * 2) = pack_bf16(o[4 * j] * i0, o[4 * j + 1] * i0);
        *reinterpret_cast<uint32_t*>(o1 + j * 8 + c4 * 2) = pack_bf16(o[4 * j + 2] * i1, o[4 * j + 3] * i1);
      }
    }
  }
}

typedef CUresult (*EncodeTiledFn)(CUtensorMap*, CUtensorMapDataType, cuuint32_t, void*, const cuuint64_t*, const cuuint64_t*,
                                  const cuuint32_t*, const cuuint32_t*, CUtensorMapInterleave, CUtensorMapSwizzle,
                                  CUtensorMapL2promotion, CUtensorMapFloatOOBfill);

static void make_map(EncodeTiledFn fn, CUtensorMap* tm, const void* ptr, uint64_t rows, uint64_t cols, uint32_t box_rows,
                     uint32_t box_cols, CUtensorMapSwizzle sw) {
  cuuint64_t dims[2] = {cols, rows};
  cuuint64_t strides[1] = {cols * 2};
  cuuint32_t box[2] = {box_cols, box_rows};
  cuuint32_t es[2] = {1, 1};
  fn(tm, CU_TENSOR_MAP_DATA_TYPE_BFLOAT16, 2, const_cast<void*>(ptr), dims, strides, box, es, CU_TENSOR_MAP_INTERLEAVE_NONE, sw,
     CU_TENSOR_MAP_L2_PROMOTION_L2_256B, CU_TENSOR_MAP_FLOAT_OOB_FILL_NONE);
}

template <typename... KArgs, typename... Args>
static void launch(void (*kern)(KArgs...), int grid, int block, int smem, int cluster, bool pdl, Args... args) {
  cudaLaunchConfig_t cfg = {};
  cfg.gridDim = dim3(grid);
  cfg.blockDim = dim3(block);
  cfg.dynamicSmemBytes = smem;
  cfg.stream = cudaStreamPerThread;
  cudaLaunchAttribute at[2];
  int n = 0;
  if (cluster > 1) {
    at[n].id = cudaLaunchAttributeClusterDimension;
    at[n].val.clusterDim.x = cluster; at[n].val.clusterDim.y = 1; at[n].val.clusterDim.z = 1;
    n++;
  }
  if (pdl) {
    at[n].id = cudaLaunchAttributeProgrammaticStreamSerialization;
    at[n].val.programmaticStreamSerializationAllowed = 1;
    n++;
  }
  cfg.attrs = at;
  cfg.numAttrs = n;
  cudaLaunchKernelEx(&cfg, kern, KArgs(args)...);
}

extern "C" void kernel_launch(void* const* d_in, const int* in_sizes, int n_in, void* d_out, int out_size) {
  const bf16* x = (const bf16*)d_in[0];
  const bf16* wqkv = (const bf16*)d_in[1];
  const bf16* wo = (const bf16*)d_in[2];
  const bf16* wg = (const bf16*)d_in[4];
  const bf16* wu = (const bf16*)d_in[5];
  const bf16* wd = (const bf16*)d_in[6];
  bf16* out = (bf16*)d_out;

  static EncodeTiledFn enc = nullptr;
  static void *p_o = nullptr, *p_h = nullptr, *p_hh = nullptr, *p_xn = nullptr;
  if (!enc) {
    void* fn = nullptr;
    cudaDriverEntryPointQueryResult qr;
    cudaGetDriverEntryPoint("cuTensorMapEncodeTiled", &fn, cudaEnableDefault, &qr);
    enc = (EncodeTiledFn)fn;
    cudaGetSymbolAddress(&p_o, g_o);
    cudaGetSymbolAddress(&p_h, g_h);
    cudaGetSymbolAddress(&p_hh, g_hh);
    cudaGetSymbolAddress(&p_xn, g_xn);
    cudaFuncSetAttribute(qkv_kernel, cudaFuncAttributeMaxDynamicSharedMemorySize, KA_SMEM);
    cudaFuncSetAttribute(mlp_kernel, cudaFuncAttributeMaxDynamicSharedMemorySize, KC_SMEM);
    cudaFuncSetAttribute(attn_kernel, cudaFuncAttributeMaxDynamicSharedMemorySize, AT_SMEM);
  }
  CUtensorMap tm_wqkv, tm_wg, tm_wu, tm_wo64, tm_wo16, tm_wd64, tm_wd16, tm_o, tm_h, tm_hh, tm_hhs, tm_xn, tm_hs, tm_out;
  make_map(enc, &tm_wqkv, wqkv, DM, 3 * DM, 32, 64, CU_TENSOR_MAP_SWIZZLE_128B);
  make_map(enc, &tm_wg, wg, DM, FF, 32, 64, CU_TENSOR_MAP_SWIZZLE_128B);
  make_map(enc, &tm_wu, wu, DM, FF, 32, 64, CU_TENSOR_MAP_SWIZZLE_128B);
  make_map(enc, &tm_wo64, wo, DM, DM, 32, 64, CU_TENSOR_MAP_SWIZZLE_128B);
  make_map(enc, &tm_wo16, wo, DM, DM, 32, 16, CU_TENSOR_MAP_SWIZZLE_32B);
  make_map(enc, &tm_wd64, wd, FF, DM, 32, 64, CU_TENSOR_MAP_SWIZZLE_128B);
  make_map(enc, &tm_wd16, wd, FF, DM, 32, 16, CU_TENSOR_MAP_SWIZZLE_32B);
  make_map(enc, &tm_o, p_o, SEQ, DM, 128, 64, CU_TENSOR_MAP_SWIZZLE_128B);
  make_map(enc, &tm_h, p_h, SEQ, DM, 128, 32, CU_TENSOR_MAP_SWIZZLE_64B);
  make_map(enc, &tm_hh, p_hh, SEQ, FF, 128, 64, CU_TENSOR_MAP_SWIZZLE_128B);
  make_map(enc, &tm_hhs, p_hh, SEQ, FF, 64, 64, CU_TENSOR_MAP_SWIZZLE_128B);
  make_map(enc, &tm_xn, p_xn, SEQ, DM, 128, 32, CU_TENSOR_MAP_SWIZZLE_64B);
  make_map(enc, &tm_hs, p_h, SEQ, DM, 64, 80, CU_TENSOR_MAP_SWIZZLE_NONE);
  make_map(enc, &tm_out, out, SEQ, DM, 64, 80, CU_TENSOR_MAP_SWIZZLE_NONE);

  launch(qkv_kernel, 128, GT, KA_SMEM, 2, false, tm_xn, tm_wqkv, x);
  launch(attn_kernel, 132, AT_THREADS, AT_SMEM, 1, true, wo, wg, wu, wd);
  launch(mlp_kernel, 128, GT, KC_SMEM, 2, true, tm_o, tm_wo64, tm_wo16, tm_h, tm_wg, tm_wu, tm_hhs, tm_hh, tm_wd64, tm_wd16, tm_hs, tm_out, x);
}
```

```cpp
#include <cuda_runtime.h>
#include <cuda_bf16.h>
#include <cuda.h>
#include <stdint.h>

typedef __nv_bfloat16 bf16;
#define FLAGV 0

constexpr int SEQ = 2048, DM = 640, NH = 32, DH = 20, FF = 1536;
constexpr float ATT_SCALE_LOG2E = 0.22360679774997896f * 1.4426950408889634f;
constexpr int IMG_HEAD_ELEMS = (SEQ / 8) * 192;

__device__ __align__(1024) bf16 g_img[3 * NH * IMG_HEAD_ELEMS];
__device__ __align__(1024) bf16 g_o[SEQ * DM];
__device__ __align__(1024) bf16 g_h[SEQ * DM];
__device__ __align__(1024) bf16 g_xn[SEQ * DM];
__device__ float2 g_stats[SEQ * 8];
__device__ float g_cs[2 * FF];
__device__ int g_flag[3 * 16];
__device__ __align__(1024) bf16 g_hh[SEQ * FF];

#define TS(k, i)
#define PH(w, t, i)
__device__ __forceinline__ uint32_t smem_u32(const void* p) { return (uint32_t)__cvta_generic_to_shared(p); }
__device__ __forceinline__ void mbar_init(uint32_t bar, uint32_t cnt) {
  asm volatile("mbarrier.init.shared::cta.b64 [%0], %1;" ::"r"(bar), "r"(cnt) : "memory");
}
__device__ __forceinline__ void mbar_expect_tx(uint32_t bar, uint32_t bytes) {
  asm volatile("mbarrier.arrive.expect_tx.shared::cta.b64 _, [%0], %1;" ::"r"(bar), "r"(bytes) : "memory");
}
__device__ __forceinline__ void mbar_arrive(uint32_t bar) {
  asm volatile("mbarrier.arrive.shared::cta.b64 _, [%0];" ::"r"(bar) : "memory");
}
__device__ __forceinline__ void mbar_arrive_cluster(uint32_t bar, uint32_t cta) {
  asm volatile(
      "{\n.reg .b32 r;\nmapa.shared::cluster.u32 r, %0, %1;\n"
      "mbarrier.arrive.shared::cluster.b64 _, [r];\n}\n" ::"r"(bar), "r"(cta)
      : "memory");
}
__device__ __forceinline__ void mbar_wait(uint32_t bar, uint32_t parity) {
  asm volatile(
      "{\n.reg .pred p;\nLAB_WAIT:\n"
      "mbarrier.try_wait.parity.shared::cta.b64 p, [%0], %1;\n"
      "@p bra DONE;\nbra LAB_WAIT;\nDONE:\n}\n" ::"r"(bar), "r"(parity)
      : "memory");
}
__device__ __forceinline__ void mbar_wait_cluster(uint32_t bar, uint32_t parity) {
  asm volatile(
      "{\n.reg .pred p;\nLAB_WAIT:\n"
      "mbarrier.try_wait.parity.acquire.cluster.shared::cta.b64 p, [%0], %1;\n"
      "@p bra DONE;\nbra LAB_WAIT;\nDONE:\n}\n" ::"r"(bar), "r"(parity)
      : "memory");
}
__device__ __forceinline__ void fence_mbar_init() { asm volatile("fence.mbarrier_init.release.cluster;" ::: "memory"); }
__device__ __forceinline__ void fence_proxy_async() { asm volatile("fence.proxy.async.shared::cta;" ::: "memory"); }
__device__ __forceinline__ void cluster_sync_all() {
  asm volatile("barrier.cluster.arrive.release.aligned;\nbarrier.cluster.wait.acquire.aligned;" ::: "memory");
}
__device__ __forceinline__ void cluster_sync_relaxed() {
  asm volatile("barrier.cluster.arrive.relaxed.aligned;\nbarrier.cluster.wait.aligned;" ::: "memory");
}
__device__ __forceinline__ void named_bar_sync(int id, int n) { asm volatile("bar.sync %0, %1;" ::"r"(id), "r"(n) : "memory"); }
__device__ __forceinline__ bool wg_any(bool pred, int id) {
  uint32_t r;
  asm volatile("{\n.reg .pred p, q;\nsetp.ne.u32 p, %1, 0;\nbar.red.or.pred q, %2, 128, p;\nselp.u32 %0, 1, 0, q;\n}\n" : "=r"(r) : "r"((uint32_t)pred), "r"(id) : "memory");
  return r != 0;
}
__device__ __forceinline__ void fence_proxy_async_all() { asm volatile("fence.proxy.async;" ::: "memory"); }
__device__ __forceinline__ void flag_signal(int* f) {
  __threadfence();
  atomicAdd(f, 1);
}
__device__ __forceinline__ void flag_wait(const int* f, int target) {
  int v;
  unsigned spins = 0;
  do {
    asm volatile("ld.acquire.gpu.global.s32 %0, [%1];" : "=r"(v) : "l"(f) : "memory");
    if (++spins > (1u << 24)) __trap();
  } while (v < target);
}
__device__ __forceinline__ void pdl_launch() { asm volatile("griddepcontrol.launch_dependents;" ::: "memory"); }
__device__ __forceinline__ void pdl_wait() { asm volatile("griddepcontrol.wait;" ::: "memory"); }

__device__ __forceinline__ void tma_load_2d(uint32_t dst, const CUtensorMap* tm, int c0, int c1, uint32_t bar) {
  asm volatile(
      "cp.async.bulk.tensor.2d.shared::cluster.global.mbarrier::complete_tx::bytes [%0], [%1, {%3, %4}], [%2];" ::"r"(dst),
      "l"((uint64_t)tm), "r"(bar), "r"(c0), "r"(c1)
      : "memory");
}
__device__ __forceinline__ void tma_load_2d_mc(uint32_t dst, const CUtensorMap* tm, int c0, int c1, uint32_t bar, uint16_t mask) {
  asm volatile(
      "cp.async.bulk.tensor.2d.shared::cluster.global.mbarrier::complete_tx::bytes.multicast::cluster [%0], [%1, {%3, %4}], [%2], %5;" ::"r"(dst),
      "l"((uint64_t)tm), "r"(bar), "r"(c0), "r"(c1), "h"(mask)
      : "memory");
}
__device__ __forceinline__ void bulk_g2s(uint32_t dst, const void* src, uint32_t bytes, uint32_t bar) {
  asm volatile("cp.async.bulk.shared::cluster.global.mbarrier::complete_tx::bytes [%0], [%1], %2, [%3];" ::"r"(dst), "l"(src),
               "r"(bytes), "r"(bar)
               : "memory");
}
__device__ __forceinline__ void bulk_s2g(void* dst, uint32_t src, uint32_t bytes) {
  asm volatile("cp.async.bulk.global.shared::cta.bulk_group [%0], [%1], %2;" ::"l"(dst), "r"(src), "r"(bytes) : "memory");
}
__device__ __forceinline__ void tma_store_2d(const CUtensorMap* tm, uint32_t src, int c0, int c1) {
  asm volatile("cp.async.bulk.tensor.2d.global.shared::cta.bulk_group [%0, {%2, %3}], [%1];" ::"l"((uint64_t)tm), "r"(src), "r"(c0), "r"(c1) : "memory");
}
__device__ __forceinline__ void bulk_commit() { asm volatile("cp.async.bulk.commit_group;" ::: "memory"); }
__device__ __forceinline__ void bulk_wait_read() { asm volatile("cp.async.bulk.wait_group.read 0;" ::: "memory"); }
__device__ __forceinline__ void prefetch_l2(const void* p, uint32_t bytes) {
  asm volatile("cp.async.bulk.prefetch.L2.global [%0], %1;" ::"l"(p), "r"(bytes) : "memory");
}
__device__ __forceinline__ void bulk_wait_all() { asm volatile("cp.async.bulk.wait_group 0;" ::: "memory"); }
__device__ __forceinline__ void st_shared_b32(uint32_t addr, uint32_t v) { asm volatile("st.shared.b32 [%0], %1;" ::"r"(addr), "r"(v) : "memory"); }
__device__ __forceinline__ void st_shared_v2(uint32_t addr, uint32_t a, uint32_t b) { asm volatile("st.shared.v2.b32 [%0], {%1, %2};" ::"r"(addr), "r"(a), "r"(b) : "memory"); }
__device__ __forceinline__ void prefetch_tmap(const CUtensorMap* tm) {
  asm volatile("prefetch.tensormap [%0];" ::"l"((uint64_t)tm) : "memory");
}
__device__ __forceinline__ void wgmma_fence() { asm volatile("wgmma.fence.sync.aligned;" ::: "memory"); }
__device__ __forceinline__ void wgmma_commit() { asm volatile("wgmma.commit_group.sync.aligned;" ::: "memory"); }
template <int N>
__device__ __forceinline__ void wgmma_wait() { asm volatile("wgmma.wait_group.sync.aligned %0;" ::"n"(N) : "memory"); }

template <int N>
__device__ __forceinline__ void fence_regs(float (&r)[N]) {
#pragma unroll
  for (int i = 0; i < N; i++) asm volatile("" : "+f"(r[i])::"memory");
}
template <int N>
__device__ __forceinline__ void fence_regs(uint32_t (&r)[N]) {
#pragma unroll
  for (int i = 0; i < N; i++) asm volatile("" : "+r"(r[i])::"memory");
}
__device__ __forceinline__ uint64_t make_desc(uint32_t addr, uint32_t lbo, uint32_t sbo, uint32_t layout) {
  return (uint64_t)((addr & 0x3FFFF) >> 4) | ((uint64_t)((lbo & 0x3FFFF) >> 4) << 16) | ((uint64_t)((sbo & 0x3FFFF) >> 4) << 32) |
         ((uint64_t)layout << 62);
}
__device__ __forceinline__ uint32_t pack_bf16(float lo, float hi) {
  uint32_t r;
  asm("cvt.rn.bf16x2.f32 %0, %1, %2;" : "=r"(r) : "f"(hi), "f"(lo));
  return r;
}
__device__ __forceinline__ float bf16_round(float x) { return __bfloat162float(__float2bfloat16_rn(x)); }
__device__ __forceinline__ float bf_lo(uint32_t u) { return __uint_as_float(u << 16); }
__device__ __forceinline__ float bf_hi(uint32_t u) { return __uint_as_float(u & 0xffff0000u); }
__device__ __forceinline__ float ex2(float x) {
  float y;
  asm("ex2.approx.ftz.f32 %0, %1;" : "=f"(y) : "f"(x));
  return y;
}

__device__ __forceinline__ void wgmma_ss_n240_tb(float (&d)[120], uint64_t descA, uint64_t descB, int scaleD) {
  asm volatile("{\n.reg .pred p;\nsetp.ne.b32 p, %122, 0;\n"
    "wgmma.mma_async.sync.aligned.m64n240k16.f32.bf16.bf16 {%0, %1, %2, %3, %4, %5, %6, %7, %8, %9, %10, %11, %12, %13, %14, %15, %16, %17, %18, %19, %20, %21, %22, %23, %24, %25, %26, %27, %28, %29, %30, %31, %32, %33, %34, %35, %36, %37, %38, %39, %40, %41, %42, %43, %44, %45, %46, %47, %48, %49, %50, %51, %52, %53, %54, %55, %56, %57, %58, %59, %60, %61, %62, %63, %64, %65, %66, %67, %68, %69, %70, %71, %72, %73, %74, %75, %76, %77, %78, %79, %80, %81, %82, %83, %84, %85, %86, %87, %88, %89, %90, %91, %92, %93, %94, %95, %96, %97, %98, %99, %100, %101, %102, %103, %104, %105, %106, %107, %108, %109, %110, %111, %112, %113, %114, %115, %116, %117, %118, %119}, %120, %121, p, 1, 1, 0, 1;\n}\n"
    : "+f"(d[0]), "+f"(d[1]), "+f"(d[2]), "+f"(d[3]), "+f"(d[4]), "+f"(d[5]), "+f"(d[6]), "+f"(d[7]), "+f"(d[8]), "+f"(d[9]), "+f"(d[10]), "+f"(d[11]), "+f"(d[12]), "+f"(d[13]), "+f"(d[14]), "+f"(d[15]), "+f"(d[16]), "+f"(d[17]), "+f"(d[18]), "+f"(d[19]), "+f"(d[20]), "+f"(d[21]), "+f"(d[22]), "+f"(d[23]), "+f"(d[24]), "+f"(d[25]), "+f"(d[26]), "+f"(d[27]), "+f"(d[28]), "+f"(d[29]), "+f"(d[30]), "+f"(d[31]), "+f"(d[32]), "+f"(d[33]), "+f"(d[34]), "+f"(d[35]), "+f"(d[36]), "+f"(d[37]), "+f"(d[38]), "+f"(d[39]), "+f"(d[40]), "+f"(d[41]), "+f"(d[42]), "+f"(d[43]), "+f"(d[44]), "+f"(d[45]), "+f"(d[46]), "+f"(d[47]), "+f"(d[48]), "+f"(d[49]), "+f"(d[50]), "+f"(d[51]), "+f"(d[52]), "+f"(d[53]), "+f"(d[54]), "+f"(d[55]), "+f"(d[56]), "+f"(d[57]), "+f"(d[58]), "+f"(d[59]), "+f"(d[60]), "+f"(d[61]), "+f"(d[62]), "+f"(d[63]), "+f"(d[64]), "+f"(d[65]), "+f"(d[66]), "+f"(d[67]), "+f"(d[68]), "+f"(d[69]), "+f"(d[70]), "+f"(d[71]), "+f"(d[72]), "+f"(d[73]), "+f"(d[74]), "+f"(d[75]), "+f"(d[76]), "+f"(d[77]), "+f"(d[78]), "+f"(d[79]), "+f"(d[80]), "+f"(d[81]), "+f"(d[82]), "+f"(d[83]), "+f"(d[84]), "+f"(d[85]), "+f"(d[86]), "+f"(d[87]), "+f"(d[88]), "+f"(d[89]), "+f"(d[90]), "+f"(d[91]), "+f"(d[92]), "+f"(d[93]), "+f"(d[94]), "+f"(d[95]), "+f"(d[96]), "+f"(d[97]), "+f"(d[98]), "+f"(d[99]), "+f"(d[100]), "+f"(d[101]), "+f"(d[102]), "+f"(d[103]), "+f"(d[104]), "+f"(d[105]), "+f"(d[106]), "+f"(d[107]), "+f"(d[108]), "+f"(d[109]), "+f"(d[110]), "+f"(d[111]), "+f"(d[112]), "+f"(d[113]), "+f"(d[114]), "+f"(d[115]), "+f"(d[116]), "+f"(d[117]), "+f"(d[118]), "+f"(d[119])
    : "l"(descA), "l"(descB), "r"(scaleD));
}
__device__ __forceinline__ void wgmma_ss_n192_tb(float (&d)[96], uint64_t descA, uint64_t descB, int scaleD) {
  asm volatile("{\n.reg .pred p;\nsetp.ne.b32 p, %98, 0;\n"
    "wgmma.mma_async.sync.aligned.m64n192k16.f32.bf16.bf16 {%0, %1, %2, %3, %4, %5, %6, %7, %8, %9, %10, %11, %12, %13, %14, %15, %16, %17, %18, %19, %20, %21, %22, %23, %24, %25, %26, %27, %28, %29, %30, %31, %32, %33, %34, %35, %36, %37, %38, %39, %40, %41, %42, %43, %44, %45, %46, %47, %48, %49, %50, %51, %52, %53, %54, %55, %56, %57, %58, %59, %60, %61, %62, %63, %64, %65, %66, %67, %68, %69, %70, %71, %72, %73, %74, %75, %76, %77, %78, %79, %80, %81, %82, %83, %84, %85, %86, %87, %88, %89, %90, %91, %92, %93, %94, %95}, %96, %97, p, 1, 1, 0, 1;\n}\n"
    : "+f"(d[0]), "+f"(d[1]), "+f"(d[2]), "+f"(d[3]), "+f"(d[4]), "+f"(d[5]), "+f"(d[6]), "+f"(d[7]), "+f"(d[8]), "+f"(d[9]), "+f"(d[10]), "+f"(d[11]), "+f"(d[12]), "+f"(d[13]), "+f"(d[14]), "+f"(d[15]), "+f"(d[16]), "+f"(d[17]), "+f"(d[18]), "+f"(d[19]), "+f"(d[20]), "+f"(d[21]), "+f"(d[22]), "+f"(d[23]), "+f"(d[24]), "+f"(d[25]), "+f"(d[26]), "+f"(d[27]), "+f"(d[28]), "+f"(d[29]), "+f"(d[30]), "+f"(d[31]), "+f"(d[32]), "+f"(d[33]), "+f"(d[34]), "+f"(d[35]), "+f"(d[36]), "+f"(d[37]), "+f"(d[38]), "+f"(d[39]), "+f"(d[40]), "+f"(d[41]), "+f"(d[42]), "+f"(d[43]), "+f"(d[44]), "+f"(d[45]), "+f"(d[46]), "+f"(d[47]), "+f"(d[48]), "+f"(d[49]), "+f"(d[50]), "+f"(d[51]), "+f"(d[52]), "+f"(d[53]), "+f"(d[54]), "+f"(d[55]), "+f"(d[56]), "+f"(d[57]), "+f"(d[58]), "+f"(d[59]), "+f"(d[60]), "+f"(d[61]), "+f"(d[62]), "+f"(d[63]), "+f"(d[64]), "+f"(d[65]), "+f"(d[66]), "+f"(d[67]), "+f"(d[68]), "+f"(d[69]), "+f"(d[70]), "+f"(d[71]), "+f"(d[72]), "+f"(d[73]), "+f"(d[74]), "+f"(d[75]), "+f"(d[76]), "+f"(d[77]), "+f"(d[78]), "+f"(d[79]), "+f"(d[80]), "+f"(d[81]), "+f"(d[82]), "+f"(d[83]), "+f"(d[84]), "+f"(d[85]), "+f"(d[86]), "+f"(d[87]), "+f"(d[88]), "+f"(d[89]), "+f"(d[90]), "+f"(d[91]), "+f"(d[92]), "+f"(d[93]), "+f"(d[94]), "+f"(d[95])
    : "l"(descA), "l"(descB), "r"(scaleD));
}
__device__ __forceinline__ void wgmma_ss_n64_tb(float (&d)[32], uint64_t descA, uint64_t descB, int scaleD) {
  asm volatile("{\n.reg .pred p;\nsetp.ne.b32 p, %34, 0;\n"
    "wgmma.mma_async.sync.aligned.m64n64k16.f32.bf16.bf16 {%0, %1, %2, %3, %4, %5, %6, %7, %8, %9, %10, %11, %12, %13, %14, %15, %16, %17, %18, %19, %20, %21, %22, %23, %24, %25, %26, %27, %28, %29, %30, %31}, %32, %33, p, 1, 1, 0, 1;\n}\n"
    : "+f"(d[0]), "+f"(d[1]), "+f"(d[2]), "+f"(d[3]), "+f"(d[4]), "+f"(d[5]), "+f"(d[6]), "+f"(d[7]), "+f"(d[8]), "+f"(d[9]), "+f"(d[10]), "+f"(d[11]), "+f"(d[12]), "+f"(d[13]), "+f"(d[14]), "+f"(d[15]), "+f"(d[16]), "+f"(d[17]), "+f"(d[18]), "+f"(d[19]), "+f"(d[20]), "+f"(d[21]), "+f"(d[22]), "+f"(d[23]), "+f"(d[24]), "+f"(d[25]), "+f"(d[26]), "+f"(d[27]), "+f"(d[28]), "+f"(d[29]), "+f"(d[30]), "+f"(d[31])
    : "l"(descA), "l"(descB), "r"(scaleD));
}
__device__ __forceinline__ void wgmma_ss_n16_tb(float (&d)[8], uint64_t descA, uint64_t descB, int scaleD) {
  asm volatile("{\n.reg .pred p;\nsetp.ne.b32 p, %10, 0;\n"
    "wgmma.mma_async.sync.aligned.m64n16k16.f32.bf16.bf16 {%0, %1, %2, %3, %4, %5, %6, %7}, %8, %9, p, 1, 1, 0, 1;\n}\n"
    : "+f"(d[0]), "+f"(d[1]), "+f"(d[2]), "+f"(d[3]), "+f"(d[4]), "+f"(d[5]), "+f"(d[6]), "+f"(d[7])
    : "l"(descA), "l"(descB), "r"(scaleD));
}
__device__ __forceinline__ void wgmma_rs_n128(float (&d)[64], uint32_t a0, uint32_t a1, uint32_t a2, uint32_t a3, uint64_t descB, int scaleD) {
  asm volatile("{\n.reg .pred p;\nsetp.ne.b32 p, %69, 0;\n"
    "wgmma.mma_async.sync.aligned.m64n128k16.f32.bf16.bf16 {%0, %1, %2, %3, %4, %5, %6, %7, %8, %9, %10, %11, %12, %13, %14, %15, %16, %17, %18, %19, %20, %21, %22, %23, %24, %25, %26, %27, %28, %29, %30, %31, %32, %33, %34, %35, %36, %37, %38, %39, %40, %41, %42, %43, %44, %45, %46, %47, %48, %49, %50, %51, %52, %53, %54, %55, %56, %57, %58, %59, %60, %61, %62, %63}, {%64, %65, %66, %67}, %68, p, 1, 1, 0;\n}\n"
    : "+f"(d[0]), "+f"(d[1]), "+f"(d[2]), "+f"(d[3]), "+f"(d[4]), "+f"(d[5]), "+f"(d[6]), "+f"(d[7]), "+f"(d[8]), "+f"(d[9]), "+f"(d[10]), "+f"(d[11]), "+f"(d[12]), "+f"(d[13]), "+f"(d[14]), "+f"(d[15]), "+f"(d[16]), "+f"(d[17]), "+f"(d[18]), "+f"(d[19]), "+f"(d[20]), "+f"(d[21]), "+f"(d[22]), "+f"(d[23]), "+f"(d[24]), "+f"(d[25]), "+f"(d[26]), "+f"(d[27]), "+f"(d[28]), "+f"(d[29]), "+f"(d[30]), "+f"(d[31]), "+f"(d[32]), "+f"(d[33]), "+f"(d[34]), "+f"(d[35]), "+f"(d[36]), "+f"(d[37]), "+f"(d[38]), "+f"(d[39]), "+f"(d[40]), "+f"(d[41]), "+f"(d[42]), "+f"(d[43]), "+f"(d[44]), "+f"(d[45]), "+f"(d[46]), "+f"(d[47]), "+f"(d[48]), "+f"(d[49]), "+f"(d[50]), "+f"(d[51]), "+f"(d[52]), "+f"(d[53]), "+f"(d[54]), "+f"(d[55]), "+f"(d[56]), "+f"(d[57]), "+f"(d[58]), "+f"(d[59]), "+f"(d[60]), "+f"(d[61]), "+f"(d[62]), "+f"(d[63])
    : "r"(a0), "r"(a1), "r"(a2), "r"(a3), "l"(descB), "r"(scaleD));
}
__device__ __forceinline__ void wgmma_rs_n64(float (&d)[32], uint32_t a0, uint32_t a1, uint32_t a2, uint32_t a3, uint64_t descB, int scaleD) {
  asm volatile("{\n.reg .pred p;\nsetp.ne.b32 p, %37, 0;\n"
    "wgmma.mma_async.sync.aligned.m64n64k16.f32.bf16.bf16 {%0, %1, %2, %3, %4, %5, %6, %7, %8, %9, %10, %11, %12, %13, %14, %15, %16, %17, %18, %19, %20, %21, %22, %23, %24, %25, %26, %27, %28, %29, %30, %31}, {%32, %33, %34, %35}, %36, p, 1, 1, 0;\n}\n"
    : "+f"(d[0]), "+f"(d[1]), "+f"(d[2]), "+f"(d[3]), "+f"(d[4]), "+f"(d[5]), "+f"(d[6]), "+f"(d[7]), "+f"(d[8]), "+f"(d[9]), "+f"(d[10]), "+f"(d[11]), "+f"(d[12]), "+f"(d[13]), "+f"(d[14]), "+f"(d[15]), "+f"(d[16]), "+f"(d[17]), "+f"(d[18]), "+f"(d[19]), "+f"(d[20]), "+f"(d[21]), "+f"(d[22]), "+f"(d[23]), "+f"(d[24]), "+f"(d[25]), "+f"(d[26]), "+f"(d[27]), "+f"(d[28]), "+f"(d[29]), "+f"(d[30]), "+f"(d[31])
    : "r"(a0), "r"(a1), "r"(a2), "r"(a3), "l"(descB), "r"(scaleD));
}
__device__ __forceinline__ void wgmma_rs_n24_tb(float (&d)[12], uint32_t a0, uint32_t a1, uint32_t a2, uint32_t a3, uint64_t descB, int scaleD) {
  asm volatile("{\n.reg .pred p;\nsetp.ne.b32 p, %17, 0;\n"
    "wgmma.mma_async.sync.aligned.m64n24k16.f32.bf16.bf16 {%0, %1, %2, %3, %4, %5, %6, %7, %8, %9, %10, %11}, {%12, %13, %14, %15}, %16, p, 1, 1, 1;\n}\n"
    : "+f"(d[0]), "+f"(d[1]), "+f"(d[2]), "+f"(d[3]), "+f"(d[4]), "+f"(d[5]), "+f"(d[6]), "+f"(d[7]), "+f"(d[8]), "+f"(d[9]), "+f"(d[10]), "+f"(d[11])
    : "r"(a0), "r"(a1), "r"(a2), "r"(a3), "l"(descB), "r"(scaleD));
}

constexpr int GT = 384;

__device__ __forceinline__ void release_stage(uint32_t bar, bool leader) {
  if (leader) {
    mbar_arrive_cluster(bar, 0);
    mbar_arrive_cluster(bar, 1);
  }
}

__device__ __forceinline__ void ln_row(const bf16* __restrict__ xin, bf16* __restrict__ xout, int l16) {
  const uint4* src = reinterpret_cast<const uint4*>(xin);
  uint4 v[5];
#pragma unroll
  for (int j = 0; j < 5; j++) v[j] = __ldg(src + j * 16 + l16);
  float s0 = 0.f, s1 = 0.f, s2 = 0.f, s3 = 0.f;
#pragma unroll
  for (int j = 0; j < 5; j++) {
    s0 += bf_lo(v[j].x) + bf_hi(v[j].x);
    s1 += bf_lo(v[j].y) + bf_hi(v[j].y);
    s2 += bf_lo(v[j].z) + bf_hi(v[j].z);
    s3 += bf_lo(v[j].w) + bf_hi(v[j].w);
  }
  float mean = (s0 + s1) + (s2 + s3);
#pragma unroll
  for (int o = 1; o < 16; o <<= 1) mean += __shfl_xor_sync(0xffffffffu, mean, o);
  mean *= (1.0f / DM);
  s0 = s1 = s2 = s3 = 0.f;
#pragma unroll
  for (int j = 0; j < 5; j++) {
    float d;
    d = bf_lo(v[j].x) - mean; s0 = fmaf(d, d, s0);
    d = bf_hi(v[j].x) - mean; s1 = fmaf(d, d, s1);
    d = bf_lo(v[j].y) - mean; s2 = fmaf(d, d, s2);
    d = bf_hi(v[j].y) - mean; s3 = fmaf(d, d, s3);
    d = bf_lo(v[j].z) - mean; s0 = fmaf(d, d, s0);
    d = bf_hi(v[j].z) - mean; s1 = fmaf(d, d, s1);
    d = bf_lo(v[j].w) - mean; s2 = fmaf(d, d, s2);
    d = bf_hi(v[j].w) - mean; s3 = fmaf(d, d, s3);
  }
  float sq = (s0 + s1) + (s2 + s3);
#pragma unroll
  for (int o = 1; o < 16; o <<= 1) sq += __shfl_xor_sync(0xffffffffu, sq, o);
  const float var_b = bf16_round(sq * (1.0f / DM));
  const float den = bf16_round(sqrtf(bf16_round(var_b + 1e-5f)));
  const float iv = __frcp_rn(den);
  const float mb = bf16_round(mean);
  uint4* dst = reinterpret_cast<uint4*>(xout);
#pragma unroll
  for (int j = 0; j < 5; j++) {
    uint4 w;
    uint32_t t;
    t = pack_bf16(bf_lo(v[j].x) - mb, bf_hi(v[j].x) - mb); w.x = pack_bf16(bf_lo(t) * iv, bf_hi(t) * iv);
    t = pack_bf16(bf_lo(v[j].y) - mb, bf_hi(v[j].y) - mb); w.y = pack_bf16(bf_lo(t) * iv, bf_hi(t) * iv);
    t = pack_bf16(bf_lo(v[j].z) - mb, bf_hi(v[j].z) - mb); w.z = pack_bf16(bf_lo(t) * iv, bf_hi(t) * iv);
    t = pack_bf16(bf_lo(v[j].w) - mb, bf_hi(v[j].w) - mb); w.w = pack_bf16(bf_lo(t) * iv, bf_hi(t) * iv);
    dst[j * 16 + l16] = w;
  }
}

constexpr int LG_STAGES = 5;
constexpr int QKV_STAGE = 8192 + 4 * 4096;
constexpr int GLU_STAGE = 8192 + 6 * 4096;

template <int WG>
__device__ __forceinline__ void qkv_mainloop(float (&acc)[120], uint32_t sbase, uint32_t sBar, bool leader) {
  constexpr int STAGE_BYTES = QKV_STAGE, NST = LG_STAGES;
  const uint64_t da_base = make_desc(sbase + WG * 4096, 16, 512, 2);
  const uint64_t db_base = make_desc(sbase + 8192, 4096, 1024, 1);
#pragma unroll 1
  for (int r = 0; r < 20 / NST; r++) {
#pragma unroll
    for (int s = 0; s < NST; s++) {
      mbar_wait(sBar + 8 * s, r & 1);
      wgmma_fence();
#pragma unroll
      for (int ks = 0; ks < 2; ks++)
        wgmma_ss_n240_tb(acc, da_base + (uint64_t)((s * STAGE_BYTES + ks * 32) >> 4), db_base + (uint64_t)((s * STAGE_BYTES + ks * 2048) >> 4), 1);
      wgmma_commit();
      wgmma_wait<1>();
      release_stage(sBar + 8 * (NST + (s + NST - 1) % NST), leader && (s > 0 || r > 0));
    }
  }
}
template <int WG>
__device__ __forceinline__ void glu_mainloop(float (&accg)[96], float (&accu)[96], uint32_t sbase, uint32_t sBar, bool leader) {
  constexpr int STAGE_BYTES = GLU_STAGE, NST = LG_STAGES;
  const uint64_t da_base = make_desc(sbase + WG * 4096, 16, 512, 2);
  const uint64_t db_base = make_desc(sbase + 8192, 4096, 1024, 1);
#pragma unroll 1
  for (int r = 0; r < 20 / NST; r++) {
#pragma unroll
    for (int s = 0; s < NST; s++) {
      mbar_wait(sBar + 8 * s, r & 1);
      wgmma_fence();
#pragma unroll
      for (int ks = 0; ks < 2; ks++) {
        const uint64_t da = da_base + (uint64_t)((s * STAGE_BYTES + ks * 32) >> 4);
        wgmma_ss_n192_tb(accg, da, db_base + (uint64_t)((s * STAGE_BYTES + ks * 2048) >> 4), 1);
        wgmma_ss_n192_tb(accu, da, db_base + (uint64_t)((s * STAGE_BYTES + 3 * 4096 + ks * 2048) >> 4), 1);
      }
      wgmma_commit();
      wgmma_wait<1>();
      release_stage(sBar + 8 * (NST + (s + NST - 1) % NST), leader && (s > 0 || r > 0));
    }
  }
}
constexpr int RG_STAGE_BYTES = 16384 + 8192 + 2048;
template <int NKB, int NST, int WG>
__device__ __forceinline__ void res_mainloop(float (&acc0)[32], float (&acc1)[8], uint32_t sbase, uint32_t sBar, bool leader) {
  const uint64_t da_base = make_desc(sbase + WG * 8192, 16, 1024, 1);
  const uint64_t db0_base = make_desc(sbase + 16384, 8192, 1024, 1);
  const uint64_t db1_base = make_desc(sbase + 16384 + 8192, 2048, 256, 3);
#pragma unroll 1
  for (int r = 0; r < NKB / NST; r++) {
#pragma unroll
    for (int s = 0; s < NST; s++) {
      const uint64_t so = (uint64_t)(s * (RG_STAGE_BYTES >> 4));
      mbar_wait(sBar + 8 * s, r & 1);
      wgmma_fence();
#pragma unroll
      for (int ks = 0; ks < 4; ks++) {
        wgmma_ss_n64_tb(acc0, da_base + so + ks * 2, db0_base + so + ks * 128, 1);
        wgmma_ss_n16_tb(acc1, da_base + so + ks * 2, db1_base + so + ks * 32, 1);
      }
      wgmma_commit();
      wgmma_wait<1>();
      release_stage(sBar + 8 * (NST + (s + NST - 1) % NST), leader && (s > 0 || r > 0));
    }
  }
}

constexpr int KA_SMEM = LG_STAGES * QKV_STAGE + 128 + 1024;

__global__ void __launch_bounds__(GT, 1)
qkv_kernel(const __grid_constant__ CUtensorMap tmA, const __grid_constant__ CUtensorMap tmB, const bf16* __restrict__ x) {
  constexpr int STAGE_BYTES = QKV_STAGE, NST = LG_STAGES, NKB = 20;
  extern __shared__ uint8_t smem_raw[];
  const uint32_t sbase = (smem_u32(smem_raw) + 1023u) & ~1023u;
  const uint32_t sBar = sbase + NST * STAGE_BYTES;
  const int tid = threadIdx.x, warp = tid >> 5, lane = tid & 31;
  const int rank = blockIdx.x & 1;
  const int pair = blockIdx.x >> 1;
  const int n_blk = pair & 7;
  const int m_blk = (pair >> 3) * 2 + rank;
  TS(0, 0);
  if (tid == 256) {
    prefetch_tmap(&tmA);
    prefetch_tmap(&tmB);
  }
  if (tid == 0) {
    for (int s = 0; s < NST; s++) {
      mbar_init(sBar + 8 * s, 1);
      mbar_init(sBar + 8 * (NST + s), 4);
    }
    fence_mbar_init();
    if (blockIdx.x < 32) g_flag[16 + blockIdx.x] = 0;
  }
  pdl_launch();
  cluster_sync_all();

  if (warp >= 8) {
    asm volatile("setmaxnreg.dec.sync.aligned.u32 40;");
    if (warp == 9) {
      named_bar_sync(5, 288);
      if (lane == 0) flag_signal(&g_flag[m_blk]);
    }
    if (tid == 256) {
      auto issue_b = [&](int kb) {
        const int s = kb % NST;
        const uint32_t full = sBar + 8 * s;
        mbar_expect_tx(full, STAGE_BYTES);
        const uint32_t dst = sbase + s * STAGE_BYTES + 8192;
#pragma unroll
        for (int j = 0; j < 2; j++) {
          const int sl = rank * 2 + j;
          tma_load_2d_mc(dst + sl * 4096, &tmB, n_blk * 240 + sl * 64, kb * 32, full, (uint16_t)3);
        }
      };
      for (int kb = 0; kb < NST; kb++) issue_b(kb);
      flag_wait(&g_flag[m_blk], 8);
      fence_proxy_async_all();
      for (int kb = 0; kb < NKB; kb++) {
        const int s = kb % NST;
        if (kb >= NST) {
          mbar_wait(sBar + 8 * (NST + s), ((kb / NST) & 1) ^ 1);
          issue_b(kb);
        }
        tma_load_2d(sbase + s * STAGE_BYTES, &tmA, kb * 32, m_blk * 128, sBar + 8 * s);
      }
    }
  } else {
    asm volatile("setmaxnreg.inc.sync.aligned.u32 232;");
    const int wg = __shfl_sync(0xffffffffu, warp >> 2, 0);
    const int wwarp = warp & 3;
    {
      const int row = m_blk * 128 + n_blk * 16 + warp * 2 + (lane >> 4);
      ln_row(x + (size_t)row * DM, g_xn + (size_t)row * DM, lane & 15);
      asm volatile("bar.arrive 5, 288;" ::: "memory");
    }
    TS(0, 1);
    mbar_wait(sBar, 0);
    TS(0, 3);
    float acc[120];
#pragma unroll
    for (int i = 0; i < 120; i++) acc[i] = 0.f;
    if (wg == 0) qkv_mainloop<0>(acc, sbase, sBar, (tid & 127) == 0);
    else qkv_mainloop<1>(acc, sbase, sBar, (tid & 127) == 0);
    wgmma_wait<0>();
    fence_regs(acc);
    TS(0, 4);
    named_bar_sync(3, 256);
    const int g = lane >> 2, c4 = lane & 3;
    const uint32_t stg = sbase + wg * (12 * 3072) + (wwarp * 2) * 384 + g * 16;
    const int hbase = n_blk * 12;
#pragma unroll
    for (int j = 0; j < 30; j++) {
      const int cb = (j * 8) % 20;
      const int hb = (j * 8) / 20;
      int d = cb + c4 * 2;
      int hl = hb;
      if (cb == 16 && c4 >= 2) { d -= 20; hl += 1; }
      const uint32_t a0 = stg + hl * 3072 + (d >> 3) * 128 + (d & 7) * 2;
      const int hg = hbase + hl;
      const float sc = hg < 32 ? ATT_SCALE_LOG2E : 1.0f;
      st_shared_b32(a0, pack_bf16(acc[4 * j] * sc, acc[4 * j + 1] * sc));
      st_shared_b32(a0 + 384, pack_bf16(acc[4 * j + 2] * sc, acc[4 * j + 3] * sc));
      if (d == 18) {
        const uint32_t pad0 = hg < 32 ? 0u : (hg < 64 ? 0x3f803f80u : 0x00003f80u);
        const uint32_t pad1 = (hg >= 32 && hg < 64) ? 0x00003f80u : 0u;
        st_shared_v2(a0 + 4, pad0, pad1);
        st_shared_v2(a0 + 388, pad0, pad1);
      }
      if (j % 10 == 9) {
        fence_proxy_async();
        named_bar_sync(1 + wg, 128);
        if ((tid & 127) < 4) {
          const int hs = (j / 10) * 4 + (tid & 127);
          bf16* dst = g_img + (size_t)(hbase + hs) * IMG_HEAD_ELEMS + (size_t)(m_blk * 16 + wg * 8) * 192;
          bulk_s2g(dst, sbase + wg * (12 * 3072) + hs * 3072, 3072);
          bulk_commit();
        }
      }
    }
    if ((tid & 127) < 4) bulk_wait_read();
  }
  __syncwarp();
  TS(0, 5);
  cluster_sync_relaxed();
  TS(0, 6);
}

constexpr int KC_NST1 = 5, KC_NST3 = 6;
constexpr int KC_STAGING = 160 * 1024;
constexpr int KC_BAR = KC_STAGING + 48 * 1024;
constexpr int KC_CS = KC_BAR + 512;
constexpr int KC_SMEM = KC_CS + 1536 + 1024;

__global__ void __launch_bounds__(GT, 1)
mlp_kernel(const __grid_constant__ CUtensorMap tmO, const __grid_constant__ CUtensorMap tmWo64, const __grid_constant__ CUtensorMap tmWo16,
           const __grid_constant__ CUtensorMap tmH, const __grid_constant__ CUtensorMap tmWg, const __grid_constant__ CUtensorMap tmWu,
           const __grid_constant__ CUtensorMap tmHHs, const __grid_constant__ CUtensorMap tmHH, const __grid_constant__ CUtensorMap tmWd64,
           const __grid_constant__ CUtensorMap tmWd16, const __grid_constant__ CUtensorMap tmHs, const __grid_constant__ CUtensorMap tmOut,
           const bf16* __restrict__ x) {
  extern __shared__ uint8_t smem_raw[];
  const uint32_t sbase = (smem_u32(smem_raw) + 1023u) & ~1023u;
  const uint32_t bar1 = sbase + KC_BAR;
  const uint32_t bar2 = bar1 + 128;
  const uint32_t bar3 = bar2 + 128;
  const uint32_t barD = bar3 + 128;
  const int tid = threadIdx.x, warp = tid >> 5, lane = tid & 31;
  const int rank = blockIdx.x & 1;
  const int pair = blockIdx.x >> 1;
  const int j_blk = pair & 7;
  const int m_blk = (pair >> 3) * 2 + rank;
  const int n0 = j_blk * 80;
  TS(2, 0);
  if (tid == 256) {
    prefetch_tmap(&tmO); prefetch_tmap(&tmWo64); prefetch_tmap(&tmWo16); prefetch_tmap(&tmH); prefetch_tmap(&tmWg);
    prefetch_tmap(&tmWu); prefetch_tmap(&tmHHs); prefetch_tmap(&tmHH); prefetch_tmap(&tmWd64); prefetch_tmap(&tmWd16);
    prefetch_tmap(&tmHs); prefetch_tmap(&tmOut);
  }
  if (tid == 0) {
    for (int s = 0; s < 5; s++) {
      mbar_init(bar1 + 8 * s, 1); mbar_init(bar1 + 8 * (5 + s), 4);
      mbar_init(bar2 + 8 * s, 1); mbar_init(bar2 + 8 * (5 + s), 4);
    }
    for (int s = 0; s < 6; s++) { mbar_init(bar3 + 8 * s, 1); mbar_init(bar3 + 8 * (6 + s), 4); }
    mbar_init(barD, 4); mbar_init(barD + 8, 4);
    fence_mbar_init();
  }
  cluster_sync_all();

  if (warp >= 8) {
    asm volatile("setmaxnreg.dec.sync.aligned.u32 40;");
    if (tid == 256) {
      auto issue_b80 = [&](const CUtensorMap* t64, const CUtensorMap* t16, uint32_t bars, int nst, int kb) {
        const int s = kb % nst;
        const uint32_t full = bars + 8 * s;
        const uint32_t st = sbase + s * RG_STAGE_BYTES;
        mbar_expect_tx(full, RG_STAGE_BYTES);
        tma_load_2d_mc(st + 16384 + rank * 4096, t64, n0, kb * 64 + rank * 32, full, (uint16_t)3);
        tma_load_2d_mc(st + 16384 + 8192 + rank * 1024, t16, n0 + 64, kb * 64 + rank * 32, full, (uint16_t)3);
      };
      for (int kb = 0; kb < KC_NST1; kb++) issue_b80(&tmWo64, &tmWo16, bar1, KC_NST1, kb);
      pdl_wait();
      for (int kb = 0; kb < 10; kb++) {
        const int s = kb % KC_NST1;
        if (kb >= KC_NST1) {
          mbar_wait(bar1 + 8 * (KC_NST1 + s), ((kb / KC_NST1) & 1) ^ 1);
          issue_b80(&tmWo64, &tmWo16, bar1, KC_NST1, kb);
        }
        tma_load_2d(sbase + s * RG_STAGE_BYTES, &tmO, kb * 64, m_blk * 128, bar1 + 8 * s);
      }
      auto issue_bglu = [&](int kb) {
        const int s = kb % LG_STAGES;
        const uint32_t full = bar2 + 8 * s;
        mbar_expect_tx(full, GLU_STAGE);
        const uint32_t dst = sbase + s * GLU_STAGE + 8192;
#pragma unroll
        for (int j = 0; j < 3; j++)
          tma_load_2d_mc(dst + (rank * 3 + j) * 4096, rank == 0 ? &tmWg : &tmWu, j_blk * 192 + j * 64, kb * 32, full, (uint16_t)3);
      };
      mbar_wait(barD, 0);
      for (int kb = 0; kb < LG_STAGES; kb++) issue_bglu(kb);
      flag_wait(&g_flag[16 + m_blk], 16);
      fence_proxy_async_all();
      for (int kb = 0; kb < 20; kb++) {
        const int s = kb % LG_STAGES;
        if (kb >= LG_STAGES) {
          mbar_wait(bar2 + 8 * (LG_STAGES + s), ((kb / LG_STAGES) & 1) ^ 1);
          issue_bglu(kb);
        }
        tma_load_2d(sbase + s * GLU_STAGE, &tmH, kb * 32, m_blk * 128, bar2 + 8 * s);
      }
      mbar_wait(barD + 8, 0);
      for (int kb = 0; kb < KC_NST3; kb++) issue_b80(&tmWd64, &tmWd16, bar3, KC_NST3, kb);
      flag_wait(&g_flag[32 + m_blk], 16);
      fence_proxy_async_all();
      for (int kb = 0; kb < 24; kb++) {
        const int s = kb % KC_NST3;
        if (kb >= KC_NST3) {
          mbar_wait(bar3 + 8 * (KC_NST3 + s), ((kb / KC_NST3) & 1) ^ 1);
          issue_b80(&tmWd64, &tmWd16, bar3, KC_NST3, kb);
        }
        tma_load_2d(sbase + s * RG_STAGE_BYTES, &tmHH, kb * 64, m_blk * 128, bar3 + 8 * s);
      }
    }
  } else {
    asm volatile("setmaxnreg.inc.sync.aligned.u32 232;");
    const int wg = __shfl_sync(0xffffffffu, warp >> 2, 0);
    const int wwarp = warp & 3;
    const int g = lane >> 2, c4 = lane & 3;
    const int row0 = m_blk * 128 + wg * 64 + wwarp * 16 + g;
    const bool leader = (tid & 127) == 0;
    const uint32_t stg80_base = sbase + KC_STAGING + wg * 24576;
    const uint32_t stg80 = stg80_base + (wwarp * 16 + g) * 160 + c4 * 4;
    {
      uint32_t res[20];
#pragma unroll
      for (int j = 0; j < 10; j++) {
        res[2 * j] = __ldg(reinterpret_cast<const uint32_t*>(x + (size_t)row0 * DM + n0 + j * 8 + c4 * 2));
        res[2 * j + 1] = __ldg(reinterpret_cast<const uint32_t*>(x + (size_t)(row0 + 8) * DM + n0 + j * 8 + c4 * 2));
      }
      float acc0[32], acc1[8];
#pragma unroll
      for (int i = 0; i < 32; i++) acc0[i] = 0.f;
#pragma unroll
      for (int i = 0; i < 8; i++) acc1[i] = 0.f;
      TS(2, 1);
      if (wg == 0) res_mainloop<10, KC_NST1, 0>(acc0, acc1, sbase, bar1, leader);
      else res_mainloop<10, KC_NST1, 1>(acc0, acc1, sbase, bar1, leader);
      wgmma_wait<0>();
      fence_regs(acc0); fence_regs(acc1);
      release_stage(barD, leader);
      TS(2, 4);
      float sum0 = 0.f, sum1 = 0.f;
#pragma unroll
      for (int j = 0; j < 10; j++) {
        const uint32_t a01 = j < 8 ? pack_bf16(acc0[4 * j], acc0[4 * j + 1]) : pack_bf16(acc1[4 * (j - 8)], acc1[4 * (j - 8) + 1]);
        const uint32_t a23 = j < 8 ? pack_bf16(acc0[4 * j + 2], acc0[4 * j + 3]) : pack_bf16(acc1[4 * (j - 8) + 2], acc1[4 * (j - 8) + 3]);
        res[2 * j] = pack_bf16(bf_lo(res[2 * j]) + bf_lo(a01), bf_hi(res[2 * j]) + bf_hi(a01));
        res[2 * j + 1] = pack_bf16(bf_lo(res[2 * j + 1]) + bf_lo(a23), bf_hi(res[2 * j + 1]) + bf_hi(a23));
        st_shared_b32(stg80 + j * 16, res[2 * j]);
        st_shared_b32(stg80 + 8 * 160 + j * 16, res[2 * j + 1]);
        sum0 += bf_lo(res[2 * j]) + bf_hi(res[2 * j]);
        sum1 += bf_lo(res[2 * j + 1]) + bf_hi(res[2 * j + 1]);
      }
      sum0 += __shfl_xor_sync(0xffffffffu, sum0, 1); sum1 += __shfl_xor_sync(0xffffffffu, sum1, 1);
      sum0 += __shfl_xor_sync(0xffffffffu, sum0, 2); sum1 += __shfl_xor_sync(0xffffffffu, sum1, 2);
      const float mu0 = sum0 * (1.0f / 80.0f), mu1 = sum1 * (1.0f / 80.0f);
      float q0 = 0.f, q1 = 0.f;
#pragma unroll
      for (int j = 0; j < 10; j++) {
        float d;
        d = bf_lo(res[2 * j]) - mu0; q0 = fmaf(d, d, q0);
        d = bf_hi(res[2 * j]) - mu0; q0 = fmaf(d, d, q0);
        d = bf_lo(res[2 * j + 1]) - mu1; q1 = fmaf(d, d, q1);
        d = bf_hi(res[2 * j + 1]) - mu1; q1 = fmaf(d, d, q1);
      }
      q0 += __shfl_xor_sync(0xffffffffu, q0, 1); q1 += __shfl_xor_sync(0xffffffffu, q1, 1);
      q0 += __shfl_xor_sync(0xffffffffu, q0, 2); q1 += __shfl_xor_sync(0xffffffffu, q1, 2);
      if (c4 == 0) {
        g_stats[row0 * 8 + j_blk] = make_float2(mu0, q0);
        g_stats[(row0 + 8) * 8 + j_blk] = make_float2(mu1, q1);
      }
      fence_proxy_async();
      named_bar_sync(1 + wg, 128);
      if (leader) {
        tma_store_2d(&tmHs, stg80_base, n0, m_blk * 128 + wg * 64);
        bulk_commit();
        bulk_wait_all();
        fence_proxy_async_all();
        flag_signal(&g_flag[16 + m_blk]);
      }
      TS(2, 5);
    }
    {
      pdl_wait();
      {
        float* cs_s = reinterpret_cast<float*>(smem_raw + (sbase - smem_u32(smem_raw)) + KC_CS);
        for (int i = tid; i < 384; i += 256) cs_s[i] = g_cs[(i >= 192 ? FF - 192 : 0) + j_blk * 192 + i];
        named_bar_sync(3, 256);
      }
      flag_wait(&g_flag[16 + m_blk], 16);
      float mb[2], iv[2];
#pragma unroll
      for (int h = 0; h < 2; h++) {
        const float4* sp = reinterpret_cast<const float4*>(g_stats + (row0 + 8 * h) * 8);
        const float4 p0 = sp[0], p1 = sp[1], p2 = sp[2], p3 = sp[3];
        const float mean = (((p0.x + p0.z) + (p1.x + p1.z)) + ((p2.x + p2.z) + (p3.x + p3.z))) * 0.125f;
        float m2 = ((p0.y + p0.w) + (p1.y + p1.w)) + ((p2.y + p2.w) + (p3.y + p3.w));
        float dd = 0.f, d;
        d = p0.x - mean; dd = fmaf(d, d, dd); d = p0.z - mean; dd = fmaf(d, d, dd);
        d = p1.x - mean; dd = fmaf(d, d, dd); d = p1.z - mean; dd = fmaf(d, d, dd);
        d = p2.x - mean; dd = fmaf(d, d, dd); d = p2.z - mean; dd = fmaf(d, d, dd);
        d = p3.x - mean; dd = fmaf(d, d, dd); d = p3.z - mean; dd = fmaf(d, d, dd);
        m2 = fmaf(dd, 80.0f, m2);
        const float var_b = bf16_round(m2 * (1.0f / DM));
        const float den = bf16_round(sqrtf(bf16_round(var_b + 1e-5f)));
        iv[h] = __frcp_rn(den);
        mb[h] = bf16_round(mean);
      }
      float accg[96], accu[96];
#pragma unroll
      for (int i = 0; i < 96; i++) { accg[i] = 0.f; accu[i] = 0.f; }
      TS(3, 3);
      if (wg == 0) glu_mainloop<0>(accg, accu, sbase, bar2, leader);
      else glu_mainloop<1>(accg, accu, sbase, bar2, leader);
      wgmma_wait<0>();
      fence_regs(accg); fence_regs(accu);
      release_stage(barD + 8, leader);
      TS(3, 4);
      const uint32_t stg = sbase + KC_STAGING + wg * 24576 + (wwarp * 16 + g) * 128 + c4 * 4;
      const float* csg = reinterpret_cast<const float*>(smem_raw + (sbase - smem_u32(smem_raw)) + KC_CS) + c4 * 2;
      const float nm0 = -mb[0] * iv[0], nm1 = -mb[1] * iv[1];
#pragma unroll
      for (int sl = 0; sl < 3; sl++) {
        float2 cgv[4], cuv[4];
#pragma unroll
        for (int jj = 0; jj < 8; jj++) {
          const int j = sl * 8 + jj;
          if ((jj & 3) == 0) {
#pragma unroll
            for (int q = 0; q < 4; q++) {
              cgv[q] = *reinterpret_cast<const float2*>(csg + (j + q) * 8);
              cuv[q] = *reinterpret_cast<const float2*>(csg + 192 + (j + q) * 8);
            }
          }
          const float2 cg = cgv[jj & 3], cu = cuv[jj & 3];
          const float r0 = fmaxf(fmaf(accg[4 * j], iv[0], nm0 * cg.x), 0.f) * fmaf(accu[4 * j], iv[0], nm0 * cu.x);
          const float r1 = fmaxf(fmaf(accg[4 * j + 1], iv[0], nm0 * cg.y), 0.f) * fmaf(accu[4 * j + 1], iv[0], nm0 * cu.y);
          const float r2 = fmaxf(fmaf(accg[4 * j + 2], iv[1], nm1 * cg.x), 0.f) * fmaf(accu[4 * j + 2], iv[1], nm1 * cu.x);
          const float r3 = fmaxf(fmaf(accg[4 * j + 3], iv[1], nm1 * cg.y), 0.f) * fmaf(accu[4 * j + 3], iv[1], nm1 * cu.y);
          const uint32_t a0 = stg + sl * 8192 + ((jj ^ g) << 4);
          st_shared_b32(a0, pack_bf16(r0, r1));
          st_shared_b32(a0 + 1024, pack_bf16(r2, r3));
        }
        fence_proxy_async();
        named_bar_sync(1 + wg, 128);
        if (leader) {
          tma_store_2d(&tmHHs, sbase + KC_STAGING + wg * 24576 + sl * 8192, j_blk * 192 + sl * 64, m_blk * 128 + wg * 64);
          bulk_commit();
        }
      }
      TS(3, 7);
      if (leader) {
        bulk_wait_all();
        TS(3, 8);
        fence_proxy_async_all();
        flag_signal(&g_flag[32 + m_blk]);
      }
      TS(3, 9);
    }
    {
      uint32_t res[20];
#pragma unroll
      for (int j = 0; j < 10; j++) {
        res[2 * j] = *reinterpret_cast<const uint32_t*>(g_h + (size_t)row0 * DM + n0 + j * 8 + c4 * 2);
        res[2 * j + 1] = *reinterpret_cast<const uint32_t*>(g_h + (size_t)(row0 + 8) * DM + n0 + j * 8 + c4 * 2);
      }
      float acc0[32], acc1[8];
#pragma unroll
      for (int i = 0; i < 32; i++) acc0[i] = 0.f;
#pragma unroll
      for (int i = 0; i < 8; i++) acc1[i] = 0.f;
      mbar_wait(bar3, 0);
      TS(4, 3);
      if (wg == 0) res_mainloop<24, KC_NST3, 0>(acc0, acc1, sbase, bar3, leader);
      else res_mainloop<24, KC_NST3, 1>(acc0, acc1, sbase, bar3, leader);
      wgmma_wait<0>();
      fence_regs(acc0); fence_regs(acc1);
      TS(4, 4);
#pragma unroll
      for (int j = 0; j < 10; j++) {
        const uint32_t a01 = j < 8 ? pack_bf16(acc0[4 * j], acc0[4 * j + 1]) : pack_bf16(acc1[4 * (j - 8)], acc1[4 * (j - 8) + 1]);
        const uint32_t a23 = j < 8 ? pack_bf16(acc0[4 * j + 2], acc0[4 * j + 3]) : pack_bf16(acc1[4 * (j - 8) + 2], acc1[4 * (j - 8) + 3]);
        st_shared_b32(stg80 + j * 16, pack_bf16(bf_lo(res[2 * j]) + bf_lo(a01), bf_hi(res[2 * j]) + bf_hi(a01)));
        st_shared_b32(stg80 + 8 * 160 + j * 16, pack_bf16(bf_lo(res[2 * j + 1]) + bf_lo(a23), bf_hi(res[2 * j + 1]) + bf_hi(a23)));
      }
      fence_proxy_async();
      named_bar_sync(1 + wg, 128);
      if (leader) {
        tma_store_2d(&tmOut, stg80_base, n0, m_blk * 128 + wg * 64);
        bulk_commit();
        bulk_wait_read();
      }
      TS(4, 5);
    }
  }
  __syncwarp();
  cluster_sync_relaxed();
  TS(4, 6);
}

constexpr int AT_THREADS = 512;
constexpr int AT_WGS = AT_THREADS / 128;
#define AT_CHUNK_MASK 3
#define AT_STAGGER 0
constexpr int AT_KV_BYTES = IMG_HEAD_ELEMS * 2;
constexpr int AT_SMEM = 2 * AT_KV_BYTES + 256 + 1024;
constexpr int AT_CHUNKS = 8;

__device__ __forceinline__ float exp2_poly(float x) {
  const float u = __saturatef(fmaf(x, 1.0f / 64.0f, 62.0f / 64.0f));
  const float MAGIC = 12582912.0f - 62.0f;
  const float r = fmaf(u, 64.0f, MAGIC);
  const float q = MAGIC - r;
  const float fr = fmaf(u, 64.0f, q);
  float p = fmaf(fr, 0.009570102207362652f, 0.05591785907745361f);
  p = fmaf(p, fr, 0.240247443318367f);
  p = fmaf(p, fr, 0.6931217908859253f);
  p = fmaf(p, fr, 0.9999992847442627f);
  return __uint_as_float(__float_as_uint(p) + (__float_as_uint(r) << 23));
}
#define AT_VARIANT 0
#define AT_POLY_MOD 8
__device__ __forceinline__ bool use_poly(int e) {
  return (e % AT_POLY_MOD) == 1;
}

struct AttnState {
  uint32_t qa0, qa1, qa2, qa3, qa4, qa5;
  float M0, M1;
};

__device__ __forceinline__ bool attn_exp_fast(const float (&s)[32], uint32_t (&p)[16]) {
#pragma unroll
  for (int j = 0; j < 16; j++) {
    const float e0 = use_poly(2 * j) ? exp2_poly(s[2 * j]) : ex2(s[2 * j]);
    const float e1 = use_poly(2 * j + 1) ? exp2_poly(s[2 * j + 1]) : ex2(s[2 * j + 1]);
    p[j] = pack_bf16(e0, e1);
  }
  uint32_t acc_or = 0;
#pragma unroll
  for (int j = 0; j < 16; j++) acc_or |= p[j];
  return __any_sync(0xffffffffu, (acc_or & 0x40004000u) != 0);
}
__device__ __forceinline__ void attn_exp_exact(const float (&s)[32], uint32_t (&p)[16], float (&o)[12], AttnState& st, bool first, int c4) {
  float mx0 = fmaxf(s[0], s[1]), mx1 = fmaxf(s[2], s[3]);
#pragma unroll
  for (int j = 1; j < 8; j++) {
    mx0 = fmaxf(mx0, fmaxf(s[4 * j], s[4 * j + 1]));
    mx1 = fmaxf(mx1, fmaxf(s[4 * j + 2], s[4 * j + 3]));
  }
  mx0 = fmaxf(mx0, __shfl_xor_sync(0xffffffffu, mx0, 1));
  mx1 = fmaxf(mx1, __shfl_xor_sync(0xffffffffu, mx1, 1));
  mx0 = fmaxf(mx0, __shfl_xor_sync(0xffffffffu, mx0, 2));
  mx1 = fmaxf(mx1, __shfl_xor_sync(0xffffffffu, mx1, 2));
  float d0 = mx0 + 7.0f, d1 = mx1 + 7.0f;
  if (!first) { d0 = fmaxf(d0, 0.f); d1 = fmaxf(d1, 0.f); }
  const float T0 = st.M0 + d0, T1 = st.M1 + d1;
  const float h0 = bf16_round(T0), h1 = bf16_round(T1);
  const float i0 = bf16_round(T0 - h0), i1 = bf16_round(T1 - h1);
  const float l0 = bf16_round((T0 - h0) - i0), l1 = bf16_round((T1 - h1) - i1);
  const float N0 = (h0 + i0) + l0, N1 = (h1 + i1) + l1;
  d0 = N0 - st.M0; d1 = N1 - st.M1;
  st.M0 = N0; st.M1 = N1;
  if (c4 == 2) { st.qa4 = pack_bf16(-h0, -i0); st.qa5 = pack_bf16(-h1, -i1); }
  if (c4 == 3) { st.qa4 = pack_bf16(-l0, 0.f); st.qa5 = pack_bf16(-l1, 0.f); }
  if (!first) {
    const float al0 = ex2(-d0), al1 = ex2(-d1);
#pragma unroll
    for (int j = 0; j < 3; j++) {
      o[4 * j] *= al0; o[4 * j + 1] *= al0;
      o[4 * j + 2] *= al1; o[4 * j + 3] *= al1;
    }
  }
#pragma unroll
  for (int j = 0; j < 8; j++) {
    p[2 * j] = pack_bf16(ex2(s[4 * j] - d0), ex2(s[4 * j + 1] - d0));
    p[2 * j + 1] = pack_bf16(ex2(s[4 * j + 2] - d1), ex2(s[4 * j + 3] - d1));
  }
}
__device__ __forceinline__ void attn_step(float (&s)[32], const uint32_t (&pp)[16], uint32_t (&pn)[16], float (&o)[12], AttnState& st,
                                          uint32_t k_addr, uint32_t v_addr_prev, int keep, int c4, int wgdbg = 0, int tdbg = 0) {
  PH(wgdbg, tdbg, 0);
  const uint64_t dk = make_desc(k_addr, 128, 384, 0);
  const uint64_t dv_prev = make_desc(v_addr_prev, 384, 128, 0);
  wgmma_fence();
  wgmma_rs_n64(s, st.qa0, st.qa1, st.qa2, st.qa3, dk, 0);
  wgmma_rs_n64(s, st.qa4, st.qa5, 0u, 0u, dk + 16, 1);
  wgmma_commit();
#pragma unroll
  for (int kk = 0; kk < 4; kk++) wgmma_rs_n24_tb(o, pp[4 * kk], pp[4 * kk + 1], pp[4 * kk + 2], pp[4 * kk + 3], dv_prev + kk * 48, kk == 0 ? keep : 1);
  wgmma_commit();
  wgmma_wait<1>();
  fence_regs(s);
  PH(wgdbg, tdbg, 1);
  const bool redo = attn_exp_fast(s, pn);
  PH(wgdbg, tdbg, 2);
  wgmma_wait<0>();
  fence_regs(o);
  if (redo) attn_exp_exact(s, pn, o, st, false, c4);
}

__global__ void __launch_bounds__(AT_THREADS, 1) attn_kernel(const bf16* __restrict__ wo, const bf16* __restrict__ wgt, const bf16* __restrict__ wup, const bf16* __restrict__ wdn) {
  extern __shared__ uint8_t smem_raw[];
  const uint32_t sbase = (smem_u32(smem_raw) + 1023u) & ~1023u;
  const uint32_t sK = sbase, sV = sbase + AT_KV_BYTES;
  const uint32_t sBar = sV + AT_KV_BYTES;
  const int tid = threadIdx.x, warp = tid >> 5, lane = tid & 31;
  const int head = blockIdx.x >> 2, quarter = blockIdx.x & 3;
  if (blockIdx.x >= 128) {
    pdl_launch();
    const int b = blockIdx.x - 128;
    const bf16* w = (b >> 1) ? wup : wgt;
    const int cgrp = tid % 96, rgrp = tid / 96;
    float acc[8];
#pragma unroll
    for (int i = 0; i < 8; i++) acc[i] = 0.f;
    float* red = reinterpret_cast<float*>(smem_raw);
    if (rgrp < 5) {
      const uint4* src = reinterpret_cast<const uint4*>(w + (size_t)(rgrp * 128) * FF + (b & 1) * 768 + cgrp * 8);
#pragma unroll 8
      for (int r = 0; r < 128; r++) {
        const uint4 v = __ldg(src + (size_t)r * (FF / 8));
        acc[0] += bf_lo(v.x); acc[1] += bf_hi(v.x); acc[2] += bf_lo(v.y); acc[3] += bf_hi(v.y);
        acc[4] += bf_lo(v.z); acc[5] += bf_hi(v.z); acc[6] += bf_lo(v.w); acc[7] += bf_hi(v.w);
      }
#pragma unroll
      for (int i = 0; i < 8; i++) red[rgrp * 768 + cgrp * 8 + i] = acc[i];
    }
    __syncthreads();
    pdl_wait();
    for (int c = tid; c < 768; c += AT_THREADS)
      g_cs[(b >> 1) * FF + (b & 1) * 768 + c] = ((red[c] + red[768 + c]) + (red[1536 + c] + red[2304 + c])) + red[3072 + c];
    if (b == 0 && tid < 16) g_flag[tid] = 0;
    return;
  }
  TS(1, 0);
  if (tid == 0) {
    for (int i = 0; i < AT_CHUNKS; i++) mbar_init(sBar + 8 * i, 1);
    fence_mbar_init();
  }
  pdl_launch();
  if (tid == 32) {
    prefetch_l2(reinterpret_cast<const uint8_t*>(wo) + blockIdx.x * 6400, 6400);
    prefetch_l2(reinterpret_cast<const uint8_t*>(wgt) + blockIdx.x * 15360, 15360);
    prefetch_l2(reinterpret_cast<const uint8_t*>(wup) + blockIdx.x * 15360, 15360);
    prefetch_l2(reinterpret_cast<const uint8_t*>(wdn) + blockIdx.x * 15360, 15360);
  }
  __syncthreads();
  TS(1, 1);
  pdl_wait();
  TS(1, 2);
  if (tid == 0) {
    const uint8_t* kg = reinterpret_cast<const uint8_t*>(g_img + (size_t)(32 + head) * IMG_HEAD_ELEMS);
    const uint8_t* vg = reinterpret_cast<const uint8_t*>(g_img + (size_t)(64 + head) * IMG_HEAD_ELEMS);
    constexpr int CB = AT_KV_BYTES / AT_CHUNKS;
    for (int i = 0; i < AT_CHUNKS; i++) {
      mbar_expect_tx(sBar + 8 * i, 2 * CB);
      bulk_g2s(sK + i * CB, kg + i * CB, CB, sBar + 8 * i);
      bulk_g2s(sV + i * CB, vg + i * CB, CB, sBar + 8 * i);
    }
  }
  const int wg = warp >> 2, wwarp = warp & 3;
  const int g = lane >> 2, c4 = lane & 3;
  const uint64_t dk_base = make_desc(sK, 128, 384, 0);
  const uint64_t dv_base = make_desc(sV, 384, 128, 0);

  uint32_t qn[6];
  {
    const bf16* q0 = g_img + (size_t)head * IMG_HEAD_ELEMS + (size_t)((quarter * 512 + wg * 64 + wwarp * 16) >> 3) * 192 + g * 8 + c4 * 2;
    qn[0] = *reinterpret_cast<const uint32_t*>(q0);
    qn[1] = *reinterpret_cast<const uint32_t*>(q0 + 192);
    qn[2] = *reinterpret_cast<const uint32_t*>(q0 + 64);
    qn[3] = *reinterpret_cast<const uint32_t*>(q0 + 192 + 64);
    qn[4] = *reinterpret_cast<const uint32_t*>(q0 + 128);
    qn[5] = *reinterpret_cast<const uint32_t*>(q0 + 192 + 128);
  }
#pragma unroll 1
  for (int rep = 0; rep < 8 / AT_WGS; rep++) {
    const int row0 = quarter * 512 + (rep * AT_WGS + wg) * 64 + wwarp * 16 + g;
    AttnState st;
    st.qa0 = qn[0]; st.qa1 = qn[1]; st.qa2 = qn[2]; st.qa3 = qn[3]; st.qa4 = qn[4]; st.qa5 = qn[5];
    if (rep + 1 < 8 / AT_WGS) {
      const bf16* q0 = g_img + (size_t)head * IMG_HEAD_ELEMS + (size_t)((row0 + AT_WGS * 64) >> 3) * 192 + g * 8 + c4 * 2;
      qn[0] = *reinterpret_cast<const uint32_t*>(q0);
      qn[1] = *reinterpret_cast<const uint32_t*>(q0 + 192);
      qn[2] = *reinterpret_cast<const uint32_t*>(q0 + 64);
      qn[3] = *reinterpret_cast<const uint32_t*>(q0 + 192 + 64);
      qn[4] = *reinterpret_cast<const uint32_t*>(q0 + 128);
      qn[5] = *reinterpret_cast<const uint32_t*>(q0 + 192 + 128);
    }
    float o[12];
    float s[32];
    uint32_t pa[16], pb[16];
    st.M0 = st.M1 = 0.f;
    if (rep == 0) mbar_wait(sBar, 0);
    wgmma_fence();
    wgmma_rs_n64(s, st.qa0, st.qa1, st.qa2, st.qa3, dk_base, 0);
    wgmma_rs_n64(s, st.qa4, st.qa5, 0u, 0u, dk_base + 16, 1);
    wgmma_commit();
    wgmma_wait<0>();
    fence_regs(s);
    attn_exp_exact(s, pa, o, st, true, c4);
    attn_step(s, pa, pb, o, st, sK + 3072, sV, 0, c4);
#pragma unroll 1
    for (int tt = 1; tt < 16; tt++) {
      if (rep == 0 && !(tt & 1)) mbar_wait(sBar + 8 * (tt >> 1), 0);
      attn_step(s, pb, pa, o, st, sK + tt * 6144, sV + tt * 6144 - 3072, 1, c4, wg, rep * 32 + tt * 2);
      attn_step(s, pa, pb, o, st, sK + tt * 6144 + 3072, sV + tt * 6144, 1, c4, wg, rep * 32 + tt * 2 + 1);
    }
    wgmma_fence();
#pragma unroll
    for (int kk = 0; kk < 4; kk++) wgmma_rs_n24_tb(o, pb[4 * kk], pb[4 * kk + 1], pb[4 * kk + 2], pb[4 * kk + 3], dv_base + 31 * 192 + kk * 48, 1);
    wgmma_commit();
    wgmma_wait<0>();
    fence_regs(o);
    TS(1, 3 + rep);
    const float l0 = __shfl_sync(0xffffffffu, o[8], (lane & ~3) | 2);
    const float l1 = __shfl_sync(0xffffffffu, o[10], (lane & ~3) | 2);
    const float i0 = 1.0f / l0, i1 = 1.0f / l1;
    bf16* o0 = g_o + (size_t)row0 * DM + head * DH;
    bf16* o1 = o0 + 8 * DM;
#pragma unroll
    for (int j = 0; j < 3; j++) {
      if (j < 2 || c4 < 2) {
        *reinterpret_cast<uint32_t*>(o0 + j * 8 + c4 * 2) = pack_bf16(o[4 * j] * i0, o[4 * j + 1] * i0);
        *reinterpret_cast<uint32_t*>(o1 + j * 8 + c4 * 2) = pack_bf16(o[4 * j + 2] * i1, o[4 * j + 3] * i1);
      }
    }
  }
}

typedef CUresult (*EncodeTiledFn)(CUtensorMap*, CUtensorMapDataType, cuuint32_t, void*, const cuuint64_t*, const cuuint64_t*,
                                  const cuuint32_t*, const cuuint32_t*, CUtensorMapInterleave, CUtensorMapSwizzle,
                                  CUtensorMapL2promotion, CUtensorMapFloatOOBfill);

static void make_map(EncodeTiledFn fn, CUtensorMap* tm, const void* ptr, uint64_t rows, uint64_t cols, uint32_t box_rows,
                     uint32_t box_cols, CUtensorMapSwizzle sw) {
  cuuint64_t dims[2] = {cols, rows};
  cuuint64_t strides[1] = {cols * 2};
  cuuint32_t box[2] = {box_cols, box_rows};
  cuuint32_t es[2] = {1, 1};
  fn(tm, CU_TENSOR_MAP_DATA_TYPE_BFLOAT16, 2, const_cast<void*>(ptr), dims, strides, box, es, CU_TENSOR_MAP_INTERLEAVE_NONE, sw,
     CU_TENSOR_MAP_L2_PROMOTION_L2_256B, CU_TENSOR_MAP_FLOAT_OOB_FILL_NONE);
}

template <typename... KArgs, typename... Args>
static void launch(void (*kern)(KArgs...), int grid, int block, int smem, int cluster, bool pdl, Args... args) {
  cudaLaunchConfig_t cfg = {};
  cfg.gridDim = dim3(grid);
  cfg.blockDim = dim3(block);
  cfg.dynamicSmemBytes = smem;
  cfg.stream = cudaStreamPerThread;
  cudaLaunchAttribute at[2];
  int n = 0;
  if (cluster > 1) {
    at[n].id = cudaLaunchAttributeClusterDimension;
    at[n].val.clusterDim.x = cluster; at[n].val.clusterDim.y = 1; at[n].val.clusterDim.z = 1;
    n++;
  }
  if (pdl) {
    at[n].id = cudaLaunchAttributeProgrammaticStreamSerialization;
    at[n].val.programmaticStreamSerializationAllowed = 1;
    n++;
  }
  cfg.attrs = at;
  cfg.numAttrs = n;
  cudaLaunchKernelEx(&cfg, kern, KArgs(args)...);
}

extern "C" void kernel_launch(void* const* d_in, const int* in_sizes, int n_in, void* d_out, int out_size) {
  const bf16* x = (const bf16*)d_in[0];
  const bf16* wqkv = (const bf16*)d_in[1];
  const bf16* wo = (const bf16*)d_in[2];
  const bf16* wg = (const bf16*)d_in[4];
  const bf16* wu = (const bf16*)d_in[5];
  const bf16* wd = (const bf16*)d_in[6];
  bf16* out = (bf16*)d_out;

  static EncodeTiledFn enc = nullptr;
  static void *p_o = nullptr, *p_h = nullptr, *p_hh = nullptr, *p_xn = nullptr;
  if (!enc) {
    void* fn = nullptr;
    cudaDriverEntryPointQueryResult qr;
    cudaGetDriverEntryPoint("cuTensorMapEncodeTiled", &fn, cudaEnableDefault, &qr);
    enc = (EncodeTiledFn)fn;
    cudaGetSymbolAddress(&p_o, g_o);
    cudaGetSymbolAddress(&p_h, g_h);
    cudaGetSymbolAddress(&p_hh, g_hh);
    cudaGetSymbolAddress(&p_xn, g_xn);
    cudaFuncSetAttribute(qkv_kernel, cudaFuncAttributeMaxDynamicSharedMemorySize, KA_SMEM);
    cudaFuncSetAttribute(mlp_kernel, cudaFuncAttributeMaxDynamicSharedMemorySize, KC_SMEM);
    cudaFuncSetAttribute(attn_kernel, cudaFuncAttributeMaxDynamicSharedMemorySize, AT_SMEM);
  }
  CUtensorMap tm_wqkv, tm_wg, tm_wu, tm_wo64, tm_wo16, tm_wd64, tm_wd16, tm_o, tm_h, tm_hh, tm_hhs, tm_xn, tm_hs, tm_out;
  make_map(enc, &tm_wqkv, wqkv, DM, 3 * DM, 32, 64, CU_TENSOR_MAP_SWIZZLE_128B);
  make_map(enc, &tm_wg, wg, DM, FF, 32, 64, CU_TENSOR_MAP_SWIZZLE_128B);
  make_map(enc, &tm_wu, wu, DM, FF, 32, 64, CU_TENSOR_MAP_SWIZZLE_128B);
  make_map(enc, &tm_wo64, wo, DM, DM, 32, 64, CU_TENSOR_MAP_SWIZZLE_128B);
  make_map(enc, &tm_wo16, wo, DM, DM, 32, 16, CU_TENSOR_MAP_SWIZZLE_32B);
  make_map(enc, &tm_wd64, wd, FF, DM, 32, 64, CU_TENSOR_MAP_SWIZZLE_128B);
  make_map(enc, &tm_wd16, wd, FF, DM, 32, 16, CU_TENSOR_MAP_SWIZZLE_32B);
  make_map(enc, &tm_o, p_o, SEQ, DM, 128, 64, CU_TENSOR_MAP_SWIZZLE_128B);
  make_map(enc, &tm_h, p_h, SEQ, DM, 128, 32, CU_TENSOR_MAP_SWIZZLE_64B);
  make_map(enc, &tm_hh, p_hh, SEQ, FF, 128, 64, CU_TENSOR_MAP_SWIZZLE_128B);
  make_map(enc, &tm_hhs, p_hh, SEQ, FF, 64, 64, CU_TENSOR_MAP_SWIZZLE_128B);
  make_map(enc, &tm_xn, p_xn, SEQ, DM, 128, 32, CU_TENSOR_MAP_SWIZZLE_64B);
  make_map(enc, &tm_hs, p_h, SEQ, DM, 64, 80, CU_TENSOR_MAP_SWIZZLE_NONE);
  make_map(enc, &tm_out, out, SEQ, DM, 64, 80, CU_TENSOR_MAP_SWIZZLE_NONE);

  launch(qkv_kernel, 128, GT, KA_SMEM, 2, false, tm_xn, tm_wqkv, x);
  launch(attn_kernel, 132, AT_THREADS, AT_SMEM, 1, true, wo, wg, wu, wd);
  launch(mlp_kernel, 128, GT, KC_SMEM, 2, true, tm_o, tm_wo64, tm_wo16, tm_h, tm_wg, tm_wu, tm_hhs, tm_hh, tm_wd64, tm_wd16, tm_hs, tm_out, x);
}
```

```cpp
#include <cuda_runtime.h>
#include <cuda_bf16.h>
#include <cuda.h>
#include <stdint.h>

typedef __nv_bfloat16 bf16;

constexpr int SEQ = 2048, DM = 640, NH = 32, DH = 20, FF = 1536;
constexpr float ATT_SCALE_LOG2E = 0.22360679774997896f * 1.4426950408889634f;
constexpr int IMG_HEAD_ELEMS = (SEQ / 8) * 192;

__device__ __align__(1024) bf16 g_img[3 * NH * IMG_HEAD_ELEMS];
__device__ __align__(1024) bf16 g_o[SEQ * DM];
__device__ __align__(1024) bf16 g_h[SEQ * DM];
__device__ __align__(1024) bf16 g_xn[SEQ * DM];
__device__ float2 g_stats[SEQ * 8];
__device__ float g_cs[2 * FF];
__device__ int g_flag[3 * 16];
__device__ __align__(1024) bf16 g_hh[SEQ * FF];

#define TS(k, i)
#define PH(w, t, i)
__device__ __forceinline__ uint32_t smem_u32(const void* p) { return (uint32_t)__cvta_generic_to_shared(p); }
__device__ __forceinline__ void mbar_init(uint32_t bar, uint32_t cnt) {
  asm volatile("mbarrier.init.shared::cta.b64 [%0], %1;" ::"r"(bar), "r"(cnt) : "memory");
}
__device__ __forceinline__ void mbar_expect_tx(uint32_t bar, uint32_t bytes) {
  asm volatile("mbarrier.arrive.expect_tx.shared::cta.b64 _, [%0], %1;" ::"r"(bar), "r"(bytes) : "memory");
}
__device__ __forceinline__ void mbar_arrive(uint32_t bar) {
  asm volatile("mbarrier.arrive.shared::cta.b64 _, [%0];" ::"r"(bar) : "memory");
}
__device__ __forceinline__ void mbar_arrive_cluster(uint32_t bar, uint32_t cta) {
  asm volatile(
      "{\n.reg .b32 r;\nmapa.shared::cluster.u32 r, %0, %1;\n"
      "mbarrier.arrive.shared::cluster.b64 _, [r];\n}\n" ::"r"(bar), "r"(cta)
      : "memory");
}
__device__ __forceinline__ void mbar_wait(uint32_t bar, uint32_t parity) {
  asm volatile(
      "{\n.reg .pred p;\nLAB_WAIT:\n"
      "mbarrier.try_wait.parity.shared::cta.b64 p, [%0], %1;\n"
      "@p bra DONE;\nbra LAB_WAIT;\nDONE:\n}\n" ::"r"(bar), "r"(parity)
      : "memory");
}
__device__ __forceinline__ void mbar_wait_cluster(uint32_t bar, uint32_t parity) {
  asm volatile(
      "{\n.reg .pred p;\nLAB_WAIT:\n"
      "mbarrier.try_wait.parity.acquire.cluster.shared::cta.b64 p, [%0], %1;\n"
      "@p bra DONE;\nbra LAB_WAIT;\nDONE:\n}\n" ::"r"(bar), "r"(parity)
      : "memory");
}
__device__ __forceinline__ void fence_mbar_init() { asm volatile("fence.mbarrier_init.release.cluster;" ::: "memory"); }
__device__ __forceinline__ void fence_proxy_async() { asm volatile("fence.proxy.async.shared::cta;" ::: "memory"); }
__device__ __forceinline__ void cluster_sync_all() {
  asm volatile("barrier.cluster.arrive.release.aligned;\nbarrier.cluster.wait.acquire.aligned;" ::: "memory");
}
__device__ __forceinline__ void cluster_sync_relaxed() {
  asm volatile("barrier.cluster.arrive.relaxed.aligned;\nbarrier.cluster.wait.aligned;" ::: "memory");
}
__device__ __forceinline__ void named_bar_sync(int id, int n) { asm volatile("bar.sync %0, %1;" ::"r"(id), "r"(n) : "memory"); }
__device__ __forceinline__ bool wg_any(bool pred, int id) {
  uint32_t r;
  asm volatile("{\n.reg .pred p, q;\nsetp.ne.u32 p, %1, 0;\nbar.red.or.pred q, %2, 128, p;\nselp.u32 %0, 1, 0, q;\n}\n" : "=r"(r) : "r"((uint32_t)pred), "r"(id) : "memory");
  return r != 0;
}
__device__ __forceinline__ void fence_proxy_async_all() { asm volatile("fence.proxy.async;" ::: "memory"); }
__device__ __forceinline__ void flag_signal(int* f) {
  __threadfence();
  atomicAdd(f, 1);
}
__device__ __forceinline__ void flag_wait(const int* f, int target) {
  int v;
  unsigned spins = 0;
  do {
    asm volatile("ld.acquire.gpu.global.s32 %0, [%1];" : "=r"(v) : "l"(f) : "memory");
    if (++spins > (1u << 24)) __trap();
  } while (v < target);
}
__device__ __forceinline__ void pdl_launch() { asm volatile("griddepcontrol.launch_dependents;" ::: "memory"); }
__device__ __forceinline__ void pdl_wait() { asm volatile("griddepcontrol.wait;" ::: "memory"); }

__device__ __forceinline__ void tma_load_2d(uint32_t dst, const CUtensorMap* tm, int c0, int c1, uint32_t bar) {
  asm volatile(
      "cp.async.bulk.tensor.2d.shared::cluster.global.mbarrier::complete_tx::bytes [%0], [%1, {%3, %4}], [%2];" ::"r"(dst),
      "l"((uint64_t)tm), "r"(bar), "r"(c0), "r"(c1)
      : "memory");
}
__device__ __forceinline__ void tma_load_2d_mc(uint32_t dst, const CUtensorMap* tm, int c0, int c1, uint32_t bar, uint16_t mask) {
  asm volatile(
      "cp.async.bulk.tensor.2d.shared::cluster.global.mbarrier::complete_tx::bytes.multicast::cluster [%0], [%1, {%3, %4}], [%2], %5;" ::"r"(dst),
      "l"((uint64_t)tm), "r"(bar), "r"(c0), "r"(c1), "h"(mask)
      : "memory");
}
__device__ __forceinline__ void bulk_g2s(uint32_t dst, const void* src, uint32_t bytes, uint32_t bar) {
  asm volatile("cp.async.bulk.shared::cluster.global.mbarrier::complete_tx::bytes [%0], [%1], %2, [%3];" ::"r"(dst), "l"(src),
               "r"(bytes), "r"(bar)
               : "memory");
}
__device__ __forceinline__ void bulk_s2g(void* dst, uint32_t src, uint32_t bytes) {
  asm volatile("cp.async.bulk.global.shared::cta.bulk_group [%0], [%1], %2;" ::"l"(dst), "r"(src), "r"(bytes) : "memory");
}
__device__ __forceinline__ void tma_store_2d(const CUtensorMap* tm, uint32_t src, int c0, int c1) {
  asm volatile("cp.async.bulk.tensor.2d.global.shared::cta.bulk_group [%0, {%2, %3}], [%1];" ::"l"((uint64_t)tm), "r"(src), "r"(c0), "r"(c1) : "memory");
}
__device__ __forceinline__ void bulk_commit() { asm volatile("cp.async.bulk.commit_group;" ::: "memory"); }
__device__ __forceinline__ void bulk_wait_read() { asm volatile("cp.async.bulk.wait_group.read 0;" ::: "memory"); }
__device__ __forceinline__ void prefetch_l2(const void* p, uint32_t bytes) {
  asm volatile("cp.async.bulk.prefetch.L2.global [%0], %1;" ::"l"(p), "r"(bytes) : "memory");
}
__device__ __forceinline__ void bulk_wait_all() { asm volatile("cp.async.bulk.wait_group 0;" ::: "memory"); }
__device__ __forceinline__ void st_shared_b32(uint32_t addr, uint32_t v) { asm volatile("st.shared.b32 [%0], %1;" ::"r"(addr), "r"(v) : "memory"); }
__device__ __forceinline__ void st_shared_v2(uint32_t addr, uint32_t a, uint32_t b) { asm volatile("st.shared.v2.b32 [%0], {%1, %2};" ::"r"(addr), "r"(a), "r"(b) : "memory"); }
__device__ __forceinline__ void prefetch_tmap(const CUtensorMap* tm) {
  asm volatile("prefetch.tensormap [%0];" ::"l"((uint64_t)tm) : "memory");
}
__device__ __forceinline__ void wgmma_fence() { asm volatile("wgmma.fence.sync.aligned;" ::: "memory"); }
__device__ __forceinline__ void wgmma_commit() { asm volatile("wgmma.commit_group.sync.aligned;" ::: "memory"); }
template <int N>
__device__ __forceinline__ void wgmma_wait() { asm volatile("wgmma.wait_group.sync.aligned %0;" ::"n"(N) : "memory"); }

template <int N>
__device__ __forceinline__ void fence_regs(float (&r)[N]) {
#pragma unroll
  for (int i = 0; i < N; i++) asm volatile("" : "+f"(r[i])::"memory");
}
template <int N>
__device__ __forceinline__ void fence_regs(uint32_t (&r)[N]) {
#pragma unroll
  for (int i = 0; i < N; i++) asm volatile("" : "+r"(r[i])::"memory");
}
__device__ __forceinline__ uint64_t make_desc(uint32_t addr, uint32_t lbo, uint32_t sbo, uint32_t layout) {
  return (uint64_t)((addr & 0x3FFFF) >> 4) | ((uint64_t)((lbo & 0x3FFFF) >> 4) << 16) | ((uint64_t)((sbo & 0x3FFFF) >> 4) << 32) |
         ((uint64_t)layout << 62);
}
__device__ __forceinline__ uint32_t pack_bf16(float lo, float hi) {
  uint32_t r;
  asm("cvt.rn.bf16x2.f32 %0, %1, %2;" : "=r"(r) : "f"(hi), "f"(lo));
  return r;
}
__device__ __forceinline__ float bf16_round(float x) { return __bfloat162float(__float2bfloat16_rn(x)); }
__device__ __forceinline__ float bf_lo(uint32_t u) { return __uint_as_float(u << 16); }
__device__ __forceinline__ float bf_hi(uint32_t u) { return __uint_as_float(u & 0xffff0000u); }
__device__ __forceinline__ float ex2(float x) {
  float y;
  asm("ex2.approx.ftz.f32 %0, %1;" : "=f"(y) : "f"(x));
  return y;
}

__device__ __forceinline__ void wgmma_ss_n240_tb(float (&d)[120], uint64_t descA, uint64_t descB, int scaleD) {
  asm volatile("{\n.reg .pred p;\nsetp.ne.b32 p, %122, 0;\n"
    "wgmma.mma_async.sync.aligned.m64n240k16.f32.bf16.bf16 {%0, %1, %2, %3, %4, %5, %6, %7, %8, %9, %10, %11, %12, %13, %14, %15, %16, %17, %18, %19, %20, %21, %22, %23, %24, %25, %26, %27, %28, %29, %30, %31, %32, %33, %34, %35, %36, %37, %38, %39, %40, %41, %42, %43, %44, %45, %46, %47, %48, %49, %50, %51, %52, %53, %54, %55, %56, %57, %58, %59, %60, %61, %62, %63, %64, %65, %66, %67, %68, %69, %70, %71, %72, %73, %74, %75, %76, %77, %78, %79, %80, %81, %82, %83, %84, %85, %86, %87, %88, %89, %90, %91, %92, %93, %94, %95, %96, %97, %98, %99, %100, %101, %102, %103, %104, %105, %106, %107, %108, %109, %110, %111, %112, %113, %114, %115, %116, %117, %118, %119}, %120, %121, p, 1, 1, 0, 1;\n}\n"
    : "+f"(d[0]), "+f"(d[1]), "+f"(d[2]), "+f"(d[3]), "+f"(d[4]), "+f"(d[5]), "+f"(d[6]), "+f"(d[7]), "+f"(d[8]), "+f"(d[9]), "+f"(d[10]), "+f"(d[11]), "+f"(d[12]), "+f"(d[13]), "+f"(d[14]), "+f"(d[15]), "+f"(d[16]), "+f"(d[17]), "+f"(d[18]), "+f"(d[19]), "+f"(d[20]), "+f"(d[21]), "+f"(d[22]), "+f"(d[23]), "+f"(d[24]), "+f"(d[25]), "+f"(d[26]), "+f"(d[27]), "+f"(d[28]), "+f"(d[29]), "+f"(d[30]), "+f"(d[31]), "+f"(d[32]), "+f"(d[33]), "+f"(d[34]), "+f"(d[35]), "+f"(d[36]), "+f"(d[37]), "+f"(d[38]), "+f"(d[39]), "+f"(d[40]), "+f"(d[41]), "+f"(d[42]), "+f"(d[43]), "+f"(d[44]), "+f"(d[45]), "+f"(d[46]), "+f"(d[47]), "+f"(d[48]), "+f"(d[49]), "+f"(d[50]), "+f"(d[51]), "+f"(d[52]), "+f"(d[53]), "+f"(d[54]), "+f"(d[55]), "+f"(d[56]), "+f"(d[57]), "+f"(d[58]), "+f"(d[59]), "+f"(d[60]), "+f"(d[61]), "+f"(d[62]), "+f"(d[63]), "+f"(d[64]), "+f"(d[65]), "+f"(d[66]), "+f"(d[67]), "+f"(d[68]), "+f"(d[69]), "+f"(d[70]), "+f"(d[71]), "+f"(d[72]), "+f"(d[73]), "+f"(d[74]), "+f"(d[75]), "+f"(d[76]), "+f"(d[77]), "+f"(d[78]), "+f"(d[79]), "+f"(d[80]), "+f"(d[81]), "+f"(d[82]), "+f"(d[83]), "+f"(d[84]), "+f"(d[85]), "+f"(d[86]), "+f"(d[87]), "+f"(d[88]), "+f"(d[89]), "+f"(d[90]), "+f"(d[91]), "+f"(d[92]), "+f"(d[93]), "+f"(d[94]), "+f"(d[95]), "+f"(d[96]), "+f"(d[97]), "+f"(d[98]), "+f"(d[99]), "+f"(d[100]), "+f"(d[101]), "+f"(d[102]), "+f"(d[103]), "+f"(d[104]), "+f"(d[105]), "+f"(d[106]), "+f"(d[107]), "+f"(d[108]), "+f"(d[109]), "+f"(d[110]), "+f"(d[111]), "+f"(d[112]), "+f"(d[113]), "+f"(d[114]), "+f"(d[115]), "+f"(d[116]), "+f"(d[117]), "+f"(d[118]), "+f"(d[119])
    : "l"(descA), "l"(descB), "r"(scaleD));
}
__device__ __forceinline__ void wgmma_ss_n192_tb(float (&d)[96], uint64_t descA, uint64_t descB, int scaleD) {
  asm volatile("{\n.reg .pred p;\nsetp.ne.b32 p, %98, 0;\n"
    "wgmma.mma_async.sync.aligned.m64n192k16.f32.bf16.bf16 {%0, %1, %2, %3, %4, %5, %6, %7, %8, %9, %10, %11, %12, %13, %14, %15, %16, %17, %18, %19, %20, %21, %22, %23, %24, %25, %26, %27, %28, %29, %30, %31, %32, %33, %34, %35, %36, %37, %38, %39, %40, %41, %42, %43, %44, %45, %46, %47, %48, %49, %50, %51, %52, %53, %54, %55, %56, %57, %58, %59, %60, %61, %62, %63, %64, %65, %66, %67, %68, %69, %70, %71, %72, %73, %74, %75, %76, %77, %78, %79, %80, %81, %82, %83, %84, %85, %86, %87, %88, %89, %90, %91, %92, %93, %94, %95}, %96, %97, p, 1, 1, 0, 1;\n}\n"
    : "+f"(d[0]), "+f"(d[1]), "+f"(d[2]), "+f"(d[3]), "+f"(d[4]), "+f"(d[5]), "+f"(d[6]), "+f"(d[7]), "+f"(d[8]), "+f"(d[9]), "+f"(d[10]), "+f"(d[11]), "+f"(d[12]), "+f"(d[13]), "+f"(d[14]), "+f"(d[15]), "+f"(d[16]), "+f"(d[17]), "+f"(d[18]), "+f"(d[19]), "+f"(d[20]), "+f"(d[21]), "+f"(d[22]), "+f"(d[23]), "+f"(d[24]), "+f"(d[25]), "+f"(d[26]), "+f"(d[27]), "+f"(d[28]), "+f"(d[29]), "+f"(d[30]), "+f"(d[31]), "+f"(d[32]), "+f"(d[33]), "+f"(d[34]), "+f"(d[35]), "+f"(d[36]), "+f"(d[37]), "+f"(d[38]), "+f"(d[39]), "+f"(d[40]), "+f"(d[41]), "+f"(d[42]), "+f"(d[43]), "+f"(d[44]), "+f"(d[45]), "+f"(d[46]), "+f"(d[47]), "+f"(d[48]), "+f"(d[49]), "+f"(d[50]), "+f"(d[51]), "+f"(d[52]), "+f"(d[53]), "+f"(d[54]), "+f"(d[55]), "+f"(d[56]), "+f"(d[57]), "+f"(d[58]), "+f"(d[59]), "+f"(d[60]), "+f"(d[61]), "+f"(d[62]), "+f"(d[63]), "+f"(d[64]), "+f"(d[65]), "+f"(d[66]), "+f"(d[67]), "+f"(d[68]), "+f"(d[69]), "+f"(d[70]), "+f"(d[71]), "+f"(d[72]), "+f"(d[73]), "+f"(d[74]), "+f"(d[75]), "+f"(d[76]), "+f"(d[77]), "+f"(d[78]), "+f"(d[79]), "+f"(d[80]), "+f"(d[81]), "+f"(d[82]), "+f"(d[83]), "+f"(d[84]), "+f"(d[85]), "+f"(d[86]), "+f"(d[87]), "+f"(d[88]), "+f"(d[89]), "+f"(d[90]), "+f"(d[91]), "+f"(d[92]), "+f"(d[93]), "+f"(d[94]), "+f"(d[95])
    : "l"(descA), "l"(descB), "r"(scaleD));
}
__device__ __forceinline__ void wgmma_ss_n64_tb(float (&d)[32], uint64_t descA, uint64_t descB, int scaleD) {
  asm volatile("{\n.reg .pred p;\nsetp.ne.b32 p, %34, 0;\n"
    "wgmma.mma_async.sync.aligned.m64n64k16.f32.bf16.bf16 {%0, %1, %2, %3, %4, %5, %6, %7, %8, %9, %10, %11, %12, %13, %14, %15, %16, %17, %18, %19, %20, %21, %22, %23, %24, %25, %26, %27, %28, %29, %30, %31}, %32, %33, p, 1, 1, 0, 1;\n}\n"
    : "+f"(d[0]), "+f"(d[1]), "+f"(d[2]), "+f"(d[3]), "+f"(d[4]), "+f"(d[5]), "+f"(d[6]), "+f"(d[7]), "+f"(d[8]), "+f"(d[9]), "+f"(d[10]), "+f"(d[11]), "+f"(d[12]), "+f"(d[13]), "+f"(d[14]), "+f"(d[15]), "+f"(d[16]), "+f"(d[17]), "+f"(d[18]), "+f"(d[19]), "+f"(d[20]), "+f"(d[21]), "+f"(d[22]), "+f"(d[23]), "+f"(d[24]), "+f"(d[25]), "+f"(d[26]), "+f"(d[27]), "+f"(d[28]), "+f"(d[29]), "+f"(d[30]), "+f"(d[31])
    : "l"(descA), "l"(descB), "r"(scaleD));
}
__device__ __forceinline__ void wgmma_ss_n16_tb(float (&d)[8], uint64_t descA, uint64_t descB, int scaleD) {
  asm volatile("{\n.reg .pred p;\nsetp.ne.b32 p, %10, 0;\n"
    "wgmma.mma_async.sync.aligned.m64n16k16.f32.bf16.bf16 {%0, %1, %2, %3, %4, %5, %6, %7}, %8, %9, p, 1, 1, 0, 1;\n}\n"
    : "+f"(d[0]), "+f"(d[1]), "+f"(d[2]), "+f"(d[3]), "+f"(d[4]), "+f"(d[5]), "+f"(d[6]), "+f"(d[7])
    : "l"(descA), "l"(descB), "r"(scaleD));
}
__device__ __forceinline__ void wgmma_rs_n128(float (&d)[64], uint32_t a0, uint32_t a1, uint32_t a2, uint32_t a3, uint64_t descB, int scaleD) {
  asm volatile("{\n.reg .pred p;\nsetp.ne.b32 p, %69, 0;\n"
    "wgmma.mma_async.sync.aligned.m64n128k16.f32.bf16.bf16 {%0, %1, %2, %3, %4, %5, %6, %7, %8, %9, %10, %11, %12, %13, %14, %15, %16, %17, %18, %19, %20, %21, %22, %23, %24, %25, %26, %27, %28, %29, %30, %31, %32, %33, %34, %35, %36, %37, %38, %39, %40, %41, %42, %43, %44, %45, %46, %47, %48, %49, %50, %51, %52, %53, %54, %55, %56, %57, %58, %59, %60, %61, %62, %63}, {%64, %65, %66, %67}, %68, p, 1, 1, 0;\n}\n"
    : "+f"(d[0]), "+f"(d[1]), "+f"(d[2]), "+f"(d[3]), "+f"(d[4]), "+f"(d[5]), "+f"(d[6]), "+f"(d[7]), "+f"(d[8]), "+f"(d[9]), "+f"(d[10]), "+f"(d[11]), "+f"(d[12]), "+f"(d[13]), "+f"(d[14]), "+f"(d[15]), "+f"(d[16]), "+f"(d[17]), "+f"(d[18]), "+f"(d[19]), "+f"(d[20]), "+f"(d[21]), "+f"(d[22]), "+f"(d[23]), "+f"(d[24]), "+f"(d[25]), "+f"(d[26]), "+f"(d[27]), "+f"(d[28]), "+f"(d[29]), "+f"(d[30]), "+f"(d[31]), "+f"(d[32]), "+f"(d[33]), "+f"(d[34]), "+f"(d[35]), "+f"(d[36]), "+f"(d[37]), "+f"(d[38]), "+f"(d[39]), "+f"(d[40]), "+f"(d[41]), "+f"(d[42]), "+f"(d[43]), "+f"(d[44]), "+f"(d[45]), "+f"(d[46]), "+f"(d[47]), "+f"(d[48]), "+f"(d[49]), "+f"(d[50]), "+f"(d[51]), "+f"(d[52]), "+f"(d[53]), "+f"(d[54]), "+f"(d[55]), "+f"(d[56]), "+f"(d[57]), "+f"(d[58]), "+f"(d[59]), "+f"(d[60]), "+f"(d[61]), "+f"(d[62]), "+f"(d[63])
    : "r"(a0), "r"(a1), "r"(a2), "r"(a3), "l"(descB), "r"(scaleD));
}
__device__ __forceinline__ void wgmma_rs_n64(float (&d)[32], uint32_t a0, uint32_t a1, uint32_t a2, uint32_t a3, uint64_t descB, int scaleD) {
  asm volatile("{\n.reg .pred p;\nsetp.ne.b32 p, %37, 0;\n"
    "wgmma.mma_async.sync.aligned.m64n64k16.f32.bf16.bf16 {%0, %1, %2, %3, %4, %5, %6, %7, %8, %9, %10, %11, %12, %13, %14, %15, %16, %17, %18, %19, %20, %21, %22, %23, %24, %25, %26, %27, %28, %29, %30, %31}, {%32, %33, %34, %35}, %36, p, 1, 1, 0;\n}\n"
    : "+f"(d[0]), "+f"(d[1]), "+f"(d[2]), "+f"(d[3]), "+f"(d[4]), "+f"(d[5]), "+f"(d[6]), "+f"(d[7]), "+f"(d[8]), "+f"(d[9]), "+f"(d[10]), "+f"(d[11]), "+f"(d[12]), "+f"(d[13]), "+f"(d[14]), "+f"(d[15]), "+f"(d[16]), "+f"(d[17]), "+f"(d[18]), "+f"(d[19]), "+f"(d[20]), "+f"(d[21]), "+f"(d[22]), "+f"(d[23]), "+f"(d[24]), "+f"(d[25]), "+f"(d[26]), "+f"(d[27]), "+f"(d[28]), "+f"(d[29]), "+f"(d[30]), "+f"(d[31])
    : "r"(a0), "r"(a1), "r"(a2), "r"(a3), "l"(descB), "r"(scaleD));
}
__device__ __forceinline__ void wgmma_rs_n24_tb(float (&d)[12], uint32_t a0, uint32_t a1, uint32_t a2, uint32_t a3, uint64_t descB, int scaleD) {
  asm volatile("{\n.reg .pred p;\nsetp.ne.b32 p, %17, 0;\n"
    "wgmma.mma_async.sync.aligned.m64n24k16.f32.bf16.bf16 {%0, %1, %2, %3, %4, %5, %6, %7, %8, %9, %10, %11}, {%12, %13, %14, %15}, %16, p, 1, 1, 1;\n}\n"
    : "+f"(d[0]), "+f"(d[1]), "+f"(d[2]), "+f"(d[3]), "+f"(d[4]), "+f"(d[5]), "+f"(d[6]), "+f"(d[7]), "+f"(d[8]), "+f"(d[9]), "+f"(d[10]), "+f"(d[11])
    : "r"(a0), "r"(a1), "r"(a2), "r"(a3), "l"(descB), "r"(scaleD));
}

constexpr int GT = 384;

__device__ __forceinline__ void release_stage(uint32_t bar, bool leader) {
  if (leader) {
    mbar_arrive_cluster(bar, 0);
    mbar_arrive_cluster(bar, 1);
  }
}

__device__ __forceinline__ void ln_row(const bf16* __restrict__ xin, bf16* __restrict__ xout, int l16) {
  const uint4* src = reinterpret_cast<const uint4*>(xin);
  uint4 v[5];
#pragma unroll
  for (int j = 0; j < 5; j++) v[j] = __ldg(src + j * 16 + l16);
  float s0 = 0.f, s1 = 0.f, s2 = 0.f, s3 = 0.f;
#pragma unroll
  for (int j = 0; j < 5; j++) {
    s0 += bf_lo(v[j].x) + bf_hi(v[j].x);
    s1 += bf_lo(v[j].y) + bf_hi(v[j].y);
    s2 += bf_lo(v[j].z) + bf_hi(v[j].z);
    s3 += bf_lo(v[j].w) + bf_hi(v[j].w);
  }
  float mean = (s0 + s1) + (s2 + s3);
#pragma unroll
  for (int o = 1; o < 16; o <<= 1) mean += __shfl_xor_sync(0xffffffffu, mean, o);
  mean *= (1.0f / DM);
  s0 = s1 = s2 = s3 = 0.f;
#pragma unroll
  for (int j = 0; j < 5; j++) {
    float d;
    d = bf_lo(v[j].x) - mean; s0 = fmaf(d, d, s0);
    d = bf_hi(v[j].x) - mean; s1 = fmaf(d, d, s1);
    d = bf_lo(v[j].y) - mean; s2 = fmaf(d, d, s2);
    d = bf_hi(v[j].y) - mean; s3 = fmaf(d, d, s3);
    d = bf_lo(v[j].z) - mean; s0 = fmaf(d, d, s0);
    d = bf_hi(v[j].z) - mean; s1 = fmaf(d, d, s1);
    d = bf_lo(v[j].w) - mean; s2 = fmaf(d, d, s2);
    d = bf_hi(v[j].w) - mean; s3 = fmaf(d, d, s3);
  }
  float sq = (s0 + s1) + (s2 + s3);
#pragma unroll
  for (int o = 1; o < 16; o <<= 1) sq += __shfl_xor_sync(0xffffffffu, sq, o);
  const float var_b = bf16_round(sq * (1.0f / DM));
  const float den = bf16_round(sqrtf(bf16_round(var_b + 1e-5f)));
  const float iv = __frcp_rn(den);
  const float mb = bf16_round(mean);
  uint4* dst = reinterpret_cast<uint4*>(xout);
#pragma unroll
  for (int j = 0; j < 5; j++) {
    uint4 w;
    uint32_t t;
    t = pack_bf16(bf_lo(v[j].x) - mb, bf_hi(v[j].x) - mb); w.x = pack_bf16(bf_lo(t) * iv, bf_hi(t) * iv);
    t = pack_bf16(bf_lo(v[j].y) - mb, bf_hi(v[j].y) - mb); w.y = pack_bf16(bf_lo(t) * iv, bf_hi(t) * iv);
    t = pack_bf16(bf_lo(v[j].z) - mb, bf_hi(v[j].z) - mb); w.z = pack_bf16(bf_lo(t) * iv, bf_hi(t) * iv);
    t = pack_bf16(bf_lo(v[j].w) - mb, bf_hi(v[j].w) - mb); w.w = pack_bf16(bf_lo(t) * iv, bf_hi(t) * iv);
    dst[j * 16 + l16] = w;
  }
}

constexpr int LG_STAGES = 5;
constexpr int QKV_STAGE = 8192 + 4 * 4096;
constexpr int GLU_STAGE = 8192 + 6 * 4096;

template <int WG>
__device__ __forceinline__ void qkv_mainloop(float (&acc)[120], uint32_t sbase, uint32_t sBar, bool leader) {
  constexpr int STAGE_BYTES = QKV_STAGE, NST = LG_STAGES;
  const uint64_t da_base = make_desc(sbase + WG * 4096, 16, 512, 2);
  const uint64_t db_base = make_desc(sbase + 8192, 4096, 1024, 1);
#pragma unroll 1
  for (int r = 0; r < 20 / NST; r++) {
#pragma unroll
    for (int s = 0; s < NST; s++) {
      mbar_wait(sBar + 8 * s, r & 1);
      wgmma_fence();
#pragma unroll
      for (int ks = 0; ks < 2; ks++)
        wgmma_ss_n240_tb(acc, da_base + (uint64_t)((s * STAGE_BYTES + ks * 32) >> 4), db_base + (uint64_t)((s * STAGE_BYTES + ks * 2048) >> 4), 1);
      wgmma_commit();
      wgmma_wait<1>();
      release_stage(sBar + 8 * (NST + (s + NST - 1) % NST), leader && (s > 0 || r > 0));
    }
  }
}
template <int WG>
__device__ __forceinline__ void glu_mainloop(float (&accg)[96], float (&accu)[96], uint32_t sbase, uint32_t sBar, bool leader) {
  constexpr int STAGE_BYTES = GLU_STAGE, NST = LG_STAGES;
  const uint64_t da_base = make_desc(sbase + WG * 4096, 16, 512, 2);
  const uint64_t db_base = make_desc(sbase + 8192, 4096, 1024, 1);
#pragma unroll 1
  for (int r = 0; r < 20 / NST; r++) {
#pragma unroll
    for (int s = 0; s < NST; s++) {
      mbar_wait(sBar + 8 * s, r & 1);
      wgmma_fence();
#pragma unroll
      for (int ks = 0; ks < 2; ks++) {
        const uint64_t da = da_base + (uint64_t)((s * STAGE_BYTES + ks * 32) >> 4);
        wgmma_ss_n192_tb(accg, da, db_base + (uint64_t)((s * STAGE_BYTES + ks * 2048) >> 4), 1);
        wgmma_ss_n192_tb(accu, da, db_base + (uint64_t)((s * STAGE_BYTES + 3 * 4096 + ks * 2048) >> 4), 1);
      }
      wgmma_commit();
      wgmma_wait<1>();
      release_stage(sBar + 8 * (NST + (s + NST - 1) % NST), leader && (s > 0 || r > 0));
    }
  }
}
constexpr int RG_STAGE_BYTES = 16384 + 8192 + 2048;
template <int NKB, int NST, int WG>
__device__ __forceinline__ void res_mainloop(float (&acc0)[32], float (&acc1)[8], uint32_t sbase, uint32_t sBar, bool leader) {
  const uint64_t da_base = make_desc(sbase + WG * 8192, 16, 1024, 1);
  const uint64_t db0_base = make_desc(sbase + 16384, 8192, 1024, 1);
  const uint64_t db1_base = make_desc(sbase + 16384 + 8192, 2048, 256, 3);
#pragma unroll 1
  for (int r = 0; r < NKB / NST; r++) {
#pragma unroll
    for (int s = 0; s < NST; s++) {
      const uint64_t so = (uint64_t)(s * (RG_STAGE_BYTES >> 4));
      mbar_wait(sBar + 8 * s, r & 1);
      wgmma_fence();
#pragma unroll
      for (int ks = 0; ks < 4; ks++) {
        wgmma_ss_n64_tb(acc0, da_base + so + ks * 2, db0_base + so + ks * 128, 1);
        wgmma_ss_n16_tb(acc1, da_base + so + ks * 2, db1_base + so + ks * 32, 1);
      }
      wgmma_commit();
      wgmma_wait<1>();
      release_stage(sBar + 8 * (NST + (s + NST - 1) % NST), leader && (s > 0 || r > 0));
    }
  }
}

constexpr int KA_SMEM = LG_STAGES * QKV_STAGE + 128 + 1024;

__global__ void __launch_bounds__(GT, 1)
qkv_kernel(const __grid_constant__ CUtensorMap tmA, const __grid_constant__ CUtensorMap tmB, const bf16* __restrict__ x) {
  constexpr int STAGE_BYTES = QKV_STAGE, NST = LG_STAGES, NKB = 20;
  extern __shared__ uint8_t smem_raw[];
  const uint32_t sbase = (smem_u32(smem_raw) + 1023u) & ~1023u;
  const uint32_t sBar = sbase + NST * STAGE_BYTES;
  const int tid = threadIdx.x, warp = tid >> 5, lane = tid & 31;
  const int rank = blockIdx.x & 1;
  const int pair = blockIdx.x >> 1;
  const int n_blk = pair & 7;
  const int m_blk = (pair >> 3) * 2 + rank;
  TS(0, 0);
  if (tid == 256) {
    prefetch_tmap(&tmA);
    prefetch_tmap(&tmB);
  }
  if (tid == 0) {
    for (int s = 0; s < NST; s++) {
      mbar_init(sBar + 8 * s, 1);
      mbar_init(sBar + 8 * (NST + s), 4);
    }
    fence_mbar_init();
    if (blockIdx.x < 32) g_flag[16 + blockIdx.x] = 0;
  }
  pdl_launch();
  cluster_sync_all();

  if (warp >= 8) {
    asm volatile("setmaxnreg.dec.sync.aligned.u32 40;");
    if (warp == 9) {
      named_bar_sync(5, 288);
      if (lane == 0) flag_signal(&g_flag[m_blk]);
    }
    if (tid == 256) {
      auto issue_b = [&](int kb) {
        const int s = kb % NST;
        const uint32_t full = sBar + 8 * s;
        mbar_expect_tx(full, STAGE_BYTES);
        const uint32_t dst = sbase + s * STAGE_BYTES + 8192;
#pragma unroll
        for (int j = 0; j < 2; j++) {
          const int sl = rank * 2 + j;
          tma_load_2d_mc(dst + sl * 4096, &tmB, n_blk * 240 + sl * 64, kb * 32, full, (uint16_t)3);
        }
      };
      for (int kb = 0; kb < NST; kb++) issue_b(kb);
      flag_wait(&g_flag[m_blk], 8);
      fence_proxy_async_all();
      for (int kb = 0; kb < NKB; kb++) {
        const int s = kb % NST;
        if (kb >= NST) {
          mbar_wait(sBar + 8 * (NST + s), ((kb / NST) & 1) ^ 1);
          issue_b(kb);
        }
        tma_load_2d(sbase + s * STAGE_BYTES, &tmA, kb * 32, m_blk * 128, sBar + 8 * s);
      }
    }
  } else {
    asm volatile("setmaxnreg.inc.sync.aligned.u32 232;");
    const int wg = __shfl_sync(0xffffffffu, warp >> 2, 0);
    const int wwarp = warp & 3;
    {
      const int row = m_blk * 128 + n_blk * 16 + warp * 2 + (lane >> 4);
      ln_row(x + (size_t)row * DM, g_xn + (size_t)row * DM, lane & 15);
      asm volatile("bar.arrive 5, 288;" ::: "memory");
    }
    TS(0, 1);
    mbar_wait(sBar, 0);
    TS(0, 3);
    float acc[120];
#pragma unroll
    for (int i = 0; i < 120; i++) acc[i] = 0.f;
    if (wg == 0) qkv_mainloop<0>(acc, sbase, sBar, (tid & 127) == 0);
    else qkv_mainloop<1>(acc, sbase, sBar, (tid & 127) == 0);
    wgmma_wait<0>();
    fence_regs(acc);
    TS(0, 4);
    named_bar_sync(3, 256);
    const int g = lane >> 2, c4 = lane & 3;
    const uint32_t stg = sbase + wg * (12 * 3072) + (wwarp * 2) * 384 + g * 16;
    const int hbase = n_blk * 12;
#pragma unroll
    for (int j = 0; j < 30; j++) {
      const int cb = (j * 8) % 20;
      const int hb = (j * 8) / 20;
      int d = cb + c4 * 2;
      int hl = hb;
      if (cb == 16 && c4 >= 2) { d -= 20; hl += 1; }
      const uint32_t a0 = stg + hl * 3072 + (d >> 3) * 128 + (d & 7) * 2;
      const int hg = hbase + hl;
      const float sc = hg < 32 ? ATT_SCALE_LOG2E : 1.0f;
      st_shared_b32(a0, pack_bf16(acc[4 * j] * sc, acc[4 * j + 1] * sc));
      st_shared_b32(a0 + 384, pack_bf16(acc[4 * j + 2] * sc, acc[4 * j + 3] * sc));
      if (d == 18) {
        const uint32_t pad0 = hg < 32 ? 0u : (hg < 64 ? 0x3f803f80u : 0x00003f80u);
        const uint32_t pad1 = (hg >= 32 && hg < 64) ? 0x00003f80u : 0u;
        st_shared_v2(a0 + 4, pad0, pad1);
        st_shared_v2(a0 + 388, pad0, pad1);
      }
      if (j % 10 == 9) {
        fence_proxy_async();
        named_bar_sync(1 + wg, 128);
        if ((tid & 127) < 4) {
          const int hs = (j / 10) * 4 + (tid & 127);
          bf16* dst = g_img + (size_t)(hbase + hs) * IMG_HEAD_ELEMS + (size_t)(m_blk * 16 + wg * 8) * 192;
          bulk_s2g(dst, sbase + wg * (12 * 3072) + hs * 3072, 3072);
          bulk_commit();
        }
      }
    }
    if ((tid & 127) < 4) bulk_wait_read();
  }
  __syncwarp();
  TS(0, 5);
  cluster_sync_relaxed();
  TS(0, 6);
}

constexpr int KC_NST1 = 5, KC_NST3 = 6;
constexpr int KC_STAGING = 160 * 1024;
constexpr int KC_BAR = KC_STAGING + 48 * 1024;
constexpr int KC_CS = KC_BAR + 512;
constexpr int KC_SMEM = KC_CS + 1536 + 1024;

__global__ void __launch_bounds__(GT, 1)
mlp_kernel(const __grid_constant__ CUtensorMap tmO, const __grid_constant__ CUtensorMap tmWo64, const __grid_constant__ CUtensorMap tmWo16,
           const __grid_constant__ CUtensorMap tmH, const __grid_constant__ CUtensorMap tmWg, const __grid_constant__ CUtensorMap tmWu,
           const __grid_constant__ CUtensorMap tmHHs, const __grid_constant__ CUtensorMap tmHH, const __grid_constant__ CUtensorMap tmWd64,
           const __grid_constant__ CUtensorMap tmWd16, const __grid_constant__ CUtensorMap tmHs, const __grid_constant__ CUtensorMap tmOut,
           const bf16* __restrict__ x) {
  extern __shared__ uint8_t smem_raw[];
  const uint32_t sbase = (smem_u32(smem_raw) + 1023u) & ~1023u;
  const uint32_t bar1 = sbase + KC_BAR;
  const uint32_t bar2 = bar1 + 128;
  const uint32_t bar3 = bar2 + 128;
  const uint32_t barD = bar3 + 128;
  const int tid = threadIdx.x, warp = tid >> 5, lane = tid & 31;
  const int rank = blockIdx.x & 1;
  const int pair = blockIdx.x >> 1;
  const int j_blk = pair & 7;
  const int m_blk = (pair >> 3) * 2 + rank;
  const int n0 = j_blk * 80;
  TS(2, 0);
  if (tid == 256) {
    prefetch_tmap(&tmO); prefetch_tmap(&tmWo64); prefetch_tmap(&tmWo16); prefetch_tmap(&tmH); prefetch_tmap(&tmWg);
    prefetch_tmap(&tmWu); prefetch_tmap(&tmHHs); prefetch_tmap(&tmHH); prefetch_tmap(&tmWd64); prefetch_tmap(&tmWd16);
    prefetch_tmap(&tmHs); prefetch_tmap(&tmOut);
  }
  if (tid == 0) {
    for (int s = 0; s < 5; s++) {
      mbar_init(bar1 + 8 * s, 1); mbar_init(bar1 + 8 * (5 + s), 4);
      mbar_init(bar2 + 8 * s, 1); mbar_init(bar2 + 8 * (5 + s), 4);
    }
    for (int s = 0; s < 6; s++) { mbar_init(bar3 + 8 * s, 1); mbar_init(bar3 + 8 * (6 + s), 4); }
    mbar_init(barD, 4); mbar_init(barD + 8, 4);
    fence_mbar_init();
  }
  cluster_sync_all();

  if (warp >= 8) {
    asm volatile("setmaxnreg.dec.sync.aligned.u32 40;");
    if (tid == 256) {
      auto issue_b80 = [&](const CUtensorMap* t64, const CUtensorMap* t16, uint32_t bars, int nst, int kb) {
        const int s = kb % nst;
        const uint32_t full = bars + 8 * s;
        const uint32_t st = sbase + s * RG_STAGE_BYTES;
        mbar_expect_tx(full, RG_STAGE_BYTES);
        tma_load_2d_mc(st + 16384 + rank * 4096, t64, n0, kb * 64 + rank * 32, full, (uint16_t)3);
        tma_load_2d_mc(st + 16384 + 8192 + rank * 1024, t16, n0 + 64, kb * 64 + rank * 32, full, (uint16_t)3);
      };
      for (int kb = 0; kb < KC_NST1; kb++) issue_b80(&tmWo64, &tmWo16, bar1, KC_NST1, kb);
      pdl_wait();
      for (int kb = 0; kb < 10; kb++) {
        const int s = kb % KC_NST1;
        if (kb >= KC_NST1) {
          mbar_wait(bar1 + 8 * (KC_NST1 + s), ((kb / KC_NST1) & 1) ^ 1);
          issue_b80(&tmWo64, &tmWo16, bar1, KC_NST1, kb);
        }
        tma_load_2d(sbase + s * RG_STAGE_BYTES, &tmO, kb * 64, m_blk * 128, bar1 + 8 * s);
      }
      auto issue_bglu = [&](int kb) {
        const int s = kb % LG_STAGES;
        const uint32_t full = bar2 + 8 * s;
        mbar_expect_tx(full, GLU_STAGE);
        const uint32_t dst = sbase + s * GLU_STAGE + 8192;
#pragma unroll
        for (int j = 0; j < 3; j++)
          tma_load_2d_mc(dst + (rank * 3 + j) * 4096, rank == 0 ? &tmWg : &tmWu, j_blk * 192 + j * 64, kb * 32, full, (uint16_t)3);
      };
      mbar_wait(barD, 0);
      for (int kb = 0; kb < LG_STAGES; kb++) issue_bglu(kb);
      flag_wait(&g_flag[16 + m_blk], 16);
      fence_proxy_async_all();
      for (int kb = 0; kb < 20; kb++) {
        const int s = kb % LG_STAGES;
        if (kb >= LG_STAGES) {
          mbar_wait(bar2 + 8 * (LG_STAGES + s), ((kb / LG_STAGES) & 1) ^ 1);
          issue_bglu(kb);
        }
        tma_load_2d(sbase + s * GLU_STAGE, &tmH, kb * 32, m_blk * 128, bar2 + 8 * s);
      }
      mbar_wait(barD + 8, 0);
      for (int kb = 0; kb < KC_NST3; kb++) issue_b80(&tmWd64, &tmWd16, bar3, KC_NST3, kb);
      flag_wait(&g_flag[32 + m_blk], 16);
      fence_proxy_async_all();
      for (int kb = 0; kb < 24; kb++) {
        const int s = kb % KC_NST3;
        if (kb >= KC_NST3) {
          mbar_wait(bar3 + 8 * (KC_NST3 + s), ((kb / KC_NST3) & 1) ^ 1);
          issue_b80(&tmWd64, &tmWd16, bar3, KC_NST3, kb);
        }
        tma_load_2d(sbase + s * RG_STAGE_BYTES, &tmHH, kb * 64, m_blk * 128, bar3 + 8 * s);
      }
    }
  } else {
    asm volatile("setmaxnreg.inc.sync.aligned.u32 232;");
    const int wg = __shfl_sync(0xffffffffu, warp >> 2, 0);
    const int wwarp = warp & 3;
    const int g = lane >> 2, c4 = lane & 3;
    const int row0 = m_blk * 128 + wg * 64 + wwarp * 16 + g;
    const bool leader = (tid & 127) == 0;
    const uint32_t stg80_base = sbase + KC_STAGING + wg * 24576;
    const uint32_t stg80 = stg80_base + (wwarp * 16 + g) * 160 + c4 * 4;
    {
      uint32_t res[20];
#pragma unroll
      for (int j = 0; j < 10; j++) {
        res[2 * j] = __ldg(reinterpret_cast<const uint32_t*>(x + (size_t)row0 * DM + n0 + j * 8 + c4 * 2));
        res[2 * j + 1] = __ldg(reinterpret_cast<const uint32_t*>(x + (size_t)(row0 + 8) * DM + n0 + j * 8 + c4 * 2));
      }
      float acc0[32], acc1[8];
#pragma unroll
      for (int i = 0; i < 32; i++) acc0[i] = 0.f;
#pragma unroll
      for (int i = 0; i < 8; i++) acc1[i] = 0.f;
      TS(2, 1);
      if (wg == 0) res_mainloop<10, KC_NST1, 0>(acc0, acc1, sbase, bar1, leader);
      else res_mainloop<10, KC_NST1, 1>(acc0, acc1, sbase, bar1, leader);
      wgmma_wait<0>();
      fence_regs(acc0); fence_regs(acc1);
      release_stage(barD, leader);
      TS(2, 4);
      float sum0 = 0.f, sum1 = 0.f;
#pragma unroll
      for (int j = 0; j < 10; j++) {
        const uint32_t a01 = j < 8 ? pack_bf16(acc0[4 * j], acc0[4 * j + 1]) : pack_bf16(acc1[4 * (j - 8)], acc1[4 * (j - 8) + 1]);
        const uint32_t a23 = j < 8 ? pack_bf16(acc0[4 * j + 2], acc0[4 * j + 3]) : pack_bf16(acc1[4 * (j - 8) + 2], acc1[4 * (j - 8) + 3]);
        res[2 * j] = pack_bf16(bf_lo(res[2 * j]) + bf_lo(a01), bf_hi(res[2 * j]) + bf_hi(a01));
        res[2 * j + 1] = pack_bf16(bf_lo(res[2 * j + 1]) + bf_lo(a23), bf_hi(res[2 * j + 1]) + bf_hi(a23));
        st_shared_b32(stg80 + j * 16, res[2 * j]);
        st_shared_b32(stg80 + 8 * 160 + j * 16, res[2 * j + 1]);
        sum0 += bf_lo(res[2 * j]) + bf_hi(res[2 * j]);
        sum1 += bf_lo(res[2 * j + 1]) + bf_hi(res[2 * j + 1]);
      }
      sum0 += __shfl_xor_sync(0xffffffffu, sum0, 1); sum1 += __shfl_xor_sync(0xffffffffu, sum1, 1);
      sum0 += __shfl_xor_sync(0xffffffffu, sum0, 2); sum1 += __shfl_xor_sync(0xffffffffu, sum1, 2);
      const float mu0 = sum0 * (1.0f / 80.0f), mu1 = sum1 * (1.0f / 80.0f);
      float q0 = 0.f, q1 = 0.f;
#pragma unroll
      for (int j = 0; j < 10; j++) {
        float d;
        d = bf_lo(res[2 * j]) - mu0; q0 = fmaf(d, d, q0);
        d = bf_hi(res[2 * j]) - mu0; q0 = fmaf(d, d, q0);
        d = bf_lo(res[2 * j + 1]) - mu1; q1 = fmaf(d, d, q1);
        d = bf_hi(res[2 * j + 1]) - mu1; q1 = fmaf(d, d, q1);
      }
      q0 += __shfl_xor_sync(0xffffffffu, q0, 1); q1 += __shfl_xor_sync(0xffffffffu, q1, 1);
      q0 += __shfl_xor_sync(0xffffffffu, q0, 2); q1 += __shfl_xor_sync(0xffffffffu, q1, 2);
      if (c4 == 0) {
        g_stats[row0 * 8 + j_blk] = make_float2(mu0, q0);
        g_stats[(row0 + 8) * 8 + j_blk] = make_float2(mu1, q1);
      }
      fence_proxy_async();
      named_bar_sync(1 + wg, 128);
      if (leader) {
        tma_store_2d(&tmHs, stg80_base, n0, m_blk * 128 + wg * 64);
        bulk_commit();
        bulk_wait_all();
        fence_proxy_async_all();
        flag_signal(&g_flag[16 + m_blk]);
      }
      TS(2, 5);
    }
    {
      pdl_wait();
      {
        float* cs_s = reinterpret_cast<float*>(smem_raw + (sbase - smem_u32(smem_raw)) + KC_CS);
        for (int i = tid; i < 384; i += 256) cs_s[i] = g_cs[(i >= 192 ? FF - 192 : 0) + j_blk * 192 + i];
        named_bar_sync(3, 256);
      }
      flag_wait(&g_flag[16 + m_blk], 16);
      float mb[2], iv[2];
#pragma unroll
      for (int h = 0; h < 2; h++) {
        const float4* sp = reinterpret_cast<const float4*>(g_stats + (row0 + 8 * h) * 8);
        const float4 p0 = sp[0], p1 = sp[1], p2 = sp[2], p3 = sp[3];
        const float mean = (((p0.x + p0.z) + (p1.x + p1.z)) + ((p2.x + p2.z) + (p3.x + p3.z))) * 0.125f;
        float m2 = ((p0.y + p0.w) + (p1.y + p1.w)) + ((p2.y + p2.w) + (p3.y + p3.w));
        float dd = 0.f, d;
        d = p0.x - mean; dd = fmaf(d, d, dd); d = p0.z - mean; dd = fmaf(d, d, dd);
        d = p1.x - mean; dd = fmaf(d, d, dd); d = p1.z - mean; dd = fmaf(d, d, dd);
        d = p2.x - mean; dd = fmaf(d, d, dd); d = p2.z - mean; dd = fmaf(d, d, dd);
        d = p3.x - mean; dd = fmaf(d, d, dd); d = p3.z - mean; dd = fmaf(d, d, dd);
        m2 = fmaf(dd, 80.0f, m2);
        const float var_b = bf16_round(m2 * (1.0f / DM));
        const float den = bf16_round(sqrtf(bf16_round(var_b + 1e-5f)));
        iv[h] = __frcp_rn(den);
        mb[h] = bf16_round(mean);
      }
      float accg[96], accu[96];
#pragma unroll
      for (int i = 0; i < 96; i++) { accg[i] = 0.f; accu[i] = 0.f; }
      TS(3, 3);
      if (wg == 0) glu_mainloop<0>(accg, accu, sbase, bar2, leader);
      else glu_mainloop<1>(accg, accu, sbase, bar2, leader);
      wgmma_wait<0>();
      fence_regs(accg); fence_regs(accu);
      release_stage(barD + 8, leader);
      TS(3, 4);
      const uint32_t stg = sbase + KC_STAGING + wg * 24576 + (wwarp * 16 + g) * 128 + c4 * 4;
      const float* csg = reinterpret_cast<const float*>(smem_raw + (sbase - smem_u32(smem_raw)) + KC_CS) + c4 * 2;
      const float nm0 = -mb[0] * iv[0], nm1 = -mb[1] * iv[1];
#pragma unroll
      for (int sl = 0; sl < 3; sl++) {
        float2 cgv[4], cuv[4];
#pragma unroll
        for (int jj = 0; jj < 8; jj++) {
          const int j = sl * 8 + jj;
          if ((jj & 3) == 0) {
#pragma unroll
            for (int q = 0; q < 4; q++) {
              cgv[q] = *reinterpret_cast<const float2*>(csg + (j + q) * 8);
              cuv[q] = *reinterpret_cast<const float2*>(csg + 192 + (j + q) * 8);
            }
          }
          const float2 cg = cgv[jj & 3], cu = cuv[jj & 3];
          const float r0 = fmaxf(fmaf(accg[4 * j], iv[0], nm0 * cg.x), 0.f) * fmaf(accu[4 * j], iv[0], nm0 * cu.x);
          const float r1 = fmaxf(fmaf(accg[4 * j + 1], iv[0], nm0 * cg.y), 0.f) * fmaf(accu[4 * j + 1], iv[0], nm0 * cu.y);
          const float r2 = fmaxf(fmaf(accg[4 * j + 2], iv[1], nm1 * cg.x), 0.f) * fmaf(accu[4 * j + 2], iv[1], nm1 * cu.x);
          const float r3 = fmaxf(fmaf(accg[4 * j + 3], iv[1], nm1 * cg.y), 0.f) * fmaf(accu[4 * j + 3], iv[1], nm1 * cu.y);
          const uint32_t a0 = stg + sl * 8192 + ((jj ^ g) << 4);
          st_shared_b32(a0, pack_bf16(r0, r1));
          st_shared_b32(a0 + 1024, pack_bf16(r2, r3));
        }
        fence_proxy_async();
        named_bar_sync(1 + wg, 128);
        if (leader) {
          tma_store_2d(&tmHHs, sbase + KC_STAGING + wg * 24576 + sl * 8192, j_blk * 192 + sl * 64, m_blk * 128 + wg * 64);
          bulk_commit();
        }
      }
      TS(3, 7);
      if (leader) {
        bulk_wait_all();
        TS(3, 8);
        fence_proxy_async_all();
        flag_signal(&g_flag[32 + m_blk]);
      }
      TS(3, 9);
    }
    {
      uint32_t res[20];
#pragma unroll
      for (int j = 0; j < 10; j++) {
        res[2 * j] = *reinterpret_cast<const uint32_t*>(g_h + (size_t)row0 * DM + n0 + j * 8 + c4 * 2);
        res[2 * j + 1] = *reinterpret_cast<const uint32_t*>(g_h + (size_t)(row0 + 8) * DM + n0 + j * 8 + c4 * 2);
      }
      float acc0[32], acc1[8];
#pragma unroll
      for (int i = 0; i < 32; i++) acc0[i] = 0.f;
#pragma unroll
      for (int i = 0; i < 8; i++) acc1[i] = 0.f;
      mbar_wait(bar3, 0);
      TS(4, 3);
      if (wg == 0) res_mainloop<24, KC_NST3, 0>(acc0, acc1, sbase, bar3, leader);
      else res_mainloop<24, KC_NST3, 1>(acc0, acc1, sbase, bar3, leader);
      wgmma_wait<0>();
      fence_regs(acc0); fence_regs(acc1);
      TS(4, 4);
#pragma unroll
      for (int j = 0; j < 10; j++) {
        const uint32_t a01 = j < 8 ? pack_bf16(acc0[4 * j], acc0[4 * j + 1]) : pack_bf16(acc1[4 * (j - 8)], acc1[4 * (j - 8) + 1]);
        const uint32_t a23 = j < 8 ? pack_bf16(acc0[4 * j + 2], acc0[4 * j + 3]) : pack_bf16(acc1[4 * (j - 8) + 2], acc1[4 * (j - 8) + 3]);
        st_shared_b32(stg80 + j * 16, pack_bf16(bf_lo(res[2 * j]) + bf_lo(a01), bf_hi(res[2 * j]) + bf_hi(a01)));
        st_shared_b32(stg80 + 8 * 160 + j * 16, pack_bf16(bf_lo(res[2 * j + 1]) + bf_lo(a23), bf_hi(res[2 * j + 1]) + bf_hi(a23)));
      }
      fence_proxy_async();
      named_bar_sync(1 + wg, 128);
      if (leader) {
        tma_store_2d(&tmOut, stg80_base, n0, m_blk * 128 + wg * 64);
        bulk_commit();
        bulk_wait_read();
      }
      TS(4, 5);
    }
  }
  __syncwarp();
  cluster_sync_relaxed();
  TS(4, 6);
}

constexpr int AT_THREADS = 512;
constexpr int AT_WGS = AT_THREADS / 128;
constexpr int AT_KV_BYTES = IMG_HEAD_ELEMS * 2;
constexpr int AT_SMEM = 2 * AT_KV_BYTES + 256 + 1024;
constexpr int AT_CHUNKS = 8;

__device__ __forceinline__ float exp2_poly(float x) {
  const float u = __saturatef(fmaf(x, 1.0f / 64.0f, 62.0f / 64.0f));
  const float MAGIC = 12582912.0f - 62.0f;
  const float r = fmaf(u, 64.0f, MAGIC);
  const float q = MAGIC - r;
  const float fr = fmaf(u, 64.0f, q);
  float p = fmaf(fr, 0.009570102207362652f, 0.05591785907745361f);
  p = fmaf(p, fr, 0.240247443318367f);
  p = fmaf(p, fr, 0.6931217908859253f);
  p = fmaf(p, fr, 0.9999992847442627f);
  return __uint_as_float(__float_as_uint(p) + (__float_as_uint(r) << 23));
}
__device__ __forceinline__ bool use_poly(int e) { return (e & 7) == 1; }

struct AttnState {
  uint32_t qa0, qa1, qa2, qa3, qa4, qa5;
  float M0, M1;
};

__device__ __forceinline__ bool attn_exp_fast(const float (&s)[32], uint32_t (&p)[16]) {
#pragma unroll
  for (int j = 0; j < 16; j++) {
    const float e0 = use_poly(2 * j) ? exp2_poly(s[2 * j]) : ex2(s[2 * j]);
    const float e1 = use_poly(2 * j + 1) ? exp2_poly(s[2 * j + 1]) : ex2(s[2 * j + 1]);
    p[j] = pack_bf16(e0, e1);
  }
  uint32_t acc_or = 0;
#pragma unroll
  for (int j = 0; j < 16; j++) acc_or |= p[j];
  return __any_sync(0xffffffffu, (acc_or & 0x40004000u) != 0);
}
__device__ __forceinline__ void attn_exp_exact(const float (&s)[32], uint32_t (&p)[16], float (&o)[12], AttnState& st, bool first, int c4) {
  float mx0 = fmaxf(s[0], s[1]), mx1 = fmaxf(s[2], s[3]);
#pragma unroll
  for (int j = 1; j < 8; j++) {
    mx0 = fmaxf(mx0, fmaxf(s[4 * j], s[4 * j + 1]));
    mx1 = fmaxf(mx1, fmaxf(s[4 * j + 2], s[4 * j + 3]));
  }
  mx0 = fmaxf(mx0, __shfl_xor_sync(0xffffffffu, mx0, 1));
  mx1 = fmaxf(mx1, __shfl_xor_sync(0xffffffffu, mx1, 1));
  mx0 = fmaxf(mx0, __shfl_xor_sync(0xffffffffu, mx0, 2));
  mx1 = fmaxf(mx1, __shfl_xor_sync(0xffffffffu, mx1, 2));
  float d0 = mx0 + 7.0f, d1 = mx1 + 7.0f;
  if (!first) { d0 = fmaxf(d0, 0.f); d1 = fmaxf(d1, 0.f); }
  const float T0 = st.M0 + d0, T1 = st.M1 + d1;
  const float h0 = bf16_round(T0), h1 = bf16_round(T1);
  const float i0 = bf16_round(T0 - h0), i1 = bf16_round(T1 - h1);
  const float l0 = bf16_round((T0 - h0) - i0), l1 = bf16_round((T1 - h1) - i1);
  const float N0 = (h0 + i0) + l0, N1 = (h1 + i1) + l1;
  d0 = N0 - st.M0; d1 = N1 - st.M1;
  st.M0 = N0; st.M1 = N1;
  if (c4 == 2) { st.qa4 = pack_bf16(-h0, -i0); st.qa5 = pack_bf16(-h1, -i1); }
  if (c4 == 3) { st.qa4 = pack_bf16(-l0, 0.f); st.qa5 = pack_bf16(-l1, 0.f); }
  if (!first) {
    const float al0 = ex2(-d0), al1 = ex2(-d1);
#pragma unroll
    for (int j = 0; j < 3; j++) {
      o[4 * j] *= al0; o[4 * j + 1] *= al0;
      o[4 * j + 2] *= al1; o[4 * j + 3] *= al1;
    }
  }
#pragma unroll
  for (int j = 0; j < 8; j++) {
    p[2 * j] = pack_bf16(ex2(s[4 * j] - d0), ex2(s[4 * j + 1] - d0));
    p[2 * j + 1] = pack_bf16(ex2(s[4 * j + 2] - d1), ex2(s[4 * j + 3] - d1));
  }
}
__device__ __forceinline__ void attn_step(float (&s)[32], const uint32_t (&pp)[16], uint32_t (&pn)[16], float (&o)[12], AttnState& st,
                                          uint32_t k_addr, uint32_t v_addr_prev, int keep, int c4, int wgdbg = 0, int tdbg = 0) {
  PH(wgdbg, tdbg, 0);
  const uint64_t dk = make_desc(k_addr, 128, 384, 0);
  const uint64_t dv_prev = make_desc(v_addr_prev, 384, 128, 0);
  wgmma_fence();
  wgmma_rs_n64(s, st.qa0, st.qa1, st.qa2, st.qa3, dk, 0);
  wgmma_rs_n64(s, st.qa4, st.qa5, 0u, 0u, dk + 16, 1);
  wgmma_commit();
#pragma unroll
  for (int kk = 0; kk < 4; kk++) wgmma_rs_n24_tb(o, pp[4 * kk], pp[4 * kk + 1], pp[4 * kk + 2], pp[4 * kk + 3], dv_prev + kk * 48, kk == 0 ? keep : 1);
  wgmma_commit();
  wgmma_wait<1>();
  fence_regs(s);
  PH(wgdbg, tdbg, 1);
  const bool redo = attn_exp_fast(s, pn);
  PH(wgdbg, tdbg, 2);
  wgmma_wait<0>();
  fence_regs(o);
  if (redo) attn_exp_exact(s, pn, o, st, false, c4);
}

__global__ void __launch_bounds__(AT_THREADS, 1) attn_kernel(const bf16* __restrict__ wo, const bf16* __restrict__ wgt, const bf16* __restrict__ wup, const bf16* __restrict__ wdn) {
  extern __shared__ uint8_t smem_raw[];
  const uint32_t sbase = (smem_u32(smem_raw) + 1023u) & ~1023u;
  const uint32_t sK = sbase, sV = sbase + AT_KV_BYTES;
  const uint32_t sBar = sV + AT_KV_BYTES;
  const int tid = threadIdx.x, warp = tid >> 5, lane = tid & 31;
  const int head = blockIdx.x >> 2, quarter = blockIdx.x & 3;
  if (blockIdx.x >= 128) {
    pdl_launch();
    const int b = blockIdx.x - 128;
    const bf16* w = (b >> 1) ? wup : wgt;
    const int cgrp = tid % 96, rgrp = tid / 96;
    float acc[8];
#pragma unroll
    for (int i = 0; i < 8; i++) acc[i] = 0.f;
    float* red = reinterpret_cast<float*>(smem_raw);
    if (rgrp < 5) {
      const uint4* src = reinterpret_cast<const uint4*>(w + (size_t)(rgrp * 128) * FF + (b & 1) * 768 + cgrp * 8);
#pragma unroll 8
      for (int r = 0; r < 128; r++) {
        const uint4 v = __ldg(src + (size_t)r * (FF / 8));
        acc[0] += bf_lo(v.x); acc[1] += bf_hi(v.x); acc[2] += bf_lo(v.y); acc[3] += bf_hi(v.y);
        acc[4] += bf_lo(v.z); acc[5] += bf_hi(v.z); acc[6] += bf_lo(v.w); acc[7] += bf_hi(v.w);
      }
#pragma unroll
      for (int i = 0; i < 8; i++) red[rgrp * 768 + cgrp * 8 + i] = acc[i];
    }
    __syncthreads();
    pdl_wait();
    for (int c = tid; c < 768; c += AT_THREADS)
      g_cs[(b >> 1) * FF + (b & 1) * 768 + c] = ((red[c] + red[768 + c]) + (red[1536 + c] + red[2304 + c])) + red[3072 + c];
    if (b == 0 && tid < 16) g_flag[tid] = 0;
    return;
  }
  TS(1, 0);
  if (tid == 0) {
    for (int i = 0; i < AT_CHUNKS; i++) mbar_init(sBar + 8 * i, 1);
    fence_mbar_init();
  }
  pdl_launch();
  if (tid == 32) {
    prefetch_l2(reinterpret_cast<const uint8_t*>(wo) + blockIdx.x * 6400, 6400);
    prefetch_l2(reinterpret_cast<const uint8_t*>(wgt) + blockIdx.x * 15360, 15360);
    prefetch_l2(reinterpret_cast<const uint8_t*>(wup) + blockIdx.x * 15360, 15360);
    prefetch_l2(reinterpret_cast<const uint8_t*>(wdn) + blockIdx.x * 15360, 15360);
  }
  __syncthreads();
  TS(1, 1);
  pdl_wait();
  TS(1, 2);
  if (tid == 0) {
    const uint8_t* kg = reinterpret_cast<const uint8_t*>(g_img + (size_t)(32 + head) * IMG_HEAD_ELEMS);
    const uint8_t* vg = reinterpret_cast<const uint8_t*>(g_img + (size_t)(64 + head) * IMG_HEAD_ELEMS);
    constexpr int CB = AT_KV_BYTES / AT_CHUNKS;
    for (int i = 0; i < AT_CHUNKS; i++) {
      mbar_expect_tx(sBar + 8 * i, 2 * CB);
      bulk_g2s(sK + i * CB, kg + i * CB, CB, sBar + 8 * i);
      bulk_g2s(sV + i * CB, vg + i * CB, CB, sBar + 8 * i);
    }
  }
  const int wg = warp >> 2, wwarp = warp & 3;
  const int g = lane >> 2, c4 = lane & 3;
  const uint64_t dk_base = make_desc(sK, 128, 384, 0);
  const uint64_t dv_base = make_desc(sV, 384, 128, 0);

  uint32_t qn[6];
  {
    const bf16* q0 = g_img + (size_t)head * IMG_HEAD_ELEMS + (size_t)((quarter * 512 + wg * 64 + wwarp * 16) >> 3) * 192 + g * 8 + c4 * 2;
    qn[0] = *reinterpret_cast<const uint32_t*>(q0);
    qn[1] = *reinterpret_cast<const uint32_t*>(q0 + 192);
    qn[2] = *reinterpret_cast<const uint32_t*>(q0 + 64);
    qn[3] = *reinterpret_cast<const uint32_t*>(q0 + 192 + 64);
    qn[4] = *reinterpret_cast<const uint32_t*>(q0 + 128);
    qn[5] = *reinterpret_cast<const uint32_t*>(q0 + 192 + 128);
  }
#pragma unroll 1
  for (int rep = 0; rep < 8 / AT_WGS; rep++) {
    const int row0 = quarter * 512 + (rep * AT_WGS + wg) * 64 + wwarp * 16 + g;
    AttnState st;
    st.qa0 = qn[0]; st.qa1 = qn[1]; st.qa2 = qn[2]; st.qa3 = qn[3]; st.qa4 = qn[4]; st.qa5 = qn[5];
    if (rep + 1 < 8 / AT_WGS) {
      const bf16* q0 = g_img + (size_t)head * IMG_HEAD_ELEMS + (size_t)((row0 + AT_WGS * 64) >> 3) * 192 + g * 8 + c4 * 2;
      qn[0] = *reinterpret_cast<const uint32_t*>(q0);
      qn[1] = *reinterpret_cast<const uint32_t*>(q0 + 192);
      qn[2] = *reinterpret_cast<const uint32_t*>(q0 + 64);
      qn[3] = *reinterpret_cast<const uint32_t*>(q0 + 192 + 64);
      qn[4] = *reinterpret_cast<const uint32_t*>(q0 + 128);
      qn[5] = *reinterpret_cast<const uint32_t*>(q0 + 192 + 128);
    }
    float o[12];
    float s[32];
    uint32_t pa[16], pb[16];
    st.M0 = st.M1 = 0.f;
    if (rep == 0) mbar_wait(sBar, 0);
    wgmma_fence();
    wgmma_rs_n64(s, st.qa0, st.qa1, st.qa2, st.qa3, dk_base, 0);
    wgmma_rs_n64(s, st.qa4, st.qa5, 0u, 0u, dk_base + 16, 1);
    wgmma_commit();
    wgmma_wait<0>();
    fence_regs(s);
    attn_exp_exact(s, pa, o, st, true, c4);
    attn_step(s, pa, pb, o, st, sK + 3072, sV, 0, c4);
#pragma unroll 1
    for (int tt = 1; tt < 16; tt++) {
      if (rep == 0 && !(tt & 1)) mbar_wait(sBar + 8 * (tt >> 1), 0);
      attn_step(s, pb, pa, o, st, sK + tt * 6144, sV + tt * 6144 - 3072, 1, c4, wg, rep * 32 + tt * 2);
      attn_step(s, pa, pb, o, st, sK + tt * 6144 + 3072, sV + tt * 6144, 1, c4, wg, rep * 32 + tt * 2 + 1);
    }
    wgmma_fence();
#pragma unroll
    for (int kk = 0; kk < 4; kk++) wgmma_rs_n24_tb(o, pb[4 * kk], pb[4 * kk + 1], pb[4 * kk + 2], pb[4 * kk + 3], dv_base + 31 * 192 + kk * 48, 1);
    wgmma_commit();
    wgmma_wait<0>();
    fence_regs(o);
    TS(1, 3 + rep);
    const float l0 = __shfl_sync(0xffffffffu, o[8], (lane & ~3) | 2);
    const float l1 = __shfl_sync(0xffffffffu, o[10], (lane & ~3) | 2);
    const float i0 = 1.0f / l0, i1 = 1.0f / l1;
    bf16* o0 = g_o + (size_t)row0 * DM + head * DH;
    bf16* o1 = o0 + 8 * DM;
#pragma unroll
    for (int j = 0; j < 3; j++) {
      if (j < 2 || c4 < 2) {
        *reinterpret_cast<uint32_t*>(o0 + j * 8 + c4 * 2) = pack_bf16(o[4 * j] * i0, o[4 * j + 1] * i0);
        *reinterpret_cast<uint32_t*>(o1 + j * 8 + c4 * 2) = pack_bf16(o[4 * j + 2] * i1, o[4 * j + 3] * i1);
      }
    }
  }
}

typedef CUresult (*EncodeTiledFn)(CUtensorMap*, CUtensorMapDataType, cuuint32_t, void*, const cuuint64_t*, const cuuint64_t*,
                                  const cuuint32_t*, const cuuint32_t*, CUtensorMapInterleave, CUtensorMapSwizzle,
                                  CUtensorMapL2promotion, CUtensorMapFloatOOBfill);

static void make_map(EncodeTiledFn fn, CUtensorMap* tm, const void* ptr, uint64_t rows, uint64_t cols, uint32_t box_rows,
                     uint32_t box_cols, CUtensorMapSwizzle sw) {
  cuuint64_t dims[2] = {cols, rows};
  cuuint64_t strides[1] = {cols * 2};
  cuuint32_t box[2] = {box_cols, box_rows};
  cuuint32_t es[2] = {1, 1};
  fn(tm, CU_TENSOR_MAP_DATA_TYPE_BFLOAT16, 2, const_cast<void*>(ptr), dims, strides, box, es, CU_TENSOR_MAP_INTERLEAVE_NONE, sw,
     CU_TENSOR_MAP_L2_PROMOTION_L2_256B, CU_TENSOR_MAP_FLOAT_OOB_FILL_NONE);
}

template <typename... KArgs, typename... Args>
static void launch(void (*kern)(KArgs...), int grid, int block, int smem, int cluster, bool pdl, Args... args) {
  cudaLaunchConfig_t cfg = {};
  cfg.gridDim = dim3(grid);
  cfg.blockDim = dim3(block);
  cfg.dynamicSmemBytes = smem;
  cfg.stream = cudaStreamPerThread;
  cudaLaunchAttribute at[2];
  int n = 0;
  if (cluster > 1) {
    at[n].id = cudaLaunchAttributeClusterDimension;
    at[n].val.clusterDim.x = cluster; at[n].val.clusterDim.y = 1; at[n].val.clusterDim.z = 1;
    n++;
  }
  if (pdl) {
    at[n].id = cudaLaunchAttributeProgrammaticStreamSerialization;
    at[n].val.programmaticStreamSerializationAllowed = 1;
    n++;
  }
  cfg.attrs = at;
  cfg.numAttrs = n;
  cudaLaunchKernelEx(&cfg, kern, KArgs(args)...);
}

extern "C" void kernel_launch(void* const* d_in, const int* in_sizes, int n_in, void* d_out, int out_size) {
  const bf16* x = (const bf16*)d_in[0];
  const bf16* wqkv = (const bf16*)d_in[1];
  const bf16* wo = (const bf16*)d_in[2];
  const bf16* wg = (const bf16*)d_in[4];
  const bf16* wu = (const bf16*)d_in[5];
  const bf16* wd = (const bf16*)d_in[6];
  bf16* out = (bf16*)d_out;

  static EncodeTiledFn enc = nullptr;
  static void *p_o = nullptr, *p_h = nullptr, *p_hh = nullptr, *p_xn = nullptr;
  if (!enc) {
    void* fn = nullptr;
    cudaDriverEntryPointQueryResult qr;
    cudaGetDriverEntryPoint("cuTensorMapEncodeTiled", &fn, cudaEnableDefault, &qr);
    enc = (EncodeTiledFn)fn;
    cudaGetSymbolAddress(&p_o, g_o);
    cudaGetSymbolAddress(&p_h, g_h);
    cudaGetSymbolAddress(&p_hh, g_hh);
    cudaGetSymbolAddress(&p_xn, g_xn);
    cudaFuncSetAttribute(qkv_kernel, cudaFuncAttributeMaxDynamicSharedMemorySize, KA_SMEM);
    cudaFuncSetAttribute(mlp_kernel, cudaFuncAttributeMaxDynamicSharedMemorySize, KC_SMEM);
    cudaFuncSetAttribute(attn_kernel, cudaFuncAttributeMaxDynamicSharedMemorySize, AT_SMEM);
  }
  CUtensorMap tm_wqkv, tm_wg, tm_wu, tm_wo64, tm_wo16, tm_wd64, tm_wd16, tm_o, tm_h, tm_hh, tm_hhs, tm_xn, tm_hs, tm_out;
  make_map(enc, &tm_wqkv, wqkv, DM, 3 * DM, 32, 64, CU_TENSOR_MAP_SWIZZLE_128B);
  make_map(enc, &tm_wg, wg, DM, FF, 32, 64, CU_TENSOR_MAP_SWIZZLE_128B);
  make_map(enc, &tm_wu, wu, DM, FF, 32, 64, CU_TENSOR_MAP_SWIZZLE_128B);
  make_map(enc, &tm_wo64, wo, DM, DM, 32, 64, CU_TENSOR_MAP_SWIZZLE_128B);
  make_map(enc, &tm_wo16, wo, DM, DM, 32, 16, CU_TENSOR_MAP_SWIZZLE_32B);
  make_map(enc, &tm_wd64, wd, FF, DM, 32, 64, CU_TENSOR_MAP_SWIZZLE_128B);
  make_map(enc, &tm_wd16, wd, FF, DM, 32, 16, CU_TENSOR_MAP_SWIZZLE_32B);
  make_map(enc, &tm_o, p_o, SEQ, DM, 128, 64, CU_TENSOR_MAP_SWIZZLE_128B);
  make_map(enc, &tm_h, p_h, SEQ, DM, 128, 32, CU_TENSOR_MAP_SWIZZLE_64B);
  make_map(enc, &tm_hh, p_hh, SEQ, FF, 128, 64, CU_TENSOR_MAP_SWIZZLE_128B);
  make_map(enc, &tm_hhs, p_hh, SEQ, FF, 64, 64, CU_TENSOR_MAP_SWIZZLE_128B);
  make_map(enc, &tm_xn, p_xn, SEQ, DM, 128, 32, CU_TENSOR_MAP_SWIZZLE_64B);
  make_map(enc, &tm_hs, p_h, SEQ, DM, 64, 80, CU_TENSOR_MAP_SWIZZLE_NONE);
  make_map(enc, &tm_out, out, SEQ, DM, 64, 80, CU_TENSOR_MAP_SWIZZLE_NONE);

  launch(qkv_kernel, 128, GT, KA_SMEM, 2, false, tm_xn, tm_wqkv, x);
  launch(attn_kernel, 132, AT_THREADS, AT_SMEM, 1, true, wo, wg, wu, wd);
  launch(mlp_kernel, 128, GT, KC_SMEM, 2, true, tm_o, tm_wo64, tm_wo16, tm_h, tm_wg, tm_wu, tm_hhs, tm_hh, tm_wd64, tm_wd16, tm_hs, tm_out, x);
}
```

```cpp
#include <cuda_runtime.h>
#include <cuda_bf16.h>
#include <cuda.h>
#include <stdint.h>

typedef __nv_bfloat16 bf16;

constexpr int SEQ = 2048, DM = 640, NH = 32, DH = 20, FF = 1536;
constexpr float ATT_SCALE_LOG2E = 0.22360679774997896f * 1.4426950408889634f;
constexpr int IMG_HEAD_ELEMS = (SEQ / 8) * 192;

__device__ __align__(1024) bf16 g_img[3 * NH * IMG_HEAD_ELEMS];
__device__ __align__(1024) bf16 g_o[SEQ * DM];
__device__ __align__(1024) bf16 g_h[SEQ * DM];
__device__ __align__(1024) bf16 g_xn[SEQ * DM];
__device__ float2 g_stats[SEQ * 8];
__device__ float g_cs[2 * FF];
__device__ int g_flag[32 + 128];
__device__ __align__(1024) bf16 g_hh[SEQ * FF];

#define TS(k, i)
#define PH(w, t, i)
__device__ __forceinline__ uint32_t smem_u32(const void* p) { return (uint32_t)__cvta_generic_to_shared(p); }
__device__ __forceinline__ void mbar_init(uint32_t bar, uint32_t cnt) {
  asm volatile("mbarrier.init.shared::cta.b64 [%0], %1;" ::"r"(bar), "r"(cnt) : "memory");
}
__device__ __forceinline__ void mbar_expect_tx(uint32_t bar, uint32_t bytes) {
  asm volatile("mbarrier.arrive.expect_tx.shared::cta.b64 _, [%0], %1;" ::"r"(bar), "r"(bytes) : "memory");
}
__device__ __forceinline__ void mbar_arrive(uint32_t bar) {
  asm volatile("mbarrier.arrive.shared::cta.b64 _, [%0];" ::"r"(bar) : "memory");
}
__device__ __forceinline__ void mbar_arrive_cluster(uint32_t bar, uint32_t cta) {
  asm volatile(
      "{\n.reg .b32 r;\nmapa.shared::cluster.u32 r, %0, %1;\n"
      "mbarrier.arrive.shared::cluster.b64 _, [r];\n}\n" ::"r"(bar), "r"(cta)
      : "memory");
}
__device__ __forceinline__ void mbar_wait(uint32_t bar, uint32_t parity) {
  asm volatile(
      "{\n.reg .pred p;\nLAB_WAIT:\n"
      "mbarrier.try_wait.parity.shared::cta.b64 p, [%0], %1;\n"
      "@p bra DONE;\nbra LAB_WAIT;\nDONE:\n}\n" ::"r"(bar), "r"(parity)
      : "memory");
}
__device__ __forceinline__ void mbar_wait_cluster(uint32_t bar, uint32_t parity) {
  asm volatile(
      "{\n.reg .pred p;\nLAB_WAIT:\n"
      "mbarrier.try_wait.parity.acquire.cluster.shared::cta.b64 p, [%0], %1;\n"
      "@p bra DONE;\nbra LAB_WAIT;\nDONE:\n}\n" ::"r"(bar), "r"(parity)
      : "memory");
}
__device__ __forceinline__ void fence_mbar_init() { asm volatile("fence.mbarrier_init.release.cluster;" ::: "memory"); }
__device__ __forceinline__ void fence_proxy_async() { asm volatile("fence.proxy.async.shared::cta;" ::: "memory"); }
__device__ __forceinline__ void cluster_sync_all() {
  asm volatile("barrier.cluster.arrive.release.aligned;\nbarrier.cluster.wait.acquire.aligned;" ::: "memory");
}
__device__ __forceinline__ void cluster_sync_relaxed() {
  asm volatile("barrier.cluster.arrive.relaxed.aligned;\nbarrier.cluster.wait.aligned;" ::: "memory");
}
__device__ __forceinline__ void named_bar_sync(int id, int n) { asm volatile("bar.sync %0, %1;" ::"r"(id), "r"(n) : "memory"); }
__device__ __forceinline__ bool wg_any(bool pred, int id) {
  uint32_t r;
  asm volatile("{\n.reg .pred p, q;\nsetp.ne.u32 p, %1, 0;\nbar.red.or.pred q, %2, 128, p;\nselp.u32 %0, 1, 0, q;\n}\n" : "=r"(r) : "r"((uint32_t)pred), "r"(id) : "memory");
  return r != 0;
}
__device__ __forceinline__ void fence_proxy_async_all() { asm volatile("fence.proxy.async;" ::: "memory"); }
__device__ __forceinline__ void flag_signal(int* f) {
  __threadfence();
  atomicAdd(f, 1);
}
__device__ __forceinline__ void flag_wait(const int* f, int target) {
  int v;
  unsigned spins = 0;
  do {
    asm volatile("ld.acquire.gpu.global.s32 %0, [%1];" : "=r"(v) : "l"(f) : "memory");
    if (++spins > (1u << 24)) __trap();
  } while (v < target);
}
__device__ __forceinline__ void pdl_launch() { asm volatile("griddepcontrol.launch_dependents;" ::: "memory"); }
__device__ __forceinline__ void pdl_wait() { asm volatile("griddepcontrol.wait;" ::: "memory"); }

__device__ __forceinline__ void tma_load_2d(uint32_t dst, const CUtensorMap* tm, int c0, int c1, uint32_t bar) {
  asm volatile(
      "cp.async.bulk.tensor.2d.shared::cluster.global.mbarrier::complete_tx::bytes [%0], [%1, {%3, %4}], [%2];" ::"r"(dst),
      "l"((uint64_t)tm), "r"(bar), "r"(c0), "r"(c1)
      : "memory");
}
__device__ __forceinline__ void tma_load_2d_mc(uint32_t dst, const CUtensorMap* tm, int c0, int c1, uint32_t bar, uint16_t mask) {
  asm volatile(
      "cp.async.bulk.tensor.2d.shared::cluster.global.mbarrier::complete_tx::bytes.multicast::cluster [%0], [%1, {%3, %4}], [%2], %5;" ::"r"(dst),
      "l"((uint64_t)tm), "r"(bar), "r"(c0), "r"(c1), "h"(mask)
      : "memory");
}
__device__ __forceinline__ void bulk_g2s(uint32_t dst, const void* src, uint32_t bytes, uint32_t bar) {
  asm volatile("cp.async.bulk.shared::cluster.global.mbarrier::complete_tx::bytes [%0], [%1], %2, [%3];" ::"r"(dst), "l"(src),
               "r"(bytes), "r"(bar)
               : "memory");
}
__device__ __forceinline__ void bulk_s2g(void* dst, uint32_t src, uint32_t bytes) {
  asm volatile("cp.async.bulk.global.shared::cta.bulk_group [%0], [%1], %2;" ::"l"(dst), "r"(src), "r"(bytes) : "memory");
}
__device__ __forceinline__ void tma_store_2d(const CUtensorMap* tm, uint32_t src, int c0, int c1) {
  asm volatile("cp.async.bulk.tensor.2d.global.shared::cta.bulk_group [%0, {%2, %3}], [%1];" ::"l"((uint64_t)tm), "r"(src), "r"(c0), "r"(c1) : "memory");
}
__device__ __forceinline__ void bulk_commit() { asm volatile("cp.async.bulk.commit_group;" ::: "memory"); }
__device__ __forceinline__ void bulk_wait_read() { asm volatile("cp.async.bulk.wait_group.read 0;" ::: "memory"); }
__device__ __forceinline__ void prefetch_l2(const void* p, uint32_t bytes) {
  asm volatile("cp.async.bulk.prefetch.L2.global [%0], %1;" ::"l"(p), "r"(bytes) : "memory");
}
__device__ __forceinline__ void bulk_wait_all() { asm volatile("cp.async.bulk.wait_group 0;" ::: "memory"); }
__device__ __forceinline__ void st_shared_b32(uint32_t addr, uint32_t v) { asm volatile("st.shared.b32 [%0], %1;" ::"r"(addr), "r"(v) : "memory"); }
__device__ __forceinline__ void st_shared_v2(uint32_t addr, uint32_t a, uint32_t b) { asm volatile("st.shared.v2.b32 [%0], {%1, %2};" ::"r"(addr), "r"(a), "r"(b) : "memory"); }
__device__ __forceinline__ void prefetch_tmap(const CUtensorMap* tm) {
  asm volatile("prefetch.tensormap [%0];" ::"l"((uint64_t)tm) : "memory");
}
__device__ __forceinline__ void wgmma_fence() { asm volatile("wgmma.fence.sync.aligned;" ::: "memory"); }
__device__ __forceinline__ void wgmma_commit() { asm volatile("wgmma.commit_group.sync.aligned;" ::: "memory"); }
template <int N>
__device__ __forceinline__ void wgmma_wait() { asm volatile("wgmma.wait_group.sync.aligned %0;" ::"n"(N) : "memory"); }

template <int N>
__device__ __forceinline__ void fence_regs(float (&r)[N]) {
#pragma unroll
  for (int i = 0; i < N; i++) asm volatile("" : "+f"(r[i])::"memory");
}
template <int N>
__device__ __forceinline__ void fence_regs(uint32_t (&r)[N]) {
#pragma unroll
  for (int i = 0; i < N; i++) asm volatile("" : "+r"(r[i])::"memory");
}
__device__ __forceinline__ uint64_t make_desc(uint32_t addr, uint32_t lbo, uint32_t sbo, uint32_t layout) {
  return (uint64_t)((addr & 0x3FFFF) >> 4) | ((uint64_t)((lbo & 0x3FFFF) >> 4) << 16) | ((uint64_t)((sbo & 0x3FFFF) >> 4) << 32) |
         ((uint64_t)layout << 62);
}
__device__ __forceinline__ uint32_t pack_bf16(float lo, float hi) {
  uint32_t r;
  asm("cvt.rn.bf16x2.f32 %0, %1, %2;" : "=r"(r) : "f"(hi), "f"(lo));
  return r;
}
__device__ __forceinline__ float bf16_round(float x) { return __bfloat162float(__float2bfloat16_rn(x)); }
__device__ __forceinline__ float bf_lo(uint32_t u) { return __uint_as_float(u << 16); }
__device__ __forceinline__ float bf_hi(uint32_t u) { return __uint_as_float(u & 0xffff0000u); }
__device__ __forceinline__ float ex2(float x) {
  float y;
  asm("ex2.approx.ftz.f32 %0, %1;" : "=f"(y) : "f"(x));
  return y;
}

__device__ __forceinline__ void wgmma_ss_n240_tb(float (&d)[120], uint64_t descA, uint64_t descB, int scaleD) {
  asm volatile("{\n.reg .pred p;\nsetp.ne.b32 p, %122, 0;\n"
    "wgmma.mma_async.sync.aligned.m64n240k16.f32.bf16.bf16 {%0, %1, %2, %3, %4, %5, %6, %7, %8, %9, %10, %11, %12, %13, %14, %15, %16, %17, %18, %19, %20, %21, %22, %23, %24, %25, %26, %27, %28, %29, %30, %31, %32, %33, %34, %35, %36, %37, %38, %39, %40, %41, %42, %43, %44, %45, %46, %47, %48, %49, %50, %51, %52, %53, %54, %55, %56, %57, %58, %59, %60, %61, %62, %63, %64, %65, %66, %67, %68, %69, %70, %71, %72, %73, %74, %75, %76, %77, %78, %79, %80, %81, %82, %83, %84, %85, %86, %87, %88, %89, %90, %91, %92, %93, %94, %95, %96, %97, %98, %99, %100, %101, %102, %103, %104, %105, %106, %107, %108, %109, %110, %111, %112, %113, %114, %115, %116, %117, %118, %119}, %120, %121, p, 1, 1, 0, 1;\n}\n"
    : "+f"(d[0]), "+f"(d[1]), "+f"(d[2]), "+f"(d[3]), "+f"(d[4]), "+f"(d[5]), "+f"(d[6]), "+f"(d[7]), "+f"(d[8]), "+f"(d[9]), "+f"(d[10]), "+f"(d[11]), "+f"(d[12]), "+f"(d[13]), "+f"(d[14]), "+f"(d[15]), "+f"(d[16]), "+f"(d[17]), "+f"(d[18]), "+f"(d[19]), "+f"(d[20]), "+f"(d[21]), "+f"(d[22]), "+f"(d[23]), "+f"(d[24]), "+f"(d[25]), "+f"(d[26]), "+f"(d[27]), "+f"(d[28]), "+f"(d[29]), "+f"(d[30]), "+f"(d[31]), "+f"(d[32]), "+f"(d[33]), "+f"(d[34]), "+f"(d[35]), "+f"(d[36]), "+f"(d[37]), "+f"(d[38]), "+f"(d[39]), "+f"(d[40]), "+f"(d[41]), "+f"(d[42]), "+f"(d[43]), "+f"(d[44]), "+f"(d[45]), "+f"(d[46]), "+f"(d[47]), "+f"(d[48]), "+f"(d[49]), "+f"(d[50]), "+f"(d[51]), "+f"(d[52]), "+f"(d[53]), "+f"(d[54]), "+f"(d[55]), "+f"(d[56]), "+f"(d[57]), "+f"(d[58]), "+f"(d[59]), "+f"(d[60]), "+f"(d[61]), "+f"(d[62]), "+f"(d[63]), "+f"(d[64]), "+f"(d[65]), "+f"(d[66]), "+f"(d[67]), "+f"(d[68]), "+f"(d[69]), "+f"(d[70]), "+f"(d[71]), "+f"(d[72]), "+f"(d[73]), "+f"(d[74]), "+f"(d[75]), "+f"(d[76]), "+f"(d[77]), "+f"(d[78]), "+f"(d[79]), "+f"(d[80]), "+f"(d[81]), "+f"(d[82]), "+f"(d[83]), "+f"(d[84]), "+f"(d[85]), "+f"(d[86]), "+f"(d[87]), "+f"(d[88]), "+f"(d[89]), "+f"(d[90]), "+f"(d[91]), "+f"(d[92]), "+f"(d[93]), "+f"(d[94]), "+f"(d[95]), "+f"(d[96]), "+f"(d[97]), "+f"(d[98]), "+f"(d[99]), "+f"(d[100]), "+f"(d[101]), "+f"(d[102]), "+f"(d[103]), "+f"(d[104]), "+f"(d[105]), "+f"(d[106]), "+f"(d[107]), "+f"(d[108]), "+f"(d[109]), "+f"(d[110]), "+f"(d[111]), "+f"(d[112]), "+f"(d[113]), "+f"(d[114]), "+f"(d[115]), "+f"(d[116]), "+f"(d[117]), "+f"(d[118]), "+f"(d[119])
    : "l"(descA), "l"(descB), "r"(scaleD));
}
__device__ __forceinline__ void wgmma_ss_n192_tb(float (&d)[96], uint64_t descA, uint64_t descB, int scaleD) {
  asm volatile("{\n.reg .pred p;\nsetp.ne.b32 p, %98, 0;\n"
    "wgmma.mma_async.sync.aligned.m64n192k16.f32.bf16.bf16 {%0, %1, %2, %3, %4, %5, %6, %7, %8, %9, %10, %11, %12, %13, %14, %15, %16, %17, %18, %19, %20, %21, %22, %23, %24, %25, %26, %27, %28, %29, %30, %31, %32, %33, %34, %35, %36, %37, %38, %39, %40, %41, %42, %43, %44, %45, %46, %47, %48, %49, %50, %51, %52, %53, %54, %55, %56, %57, %58, %59, %60, %61, %62, %63, %64, %65, %66, %67, %68, %69, %70, %71, %72, %73, %74, %75, %76, %77, %78, %79, %80, %81, %82, %83, %84, %85, %86, %87, %88, %89, %90, %91, %92, %93, %94, %95}, %96, %97, p, 1, 1, 0, 1;\n}\n"
    : "+f"(d[0]), "+f"(d[1]), "+f"(d[2]), "+f"(d[3]), "+f"(d[4]), "+f"(d[5]), "+f"(d[6]), "+f"(d[7]), "+f"(d[8]), "+f"(d[9]), "+f"(d[10]), "+f"(d[11]), "+f"(d[12]), "+f"(d[13]), "+f"(d[14]), "+f"(d[15]), "+f"(d[16]), "+f"(d[17]), "+f"(d[18]), "+f"(d[19]), "+f"(d[20]), "+f"(d[21]), "+f"(d[22]), "+f"(d[23]), "+f"(d[24]), "+f"(d[25]), "+f"(d[26]), "+f"(d[27]), "+f"(d[28]), "+f"(d[29]), "+f"(d[30]), "+f"(d[31]), "+f"(d[32]), "+f"(d[33]), "+f"(d[34]), "+f"(d[35]), "+f"(d[36]), "+f"(d[37]), "+f"(d[38]), "+f"(d[39]), "+f"(d[40]), "+f"(d[41]), "+f"(d[42]), "+f"(d[43]), "+f"(d[44]), "+f"(d[45]), "+f"(d[46]), "+f"(d[47]), "+f"(d[48]), "+f"(d[49]), "+f"(d[50]), "+f"(d[51]), "+f"(d[52]), "+f"(d[53]), "+f"(d[54]), "+f"(d[55]), "+f"(d[56]), "+f"(d[57]), "+f"(d[58]), "+f"(d[59]), "+f"(d[60]), "+f"(d[61]), "+f"(d[62]), "+f"(d[63]), "+f"(d[64]), "+f"(d[65]), "+f"(d[66]), "+f"(d[67]), "+f"(d[68]), "+f"(d[69]), "+f"(d[70]), "+f"(d[71]), "+f"(d[72]), "+f"(d[73]), "+f"(d[74]), "+f"(d[75]), "+f"(d[76]), "+f"(d[77]), "+f"(d[78]), "+f"(d[79]), "+f"(d[80]), "+f"(d[81]), "+f"(d[82]), "+f"(d[83]), "+f"(d[84]), "+f"(d[85]), "+f"(d[86]), "+f"(d[87]), "+f"(d[88]), "+f"(d[89]), "+f"(d[90]), "+f"(d[91]), "+f"(d[92]), "+f"(d[93]), "+f"(d[94]), "+f"(d[95])
    : "l"(descA), "l"(descB), "r"(scaleD));
}
__device__ __forceinline__ void wgmma_ss_n64_tb(float (&d)[32], uint64_t descA, uint64_t descB, int scaleD) {
  asm volatile("{\n.reg .pred p;\nsetp.ne.b32 p, %34, 0;\n"
    "wgmma.mma_async.sync.aligned.m64n64k16.f32.bf16.bf16 {%0, %1, %2, %3, %4, %5, %6, %7, %8, %9, %10, %11, %12, %13, %14, %15, %16, %17, %18, %19, %20, %21, %22, %23, %24, %25, %26, %27, %28, %29, %30, %31}, %32, %33, p, 1, 1, 0, 1;\n}\n"
    : "+f"(d[0]), "+f"(d[1]), "+f"(d[2]), "+f"(d[3]), "+f"(d[4]), "+f"(d[5]), "+f"(d[6]), "+f"(d[7]), "+f"(d[8]), "+f"(d[9]), "+f"(d[10]), "+f"(d[11]), "+f"(d[12]), "+f"(d[13]), "+f"(d[14]), "+f"(d[15]), "+f"(d[16]), "+f"(d[17]), "+f"(d[18]), "+f"(d[19]), "+f"(d[20]), "+f"(d[21]), "+f"(d[22]), "+f"(d[23]), "+f"(d[24]), "+f"(d[25]), "+f"(d[26]), "+f"(d[27]), "+f"(d[28]), "+f"(d[29]), "+f"(d[30]), "+f"(d[31])
    : "l"(descA), "l"(descB), "r"(scaleD));
}
__device__ __forceinline__ void wgmma_ss_n16_tb(float (&d)[8], uint64_t descA, uint64_t descB, int scaleD) {
  asm volatile("{\n.reg .pred p;\nsetp.ne.b32 p, %10, 0;\n"
    "wgmma.mma_async.sync.aligned.m64n16k16.f32.bf16.bf16 {%0, %1, %2, %3, %4, %5, %6, %7}, %8, %9, p, 1, 1, 0, 1;\n}\n"
    : "+f"(d[0]), "+f"(d[1]), "+f"(d[2]), "+f"(d[3]), "+f"(d[4]), "+f"(d[5]), "+f"(d[6]), "+f"(d[7])
    : "l"(descA), "l"(descB), "r"(scaleD));
}
__device__ __forceinline__ void wgmma_rs_n128(float (&d)[64], uint32_t a0, uint32_t a1, uint32_t a2, uint32_t a3, uint64_t descB, int scaleD) {
  asm volatile("{\n.reg .pred p;\nsetp.ne.b32 p, %69, 0;\n"
    "wgmma.mma_async.sync.aligned.m64n128k16.f32.bf16.bf16 {%0, %1, %2, %3, %4, %5, %6, %7, %8, %9, %10, %11, %12, %13, %14, %15, %16, %17, %18, %19, %20, %21, %22, %23, %24, %25, %26, %27, %28, %29, %30, %31, %32, %33, %34, %35, %36, %37, %38, %39, %40, %41, %42, %43, %44, %45, %46, %47, %48, %49, %50, %51, %52, %53, %54, %55, %56, %57, %58, %59, %60, %61, %62, %63}, {%64, %65, %66, %67}, %68, p, 1, 1, 0;\n}\n"
    : "+f"(d[0]), "+f"(d[1]), "+f"(d[2]), "+f"(d[3]), "+f"(d[4]), "+f"(d[5]), "+f"(d[6]), "+f"(d[7]), "+f"(d[8]), "+f"(d[9]), "+f"(d[10]), "+f"(d[11]), "+f"(d[12]), "+f"(d[13]), "+f"(d[14]), "+f"(d[15]), "+f"(d[16]), "+f"(d[17]), "+f"(d[18]), "+f"(d[19]), "+f"(d[20]), "+f"(d[21]), "+f"(d[22]), "+f"(d[23]), "+f"(d[24]), "+f"(d[25]), "+f"(d[26]), "+f"(d[27]), "+f"(d[28]), "+f"(d[29]), "+f"(d[30]), "+f"(d[31]), "+f"(d[32]), "+f"(d[33]), "+f"(d[34]), "+f"(d[35]), "+f"(d[36]), "+f"(d[37]), "+f"(d[38]), "+f"(d[39]), "+f"(d[40]), "+f"(d[41]), "+f"(d[42]), "+f"(d[43]), "+f"(d[44]), "+f"(d[45]), "+f"(d[46]), "+f"(d[47]), "+f"(d[48]), "+f"(d[49]), "+f"(d[50]), "+f"(d[51]), "+f"(d[52]), "+f"(d[53]), "+f"(d[54]), "+f"(d[55]), "+f"(d[56]), "+f"(d[57]), "+f"(d[58]), "+f"(d[59]), "+f"(d[60]), "+f"(d[61]), "+f"(d[62]), "+f"(d[63])
    : "r"(a0), "r"(a1), "r"(a2), "r"(a3), "l"(descB), "r"(scaleD));
}
__device__ __forceinline__ void wgmma_rs_n64(float (&d)[32], uint32_t a0, uint32_t a1, uint32_t a2, uint32_t a3, uint64_t descB, int scaleD) {
  asm volatile("{\n.reg .pred p;\nsetp.ne.b32 p, %37, 0;\n"
    "wgmma.mma_async.sync.aligned.m64n64k16.f32.bf16.bf16 {%0, %1, %2, %3, %4, %5, %6, %7, %8, %9, %10, %11, %12, %13, %14, %15, %16, %17, %18, %19, %20, %21, %22, %23, %24, %25, %26, %27, %28, %29, %30, %31}, {%32, %33, %34, %35}, %36, p, 1, 1, 0;\n}\n"
    : "+f"(d[0]), "+f"(d[1]), "+f"(d[2]), "+f"(d[3]), "+f"(d[4]), "+f"(d[5]), "+f"(d[6]), "+f"(d[7]), "+f"(d[8]), "+f"(d[9]), "+f"(d[10]), "+f"(d[11]), "+f"(d[12]), "+f"(d[13]), "+f"(d[14]), "+f"(d[15]), "+f"(d[16]), "+f"(d[17]), "+f"(d[18]), "+f"(d[19]), "+f"(d[20]), "+f"(d[21]), "+f"(d[22]), "+f"(d[23]), "+f"(d[24]), "+f"(d[25]), "+f"(d[26]), "+f"(d[27]), "+f"(d[28]), "+f"(d[29]), "+f"(d[30]), "+f"(d[31])
    : "r"(a0), "r"(a1), "r"(a2), "r"(a3), "l"(descB), "r"(scaleD));
}
__device__ __forceinline__ void wgmma_rs_n24_tb(float (&d)[12], uint32_t a0, uint32_t a1, uint32_t a2, uint32_t a3, uint64_t descB, int scaleD) {
  asm volatile("{\n.reg .pred p;\nsetp.ne.b32 p, %17, 0;\n"
    "wgmma.mma_async.sync.aligned.m64n24k16.f32.bf16.bf16 {%0, %1, %2, %3, %4, %5, %6, %7, %8, %9, %10, %11}, {%12, %13, %14, %15}, %16, p, 1, 1, 1;\n}\n"
    : "+f"(d[0]), "+f"(d[1]), "+f"(d[2]), "+f"(d[3]), "+f"(d[4]), "+f"(d[5]), "+f"(d[6]), "+f"(d[7]), "+f"(d[8]), "+f"(d[9]), "+f"(d[10]), "+f"(d[11])
    : "r"(a0), "r"(a1), "r"(a2), "r"(a3), "l"(descB), "r"(scaleD));
}

constexpr int GT = 384;

__device__ __forceinline__ void release_stage(uint32_t bar, bool leader) {
  if (leader) {
    mbar_arrive_cluster(bar, 0);
    mbar_arrive_cluster(bar, 1);
  }
}

__device__ __forceinline__ void ln_row(const bf16* __restrict__ xin, bf16* __restrict__ xout, int l16) {
  const uint4* src = reinterpret_cast<const uint4*>(xin);
  uint4 v[5];
#pragma unroll
  for (int j = 0; j < 5; j++) v[j] = __ldg(src + j * 16 + l16);
  float s0 = 0.f, s1 = 0.f, s2 = 0.f, s3 = 0.f;
#pragma unroll
  for (int j = 0; j < 5; j++) {
    s0 += bf_lo(v[j].x) + bf_hi(v[j].x);
    s1 += bf_lo(v[j].y) + bf_hi(v[j].y);
    s2 += bf_lo(v[j].z) + bf_hi(v[j].z);
    s3 += bf_lo(v[j].w) + bf_hi(v[j].w);
  }
  float mean = (s0 + s1) + (s2 + s3);
#pragma unroll
  for (int o = 1; o < 16; o <<= 1) mean += __shfl_xor_sync(0xffffffffu, mean, o);
  mean *= (1.0f / DM);
  s0 = s1 = s2 = s3 = 0.f;
#pragma unroll
  for (int j = 0; j < 5; j++) {
    float d;
    d = bf_lo(v[j].x) - mean; s0 = fmaf(d, d, s0);
    d = bf_hi(v[j].x) - mean; s1 = fmaf(d, d, s1);
    d = bf_lo(v[j].y) - mean; s2 = fmaf(d, d, s2);
    d = bf_hi(v[j].y) - mean; s3 = fmaf(d, d, s3);
    d = bf_lo(v[j].z) - mean; s0 = fmaf(d, d, s0);
    d = bf_hi(v[j].z) - mean; s1 = fmaf(d, d, s1);
    d = bf_lo(v[j].w) - mean; s2 = fmaf(d, d, s2);
    d = bf_hi(v[j].w) - mean; s3 = fmaf(d, d, s3);
  }
  float sq = (s0 + s1) + (s2 + s3);
#pragma unroll
  for (int o = 1; o < 16; o <<= 1) sq += __shfl_xor_sync(0xffffffffu, sq, o);
  const float var_b = bf16_round(sq * (1.0f / DM));
  const float den = bf16_round(sqrtf(bf16_round(var_b + 1e-5f)));
  const float iv = __frcp_rn(den);
  const float mb = bf16_round(mean);
  uint4* dst = reinterpret_cast<uint4*>(xout);
#pragma unroll
  for (int j = 0; j < 5; j++) {
    uint4 w;
    uint32_t t;
    t = pack_bf16(bf_lo(v[j].x) - mb, bf_hi(v[j].x) - mb); w.x = pack_bf16(bf_lo(t) * iv, bf_hi(t) * iv);
    t = pack_bf16(bf_lo(v[j].y) - mb, bf_hi(v[j].y) - mb); w.y = pack_bf16(bf_lo(t) * iv, bf_hi(t) * iv);
    t = pack_bf16(bf_lo(v[j].z) - mb, bf_hi(v[j].z) - mb); w.z = pack_bf16(bf_lo(t) * iv, bf_hi(t) * iv);
    t = pack_bf16(bf_lo(v[j].w) - mb, bf_hi(v[j].w) - mb); w.w = pack_bf16(bf_lo(t) * iv, bf_hi(t) * iv);
    dst[j * 16 + l16] = w;
  }
}

constexpr int LG_STAGES = 5;
constexpr int QKV_STAGE = 8192 + 4 * 4096;
constexpr int GLU_STAGE = 8192 + 6 * 4096;

template <int WG>
__device__ __forceinline__ void qkv_mainloop(float (&acc)[120], uint32_t sbase, uint32_t sBar, bool leader) {
  constexpr int STAGE_BYTES = QKV_STAGE, NST = LG_STAGES;
  const uint64_t da_base = make_desc(sbase + WG * 4096, 16, 512, 2);
  const uint64_t db_base = make_desc(sbase + 8192, 4096, 1024, 1);
#pragma unroll 1
  for (int r = 0; r < 20 / NST; r++) {
#pragma unroll
    for (int s = 0; s < NST; s++) {
      mbar_wait(sBar + 8 * s, r & 1);
      wgmma_fence();
#pragma unroll
      for (int ks = 0; ks < 2; ks++)
        wgmma_ss_n240_tb(acc, da_base + (uint64_t)((s * STAGE_BYTES + ks * 32) >> 4), db_base + (uint64_t)((s * STAGE_BYTES + ks * 2048) >> 4), 1);
      wgmma_commit();
      wgmma_wait<1>();
      release_stage(sBar + 8 * (NST + (s + NST - 1) % NST), leader && (s > 0 || r > 0));
    }
  }
}
template <int WG>
__device__ __forceinline__ void glu_mainloop(float (&accg)[96], float (&accu)[96], uint32_t sbase, uint32_t sBar, bool leader) {
  constexpr int STAGE_BYTES = GLU_STAGE, NST = LG_STAGES;
  const uint64_t da_base = make_desc(sbase + WG * 4096, 16, 512, 2);
  const uint64_t db_base = make_desc(sbase + 8192, 4096, 1024, 1);
#pragma unroll 1
  for (int r = 0; r < 20 / NST; r++) {
#pragma unroll
    for (int s = 0; s < NST; s++) {
      mbar_wait(sBar + 8 * s, r & 1);
      wgmma_fence();
#pragma unroll
      for (int ks = 0; ks < 2; ks++) {
        const uint64_t da = da_base + (uint64_t)((s * STAGE_BYTES + ks * 32) >> 4);
        wgmma_ss_n192_tb(accg, da, db_base + (uint64_t)((s * STAGE_BYTES + ks * 2048) >> 4), 1);
        wgmma_ss_n192_tb(accu, da, db_base + (uint64_t)((s * STAGE_BYTES + 3 * 4096 + ks * 2048) >> 4), 1);
      }
      wgmma_commit();
      wgmma_wait<1>();
      release_stage(sBar + 8 * (NST + (s + NST - 1) % NST), leader && (s > 0 || r > 0));
    }
  }
}
constexpr int RG_STAGE_BYTES = 16384 + 8192 + 2048;
template <int NKB, int NST, int WG>
__device__ __forceinline__ void res_mainloop(float (&acc0)[32], float (&acc1)[8], uint32_t sbase, uint32_t sBar, bool leader) {
  const uint64_t da_base = make_desc(sbase + WG * 8192, 16, 1024, 1);
  const uint64_t db0_base = make_desc(sbase + 16384, 8192, 1024, 1);
  const uint64_t db1_base = make_desc(sbase + 16384 + 8192, 2048, 256, 3);
#pragma unroll 1
  for (int r = 0; r < NKB / NST; r++) {
#pragma unroll
    for (int s = 0; s < NST; s++) {
      const uint64_t so = (uint64_t)(s * (RG_STAGE_BYTES >> 4));
      mbar_wait(sBar + 8 * s, r & 1);
      wgmma_fence();
#pragma unroll
      for (int ks = 0; ks < 4; ks++) {
        wgmma_ss_n64_tb(acc0, da_base + so + ks * 2, db0_base + so + ks * 128, 1);
        wgmma_ss_n16_tb(acc1, da_base + so + ks * 2, db1_base + so + ks * 32, 1);
      }
      wgmma_commit();
      wgmma_wait<1>();
      release_stage(sBar + 8 * (NST + (s + NST - 1) % NST), leader && (s > 0 || r > 0));
    }
  }
}

constexpr int KA_SMEM = LG_STAGES * QKV_STAGE + 128 + 1024;

__global__ void __launch_bounds__(GT, 1)
qkv_kernel(const __grid_constant__ CUtensorMap tmA, const __grid_constant__ CUtensorMap tmB, const bf16* __restrict__ x) {
  constexpr int STAGE_BYTES = QKV_STAGE, NST = LG_STAGES, NKB = 20;
  extern __shared__ uint8_t smem_raw[];
  const uint32_t sbase = (smem_u32(smem_raw) + 1023u) & ~1023u;
  const uint32_t sBar = sbase + NST * STAGE_BYTES;
  const int tid = threadIdx.x, warp = tid >> 5, lane = tid & 31;
  const int rank = blockIdx.x & 1;
  const int pair = blockIdx.x >> 1;
  const int n_blk = pair & 7;
  const int m_blk = (pair >> 3) * 2 + rank;
  TS(0, 0);
  if (tid == 256) {
    prefetch_tmap(&tmA);
    prefetch_tmap(&tmB);
  }
  if (tid == 0) {
    for (int s = 0; s < NST; s++) {
      mbar_init(sBar + 8 * s, 1);
      mbar_init(sBar + 8 * (NST + s), 4);
    }
    fence_mbar_init();
    if (blockIdx.x < 16) g_flag[16 + blockIdx.x] = 0;
    g_flag[32 + blockIdx.x] = 0;
  }
  pdl_launch();
  cluster_sync_all();

  if (warp >= 8) {
    asm volatile("setmaxnreg.dec.sync.aligned.u32 40;");
    if (warp == 9) {
      named_bar_sync(5, 288);
      if (lane == 0) flag_signal(&g_flag[m_blk]);
    }
    if (tid == 256) {
      auto issue_b = [&](int kb) {
        const int s = kb % NST;
        const uint32_t full = sBar + 8 * s;
        mbar_expect_tx(full, STAGE_BYTES);
        const uint32_t dst = sbase + s * STAGE_BYTES + 8192;
#pragma unroll
        for (int j = 0; j < 2; j++) {
          const int sl = rank * 2 + j;
          tma_load_2d_mc(dst + sl * 4096, &tmB, n_blk * 240 + sl * 64, kb * 32, full, (uint16_t)3);
        }
      };
      for (int kb = 0; kb < NST; kb++) issue_b(kb);
      flag_wait(&g_flag[m_blk], 8);
      fence_proxy_async_all();
      for (int kb = 0; kb < NKB; kb++) {
        const int s = kb % NST;
        if (kb >= NST) {
          mbar_wait(sBar + 8 * (NST + s), ((kb / NST) & 1) ^ 1);
          issue_b(kb);
        }
        tma_load_2d(sbase + s * STAGE_BYTES, &tmA, kb * 32, m_blk * 128, sBar + 8 * s);
      }
    }
  } else {
    asm volatile("setmaxnreg.inc.sync.aligned.u32 232;");
    const int wg = __shfl_sync(0xffffffffu, warp >> 2, 0);
    const int wwarp = warp & 3;
    {
      const int row = m_blk * 128 + n_blk * 16 + warp * 2 + (lane >> 4);
      ln_row(x + (size_t)row * DM, g_xn + (size_t)row * DM, lane & 15);
      asm volatile("bar.arrive 5, 288;" ::: "memory");
    }
    TS(0, 1);
    mbar_wait(sBar, 0);
    TS(0, 3);
    float acc[120];
#pragma unroll
    for (int i = 0; i < 120; i++) acc[i] = 0.f;
    if (wg == 0) qkv_mainloop<0>(acc, sbase, sBar, (tid & 127) == 0);
    else qkv_mainloop<1>(acc, sbase, sBar, (tid & 127) == 0);
    wgmma_wait<0>();
    fence_regs(acc);
    TS(0, 4);
    named_bar_sync(3, 256);
    const int g = lane >> 2, c4 = lane & 3;
    const uint32_t stg = sbase + wg * (12 * 3072) + (wwarp * 2) * 384 + g * 16;
    const int hbase = n_blk * 12;
#pragma unroll
    for (int j = 0; j < 30; j++) {
      const int cb = (j * 8) % 20;
      const int hb = (j * 8) / 20;
      int d = cb + c4 * 2;
      int hl = hb;
      if (cb == 16 && c4 >= 2) { d -= 20; hl += 1; }
      const uint32_t a0 = stg + hl * 3072 + (d >> 3) * 128 + (d & 7) * 2;
      const int hg = hbase + hl;
      const float sc = hg < 32 ? ATT_SCALE_LOG2E : 1.0f;
      st_shared_b32(a0, pack_bf16(acc[4 * j] * sc, acc[4 * j + 1] * sc));
      st_shared_b32(a0 + 384, pack_bf16(acc[4 * j + 2] * sc, acc[4 * j + 3] * sc));
      if (d == 18) {
        const uint32_t pad0 = hg < 32 ? 0u : (hg < 64 ? 0x3f803f80u : 0x00003f80u);
        const uint32_t pad1 = (hg >= 32 && hg < 64) ? 0x00003f80u : 0u;
        st_shared_v2(a0 + 4, pad0, pad1);
        st_shared_v2(a0 + 388, pad0, pad1);
      }
      if (j % 10 == 9) {
        fence_proxy_async();
        named_bar_sync(1 + wg, 128);
        if ((tid & 127) < 4) {
          const int hs = (j / 10) * 4 + (tid & 127);
          bf16* dst = g_img + (size_t)(hbase + hs) * IMG_HEAD_ELEMS + (size_t)(m_blk * 16 + wg * 8) * 192;
          bulk_s2g(dst, sbase + wg * (12 * 3072) + hs * 3072, 3072);
          bulk_commit();
        }
      }
    }
    if ((tid & 127) < 4) bulk_wait_read();
  }
  __syncwarp();
  TS(0, 5);
  cluster_sync_relaxed();
  TS(0, 6);
}

constexpr int KC_NST1 = 5, KC_NST3 = 6;
constexpr int KC_STAGING = 160 * 1024;
constexpr int KC_BAR = KC_STAGING + 48 * 1024;
constexpr int KC_CS = KC_BAR + 512;
constexpr int KC_SMEM = KC_CS + 1536 + 1024;

__global__ void __launch_bounds__(GT, 1)
mlp_kernel(const __grid_constant__ CUtensorMap tmO, const __grid_constant__ CUtensorMap tmWo64, const __grid_constant__ CUtensorMap tmWo16,
           const __grid_constant__ CUtensorMap tmH, const __grid_constant__ CUtensorMap tmWg, const __grid_constant__ CUtensorMap tmWu,
           const __grid_constant__ CUtensorMap tmHHs, const __grid_constant__ CUtensorMap tmHH, const __grid_constant__ CUtensorMap tmWd64,
           const __grid_constant__ CUtensorMap tmWd16, const __grid_constant__ CUtensorMap tmHs, const __grid_constant__ CUtensorMap tmOut,
           const bf16* __restrict__ x) {
  extern __shared__ uint8_t smem_raw[];
  const uint32_t sbase = (smem_u32(smem_raw) + 1023u) & ~1023u;
  const uint32_t bar1 = sbase + KC_BAR;
  const uint32_t bar2 = bar1 + 128;
  const uint32_t bar3 = bar2 + 128;
  const uint32_t barD = bar3 + 128;
  const int tid = threadIdx.x, warp = tid >> 5, lane = tid & 31;
  const int rank = blockIdx.x & 1;
  const int pair = blockIdx.x >> 1;
  const int j_blk = pair & 7;
  const int m_blk = (pair >> 3) * 2 + rank;
  const int n0 = j_blk * 80;
  TS(2, 0);
  if (tid == 256) {
    prefetch_tmap(&tmO); prefetch_tmap(&tmWo64); prefetch_tmap(&tmWo16); prefetch_tmap(&tmH); prefetch_tmap(&tmWg);
    prefetch_tmap(&tmWu); prefetch_tmap(&tmHHs); prefetch_tmap(&tmHH); prefetch_tmap(&tmWd64); prefetch_tmap(&tmWd16);
    prefetch_tmap(&tmHs); prefetch_tmap(&tmOut);
  }
  if (tid == 0) {
    for (int s = 0; s < 5; s++) {
      mbar_init(bar1 + 8 * s, 1); mbar_init(bar1 + 8 * (5 + s), 4);
      mbar_init(bar2 + 8 * s, 1); mbar_init(bar2 + 8 * (5 + s), 4);
    }
    for (int s = 0; s < 6; s++) { mbar_init(bar3 + 8 * s, 1); mbar_init(bar3 + 8 * (6 + s), 4); }
    mbar_init(barD, 4); mbar_init(barD + 8, 4); mbar_init(barD + 16, 2);
    fence_mbar_init();
  }
  cluster_sync_all();

  if (warp >= 8) {
    asm volatile("setmaxnreg.dec.sync.aligned.u32 40;");
    if (tid == 256) {
      auto issue_b80 = [&](const CUtensorMap* t64, const CUtensorMap* t16, uint32_t bars, int nst, int kb) {
        const int s = kb % nst;
        const uint32_t full = bars + 8 * s;
        const uint32_t st = sbase + s * RG_STAGE_BYTES;
        mbar_expect_tx(full, RG_STAGE_BYTES);
        tma_load_2d_mc(st + 16384 + rank * 4096, t64, n0, kb * 64 + rank * 32, full, (uint16_t)3);
        tma_load_2d_mc(st + 16384 + 8192 + rank * 1024, t16, n0 + 64, kb * 64 + rank * 32, full, (uint16_t)3);
      };
      for (int kb = 0; kb < KC_NST1; kb++) issue_b80(&tmWo64, &tmWo16, bar1, KC_NST1, kb);
      pdl_wait();
      for (int kb = 0; kb < 10; kb++) {
        const int s = kb % KC_NST1;
        if (kb >= KC_NST1) {
          mbar_wait(bar1 + 8 * (KC_NST1 + s), ((kb / KC_NST1) & 1) ^ 1);
          issue_b80(&tmWo64, &tmWo16, bar1, KC_NST1, kb);
        }
        tma_load_2d(sbase + s * RG_STAGE_BYTES, &tmO, kb * 64, m_blk * 128, bar1 + 8 * s);
      }
      auto issue_bglu = [&](int kb) {
        const int s = kb % LG_STAGES;
        const uint32_t full = bar2 + 8 * s;
        mbar_expect_tx(full, GLU_STAGE);
        const uint32_t dst = sbase + s * GLU_STAGE + 8192;
#pragma unroll
        for (int j = 0; j < 3; j++)
          tma_load_2d_mc(dst + (rank * 3 + j) * 4096, rank == 0 ? &tmWg : &tmWu, j_blk * 192 + j * 64, kb * 32, full, (uint16_t)3);
      };
      mbar_wait(barD, 0);
      for (int kb = 0; kb < LG_STAGES; kb++) issue_bglu(kb);
      flag_wait(&g_flag[16 + m_blk], 16);
      fence_proxy_async_all();
      for (int kb = 0; kb < 20; kb++) {
        const int s = kb % LG_STAGES;
        if (kb >= LG_STAGES) {
          mbar_wait(bar2 + 8 * (LG_STAGES + s), ((kb / LG_STAGES) & 1) ^ 1);
          issue_bglu(kb);
        }
        tma_load_2d(sbase + s * GLU_STAGE, &tmH, kb * 32, m_blk * 128, bar2 + 8 * s);
      }
      mbar_wait(barD + 8, 0);
      auto issue_b3 = [&](int it) {
        const int kb = (j_blk * 3 + it) % 24;
        const int s = it % KC_NST3;
        const uint32_t full = bar3 + 8 * s;
        const uint32_t st = sbase + s * RG_STAGE_BYTES;
        mbar_expect_tx(full, RG_STAGE_BYTES);
        tma_load_2d_mc(st + 16384 + rank * 4096, &tmWd64, n0, kb * 64 + rank * 32, full, (uint16_t)3);
        tma_load_2d_mc(st + 16384 + 8192 + rank * 1024, &tmWd16, n0 + 64, kb * 64 + rank * 32, full, (uint16_t)3);
      };
      for (int it = 0; it < KC_NST3; it++) issue_b3(it);
      for (int it = 0; it < 24; it++) {
        const int s = it % KC_NST3;
        if (it >= KC_NST3) {
          mbar_wait(bar3 + 8 * (KC_NST3 + s), ((it / KC_NST3) & 1) ^ 1);
          issue_b3(it);
        }
        if (it % 3 == 0) {
          if (it == 0) mbar_wait(barD + 16, 0);
          else flag_wait(&g_flag[32 + m_blk * 8 + (j_blk + it / 3) % 8], 2);
          fence_proxy_async_all();
        }
        tma_load_2d(sbase + s * RG_STAGE_BYTES, &tmHH, ((j_blk * 3 + it) % 24) * 64, m_blk * 128, bar3 + 8 * s);
      }
    }
  } else {
    asm volatile("setmaxnreg.inc.sync.aligned.u32 232;");
    const int wg = __shfl_sync(0xffffffffu, warp >> 2, 0);
    const int wwarp = warp & 3;
    const int g = lane >> 2, c4 = lane & 3;
    const int row0 = m_blk * 128 + wg * 64 + wwarp * 16 + g;
    const bool leader = (tid & 127) == 0;
    const uint32_t stg80_base = sbase + KC_STAGING + wg * 24576;
    const uint32_t stg80 = stg80_base + (wwarp * 16 + g) * 160 + c4 * 4;
    {
      uint32_t res[20];
#pragma unroll
      for (int j = 0; j < 10; j++) {
        res[2 * j] = __ldg(reinterpret_cast<const uint32_t*>(x + (size_t)row0 * DM + n0 + j * 8 + c4 * 2));
        res[2 * j + 1] = __ldg(reinterpret_cast<const uint32_t*>(x + (size_t)(row0 + 8) * DM + n0 + j * 8 + c4 * 2));
      }
      float acc0[32], acc1[8];
#pragma unroll
      for (int i = 0; i < 32; i++) acc0[i] = 0.f;
#pragma unroll
      for (int i = 0; i < 8; i++) acc1[i] = 0.f;
      TS(2, 1);
      if (wg == 0) res_mainloop<10, KC_NST1, 0>(acc0, acc1, sbase, bar1, leader);
      else res_mainloop<10, KC_NST1, 1>(acc0, acc1, sbase, bar1, leader);
      wgmma_wait<0>();
      fence_regs(acc0); fence_regs(acc1);
      release_stage(barD, leader);
      TS(2, 4);
      float sum0 = 0.f, sum1 = 0.f;
#pragma unroll
      for (int j = 0; j < 10; j++) {
        const uint32_t a01 = j < 8 ? pack_bf16(acc0[4 * j], acc0[4 * j + 1]) : pack_bf16(acc1[4 * (j - 8)], acc1[4 * (j - 8) + 1]);
        const uint32_t a23 = j < 8 ? pack_bf16(acc0[4 * j + 2], acc0[4 * j + 3]) : pack_bf16(acc1[4 * (j - 8) + 2], acc1[4 * (j - 8) + 3]);
        res[2 * j] = pack_bf16(bf_lo(res[2 * j]) + bf_lo(a01), bf_hi(res[2 * j]) + bf_hi(a01));
        res[2 * j + 1] = pack_bf16(bf_lo(res[2 * j + 1]) + bf_lo(a23), bf_hi(res[2 * j + 1]) + bf_hi(a23));
        st_shared_b32(stg80 + j * 16, res[2 * j]);
        st_shared_b32(stg80 + 8 * 160 + j * 16, res[2 * j + 1]);
        sum0 += bf_lo(res[2 * j]) + bf_hi(res[2 * j]);
        sum1 += bf_lo(res[2 * j + 1]) + bf_hi(res[2 * j + 1]);
      }
      sum0 += __shfl_xor_sync(0xffffffffu, sum0, 1); sum1 += __shfl_xor_sync(0xffffffffu, sum1, 1);
      sum0 += __shfl_xor_sync(0xffffffffu, sum0, 2); sum1 += __shfl_xor_sync(0xffffffffu, sum1, 2);
      const float mu0 = sum0 * (1.0f / 80.0f), mu1 = sum1 * (1.0f / 80.0f);
      float q0 = 0.f, q1 = 0.f;
#pragma unroll
      for (int j = 0; j < 10; j++) {
        float d;
        d = bf_lo(res[2 * j]) - mu0; q0 = fmaf(d, d, q0);
        d = bf_hi(res[2 * j]) - mu0; q0 = fmaf(d, d, q0);
        d = bf_lo(res[2 * j + 1]) - mu1; q1 = fmaf(d, d, q1);
        d = bf_hi(res[2 * j + 1]) - mu1; q1 = fmaf(d, d, q1);
      }
      q0 += __shfl_xor_sync(0xffffffffu, q0, 1); q1 += __shfl_xor_sync(0xffffffffu, q1, 1);
      q0 += __shfl_xor_sync(0xffffffffu, q0, 2); q1 += __shfl_xor_sync(0xffffffffu, q1, 2);
      if (c4 == 0) {
        g_stats[row0 * 8 + j_blk] = make_float2(mu0, q0);
        g_stats[(row0 + 8) * 8 + j_blk] = make_float2(mu1, q1);
      }
      fence_proxy_async();
      named_bar_sync(1 + wg, 128);
      if (leader) {
        tma_store_2d(&tmHs, stg80_base, n0, m_blk * 128 + wg * 64);
        bulk_commit();
        bulk_wait_all();
        fence_proxy_async_all();
        flag_signal(&g_flag[16 + m_blk]);
      }
      TS(2, 5);
    }
    {
      pdl_wait();
      {
        float* cs_s = reinterpret_cast<float*>(smem_raw + (sbase - smem_u32(smem_raw)) + KC_CS);
        for (int i = tid; i < 384; i += 256) cs_s[i] = g_cs[(i >= 192 ? FF - 192 : 0) + j_blk * 192 + i];
        named_bar_sync(3, 256);
      }
      flag_wait(&g_flag[16 + m_blk], 16);
      float mb[2], iv[2];
#pragma unroll
      for (int h = 0; h < 2; h++) {
        const float4* sp = reinterpret_cast<const float4*>(g_stats + (row0 + 8 * h) * 8);
        const float4 p0 = sp[0], p1 = sp[1], p2 = sp[2], p3 = sp[3];
        const float mean = (((p0.x + p0.z) + (p1.x + p1.z)) + ((p2.x + p2.z) + (p3.x + p3.z))) * 0.125f;
        float m2 = ((p0.y + p0.w) + (p1.y + p1.w)) + ((p2.y + p2.w) + (p3.y + p3.w));
        float dd = 0.f, d;
        d = p0.x - mean; dd = fmaf(d, d, dd); d = p0.z - mean; dd = fmaf(d, d, dd);
        d = p1.x - mean; dd = fmaf(d, d, dd); d = p1.z - mean; dd = fmaf(d, d, dd);
        d = p2.x - mean; dd = fmaf(d, d, dd); d = p2.z - mean; dd = fmaf(d, d, dd);
        d = p3.x - mean; dd = fmaf(d, d, dd); d = p3.z - mean; dd = fmaf(d, d, dd);
        m2 = fmaf(dd, 80.0f, m2);
        const float var_b = bf16_round(m2 * (1.0f / DM));
        const float den = bf16_round(sqrtf(bf16_round(var_b + 1e-5f)));
        iv[h] = __frcp_rn(den);
        mb[h] = bf16_round(mean);
      }
      float accg[96], accu[96];
#pragma unroll
      for (int i = 0; i < 96; i++) { accg[i] = 0.f; accu[i] = 0.f; }
      TS(3, 3);
      if (wg == 0) glu_mainloop<0>(accg, accu, sbase, bar2, leader);
      else glu_mainloop<1>(accg, accu, sbase, bar2, leader);
      wgmma_wait<0>();
      fence_regs(accg); fence_regs(accu);
      release_stage(barD + 8, leader);
      TS(3, 4);
      const uint32_t stg = sbase + KC_STAGING + wg * 24576 + (wwarp * 16 + g) * 128 + c4 * 4;
      const float* csg = reinterpret_cast<const float*>(smem_raw + (sbase - smem_u32(smem_raw)) + KC_CS) + c4 * 2;
      const float nm0 = -mb[0] * iv[0], nm1 = -mb[1] * iv[1];
#pragma unroll
      for (int sl = 0; sl < 3; sl++) {
        float2 cgv[4], cuv[4];
#pragma unroll
        for (int jj = 0; jj < 8; jj++) {
          const int j = sl * 8 + jj;
          if ((jj & 3) == 0) {
#pragma unroll
            for (int q = 0; q < 4; q++) {
              cgv[q] = *reinterpret_cast<const float2*>(csg + (j + q) * 8);
              cuv[q] = *reinterpret_cast<const float2*>(csg + 192 + (j + q) * 8);
            }
          }
          const float2 cg = cgv[jj & 3], cu = cuv[jj & 3];
          const float r0 = fmaxf(fmaf(accg[4 * j], iv[0], nm0 * cg.x), 0.f) * fmaf(accu[4 * j], iv[0], nm0 * cu.x);
          const float r1 = fmaxf(fmaf(accg[4 * j + 1], iv[0], nm0 * cg.y), 0.f) * fmaf(accu[4 * j + 1], iv[0], nm0 * cu.y);
          const float r2 = fmaxf(fmaf(accg[4 * j + 2], iv[1], nm1 * cg.x), 0.f) * fmaf(accu[4 * j + 2], iv[1], nm1 * cu.x);
          const float r3 = fmaxf(fmaf(accg[4 * j + 3], iv[1], nm1 * cg.y), 0.f) * fmaf(accu[4 * j + 3], iv[1], nm1 * cu.y);
          const uint32_t a0 = stg + sl * 8192 + ((jj ^ g) << 4);
          st_shared_b32(a0, pack_bf16(r0, r1));
          st_shared_b32(a0 + 1024, pack_bf16(r2, r3));
        }
        fence_proxy_async();
        named_bar_sync(1 + wg, 128);
        if (leader) {
          tma_store_2d(&tmHHs, sbase + KC_STAGING + wg * 24576 + sl * 8192, j_blk * 192 + sl * 64, m_blk * 128 + wg * 64);
          bulk_commit();
        }
      }
      TS(3, 7);
      if (leader) {
        bulk_wait_all();
        TS(3, 8);
        fence_proxy_async_all();
        mbar_arrive(barD + 16);
        flag_signal(&g_flag[32 + m_blk * 8 + j_blk]);
      }
      TS(3, 9);
    }
    {
      uint32_t res[20];
#pragma unroll
      for (int j = 0; j < 10; j++) {
        res[2 * j] = *reinterpret_cast<const uint32_t*>(g_h + (size_t)row0 * DM + n0 + j * 8 + c4 * 2);
        res[2 * j + 1] = *reinterpret_cast<const uint32_t*>(g_h + (size_t)(row0 + 8) * DM + n0 + j * 8 + c4 * 2);
      }
      float acc0[32], acc1[8];
#pragma unroll
      for (int i = 0; i < 32; i++) acc0[i] = 0.f;
#pragma unroll
      for (int i = 0; i < 8; i++) acc1[i] = 0.f;
      mbar_wait(bar3, 0);
      TS(4, 3);
      if (wg == 0) res_mainloop<24, KC_NST3, 0>(acc0, acc1, sbase, bar3, leader);
      else res_mainloop<24, KC_NST3, 1>(acc0, acc1, sbase, bar3, leader);
      wgmma_wait<0>();
      fence_regs(acc0); fence_regs(acc1);
      TS(4, 4);
#pragma unroll
      for (int j = 0; j < 10; j++) {
        const uint32_t a01 = j < 8 ? pack_bf16(acc0[4 * j], acc0[4 * j + 1]) : pack_bf16(acc1[4 * (j - 8)], acc1[4 * (j - 8) + 1]);
        const uint32_t a23 = j < 8 ? pack_bf16(acc0[4 * j + 2], acc0[4 * j + 3]) : pack_bf16(acc1[4 * (j - 8) + 2], acc1[4 * (j - 8) + 3]);
        st_shared_b32(stg80 + j * 16, pack_bf16(bf_lo(res[2 * j]) + bf_lo(a01), bf_hi(res[2 * j]) + bf_hi(a01)));
        st_shared_b32(stg80 + 8 * 160 + j * 16, pack_bf16(bf_lo(res[2 * j + 1]) + bf_lo(a23), bf_hi(res[2 * j + 1]) + bf_hi(a23)));
      }
      fence_proxy_async();
      named_bar_sync(1 + wg, 128);
      if (leader) {
        tma_store_2d(&tmOut, stg80_base, n0, m_blk * 128 + wg * 64);
        bulk_commit();
        bulk_wait_read();
      }
      TS(4, 5);
    }
  }
  __syncwarp();
  cluster_sync_relaxed();
  TS(4, 6);
}

constexpr int AT_THREADS = 512;
constexpr int AT_WGS = AT_THREADS / 128;
constexpr int AT_KV_BYTES = IMG_HEAD_ELEMS * 2;
constexpr int AT_SMEM = 2 * AT_KV_BYTES + 256 + 1024;
constexpr int AT_CHUNKS = 8;

__device__ __forceinline__ float exp2_poly(float x) {
  const float u = __saturatef(fmaf(x, 1.0f / 64.0f, 62.0f / 64.0f));
  const float MAGIC = 12582912.0f - 62.0f;
  const float r = fmaf(u, 64.0f, MAGIC);
  const float q = MAGIC - r;
  const float fr = fmaf(u, 64.0f, q);
  float p = fmaf(fr, 0.009570102207362652f, 0.05591785907745361f);
  p = fmaf(p, fr, 0.240247443318367f);
  p = fmaf(p, fr, 0.6931217908859253f);
  p = fmaf(p, fr, 0.9999992847442627f);
  return __uint_as_float(__float_as_uint(p) + (__float_as_uint(r) << 23));
}
__device__ __forceinline__ bool use_poly(int e) { return (e & 7) == 1; }

struct AttnState {
  uint32_t qa0, qa1, qa2, qa3, qa4, qa5;
  float M0, M1;
};

__device__ __forceinline__ bool attn_exp_fast(const float (&s)[32], uint32_t (&p)[16]) {
#pragma unroll
  for (int j = 0; j < 16; j++) {
    const float e0 = use_poly(2 * j) ? exp2_poly(s[2 * j]) : ex2(s[2 * j]);
    const float e1 = use_poly(2 * j + 1) ? exp2_poly(s[2 * j + 1]) : ex2(s[2 * j + 1]);
    p[j] = pack_bf16(e0, e1);
  }
  uint32_t acc_or = 0;
#pragma unroll
  for (int j = 0; j < 16; j++) acc_or |= p[j];
  return __any_sync(0xffffffffu, (acc_or & 0x40004000u) != 0);
}
__device__ __forceinline__ void attn_exp_exact(const float (&s)[32], uint32_t (&p)[16], float (&o)[12], AttnState& st, bool first, int c4) {
  float mx0 = fmaxf(s[0], s[1]), mx1 = fmaxf(s[2], s[3]);
#pragma unroll
  for (int j = 1; j < 8; j++) {
    mx0 = fmaxf(mx0, fmaxf(s[4 * j], s[4 * j + 1]));
    mx1 = fmaxf(mx1, fmaxf(s[4 * j + 2], s[4 * j + 3]));
  }
  mx0 = fmaxf(mx0, __shfl_xor_sync(0xffffffffu, mx0, 1));
  mx1 = fmaxf(mx1, __shfl_xor_sync(0xffffffffu, mx1, 1));
  mx0 = fmaxf(mx0, __shfl_xor_sync(0xffffffffu, mx0, 2));
  mx1 = fmaxf(mx1, __shfl_xor_sync(0xffffffffu, mx1, 2));
  float d0 = mx0 + 7.0f, d1 = mx1 + 7.0f;
  if (!first) { d0 = fmaxf(d0, 0.f); d1 = fmaxf(d1, 0.f); }
  const float T0 = st.M0 + d0, T1 = st.M1 + d1;
  const float h0 = bf16_round(T0), h1 = bf16_round(T1);
  const float i0 = bf16_round(T0 - h0), i1 = bf16_round(T1 - h1);
  const float l0 = bf16_round((T0 - h0) - i0), l1 = bf16_round((T1 - h1) - i1);
  const float N0 = (h0 + i0) + l0, N1 = (h1 + i1) + l1;
  d0 = N0 - st.M0; d1 = N1 - st.M1;
  st.M0 = N0; st.M1 = N1;
  if (c4 == 2) { st.qa4 = pack_bf16(-h0, -i0); st.qa5 = pack_bf16(-h1, -i1); }
  if (c4 == 3) { st.qa4 = pack_bf16(-l0, 0.f); st.qa5 = pack_bf16(-l1, 0.f); }
  if (!first) {
    const float al0 = ex2(-d0), al1 = ex2(-d1);
#pragma unroll
    for (int j = 0; j < 3; j++) {
      o[4 * j] *= al0; o[4 * j + 1] *= al0;
      o[4 * j + 2] *= al1; o[4 * j + 3] *= al1;
    }
  }
#pragma unroll
  for (int j = 0; j < 8; j++) {
    p[2 * j] = pack_bf16(ex2(s[4 * j] - d0), ex2(s[4 * j + 1] - d0));
    p[2 * j + 1] = pack_bf16(ex2(s[4 * j + 2] - d1), ex2(s[4 * j + 3] - d1));
  }
}
__device__ __forceinline__ void attn_step(float (&s)[32], const uint32_t (&pp)[16], uint32_t (&pn)[16], float (&o)[12], AttnState& st,
                                          uint32_t k_addr, uint32_t v_addr_prev, int keep, int c4, int wgdbg = 0, int tdbg = 0) {
  PH(wgdbg, tdbg, 0);
  const uint64_t dk = make_desc(k_addr, 128, 384, 0);
  const uint64_t dv_prev = make_desc(v_addr_prev, 384, 128, 0);
  wgmma_fence();
  wgmma_rs_n64(s, st.qa0, st.qa1, st.qa2, st.qa3, dk, 0);
  wgmma_rs_n64(s, st.qa4, st.qa5, 0u, 0u, dk + 16, 1);
  wgmma_commit();
#pragma unroll
  for (int kk = 0; kk < 4; kk++) wgmma_rs_n24_tb(o, pp[4 * kk], pp[4 * kk + 1], pp[4 * kk + 2], pp[4 * kk + 3], dv_prev + kk * 48, kk == 0 ? keep : 1);
  wgmma_commit();
  wgmma_wait<1>();
  fence_regs(s);
  PH(wgdbg, tdbg, 1);
  const bool redo = attn_exp_fast(s, pn);
  PH(wgdbg, tdbg, 2);
  wgmma_wait<0>();
  fence_regs(o);
  if (redo) attn_exp_exact(s, pn, o, st, false, c4);
}

__global__ void __launch_bounds__(AT_THREADS, 1) attn_kernel(const bf16* __restrict__ wo, const bf16* __restrict__ wgt, const bf16* __restrict__ wup, const bf16* __restrict__ wdn) {
  extern __shared__ uint8_t smem_raw[];
  const uint32_t sbase = (smem_u32(smem_raw) + 1023u) & ~1023u;
  const uint32_t sK = sbase, sV = sbase + AT_KV_BYTES;
  const uint32_t sBar = sV + AT_KV_BYTES;
  const int tid = threadIdx.x, warp = tid >> 5, lane = tid & 31;
  const int head = blockIdx.x >> 2, quarter = blockIdx.x & 3;
  if (blockIdx.x >= 128) {
    pdl_launch();
    const int b = blockIdx.x - 128;
    const bf16* w = (b >> 1) ? wup : wgt;
    const int cgrp = tid % 96, rgrp = tid / 96;
    float acc[8];
#pragma unroll
    for (int i = 0; i < 8; i++) acc[i] = 0.f;
    float* red = reinterpret_cast<float*>(smem_raw);
    if (rgrp < 5) {
      const uint4* src = reinterpret_cast<const uint4*>(w + (size_t)(rgrp * 128) * FF + (b & 1) * 768 + cgrp * 8);
#pragma unroll 8
      for (int r = 0; r < 128; r++) {
        const uint4 v = __ldg(src + (size_t)r * (FF / 8));
        acc[0] += bf_lo(v.x); acc[1] += bf_hi(v.x); acc[2] += bf_lo(v.y); acc[3] += bf_hi(v.y);
        acc[4] += bf_lo(v.z); acc[5] += bf_hi(v.z); acc[6] += bf_lo(v.w); acc[7] += bf_hi(v.w);
      }
#pragma unroll
      for (int i = 0; i < 8; i++) red[rgrp * 768 + cgrp * 8 + i] = acc[i];
    }
    __syncthreads();
    pdl_wait();
    for (int c = tid; c < 768; c += AT_THREADS)
      g_cs[(b >> 1) * FF + (b & 1) * 768 + c] = ((red[c] + red[768 + c]) + (red[1536 + c] + red[2304 + c])) + red[3072 + c];
    if (b == 0 && tid < 16) g_flag[tid] = 0;
    return;
  }
  TS(1, 0);
  if (tid == 0) {
    for (int i = 0; i < AT_CHUNKS; i++) mbar_init(sBar + 8 * i, 1);
    fence_mbar_init();
  }
  pdl_launch();
  if (tid == 32) {
    prefetch_l2(reinterpret_cast<const uint8_t*>(wo) + blockIdx.x * 6400, 6400);
    prefetch_l2(reinterpret_cast<const uint8_t*>(wgt) + blockIdx.x * 15360, 15360);
    prefetch_l2(reinterpret_cast<const uint8_t*>(wup) + blockIdx.x * 15360, 15360);
    prefetch_l2(reinterpret_cast<const uint8_t*>(wdn) + blockIdx.x * 15360, 15360);
  }
  __syncthreads();
  TS(1, 1);
  pdl_wait();
  TS(1, 2);
  if (tid == 0) {
    const uint8_t* kg = reinterpret_cast<const uint8_t*>(g_img + (size_t)(32 + head) * IMG_HEAD_ELEMS);
    const uint8_t* vg = reinterpret_cast<const uint8_t*>(g_img + (size_t)(64 + head) * IMG_HEAD_ELEMS);
    constexpr int CB = AT_KV_BYTES / AT_CHUNKS;
    for (int i = 0; i < AT_CHUNKS; i++) {
      mbar_expect_tx(sBar + 8 * i, 2 * CB);
      bulk_g2s(sK + i * CB, kg + i * CB, CB, sBar + 8 * i);
      bulk_g2s(sV + i * CB, vg + i * CB, CB, sBar + 8 * i);
    }
  }
  const int wg = warp >> 2, wwarp = warp & 3;
  const int g = lane >> 2, c4 = lane & 3;
  const uint64_t dk_base = make_desc(sK, 128, 384, 0);
  const uint64_t dv_base = make_desc(sV, 384, 128, 0);

  uint32_t qn[6];
  {
    const bf16* q0 = g_img + (size_t)head * IMG_HEAD_ELEMS + (size_t)((quarter * 512 + wg * 64 + wwarp * 16) >> 3) * 192 + g * 8 + c4 * 2;
    qn[0] = *reinterpret_cast<const uint32_t*>(q0);
    qn[1] = *reinterpret_cast<const uint32_t*>(q0 + 192);
    qn[2] = *reinterpret_cast<const uint32_t*>(q0 + 64);
    qn[3] = *reinterpret_cast<const uint32_t*>(q0 + 192 + 64);
    qn[4] = *reinterpret_cast<const uint32_t*>(q0 + 128);
    qn[5] = *reinterpret_cast<const uint32_t*>(q0 + 192 + 128);
  }
#pragma unroll 1
  for (int rep = 0; rep < 8 / AT_WGS; rep++) {
    const int row0 = quarter * 512 + (rep * AT_WGS + wg) * 64 + wwarp * 16 + g;
    AttnState st;
    st.qa0 = qn[0]; st.qa1 = qn[1]; st.qa2 = qn[2]; st.qa3 = qn[3]; st.qa4 = qn[4]; st.qa5 = qn[5];
    if (rep + 1 < 8 / AT_WGS) {
      const bf16* q0 = g_img + (size_t)head * IMG_HEAD_ELEMS + (size_t)((row0 + AT_WGS * 64) >> 3) * 192 + g * 8 + c4 * 2;
      qn[0] = *reinterpret_cast<const uint32_t*>(q0);
      qn[1] = *reinterpret_cast<const uint32_t*>(q0 + 192);
      qn[2] = *reinterpret_cast<const uint32_t*>(q0 + 64);
      qn[3] = *reinterpret_cast<const uint32_t*>(q0 + 192 + 64);
      qn[4] = *reinterpret_cast<const uint32_t*>(q0 + 128);
      qn[5] = *reinterpret_cast<const uint32_t*>(q0 + 192 + 128);
    }
    float o[12];
    float s[32];
    uint32_t pa[16], pb[16];
    st.M0 = st.M1 = 0.f;
    if (rep == 0) mbar_wait(sBar, 0);
    wgmma_fence();
    wgmma_rs_n64(s, st.qa0, st.qa1, st.qa2, st.qa3, dk_base, 0);
    wgmma_rs_n64(s, st.qa4, st.qa5, 0u, 0u, dk_base + 16, 1);
    wgmma_commit();
    wgmma_wait<0>();
    fence_regs(s);
    attn_exp_exact(s, pa, o, st, true, c4);
    attn_step(s, pa, pb, o, st, sK + 3072, sV, 0, c4);
#pragma unroll 1
    for (int tt = 1; tt < 16; tt++) {
      if (rep == 0 && !(tt & 1)) mbar_wait(sBar + 8 * (tt >> 1), 0);
      attn_step(s, pb, pa, o, st, sK + tt * 6144, sV + tt * 6144 - 3072, 1, c4, wg, rep * 32 + tt * 2);
      attn_step(s, pa, pb, o, st, sK + tt * 6144 + 3072, sV + tt * 6144, 1, c4, wg, rep * 32 + tt * 2 + 1);
    }
    wgmma_fence();
#pragma unroll
    for (int kk = 0; kk < 4; kk++) wgmma_rs_n24_tb(o, pb[4 * kk], pb[4 * kk + 1], pb[4 * kk + 2], pb[4 * kk + 3], dv_base + 31 * 192 + kk * 48, 1);
    wgmma_commit();
    wgmma_wait<0>();
    fence_regs(o);
    TS(1, 3 + rep);
    const float l0 = __shfl_sync(0xffffffffu, o[8], (lane & ~3) | 2);
    const float l1 = __shfl_sync(0xffffffffu, o[10], (lane & ~3) | 2);
    const float i0 = 1.0f / l0, i1 = 1.0f / l1;
    bf16* o0 = g_o + (size_t)row0 * DM + head * DH;
    bf16* o1 = o0 + 8 * DM;
#pragma unroll
    for (int j = 0; j < 3; j++) {
      if (j < 2 || c4 < 2) {
        *reinterpret_cast<uint32_t*>(o0 + j * 8 + c4 * 2) = pack_bf16(o[4 * j] * i0, o[4 * j + 1] * i0);
        *reinterpret_cast<uint32_t*>(o1 + j * 8 + c4 * 2) = pack_bf16(o[4 * j + 2] * i1, o[4 * j + 3] * i1);
      }
    }
  }
}

typedef CUresult (*EncodeTiledFn)(CUtensorMap*, CUtensorMapDataType, cuuint32_t, void*, const cuuint64_t*, const cuuint64_t*,
                                  const cuuint32_t*, const cuuint32_t*, CUtensorMapInterleave, CUtensorMapSwizzle,
                                  CUtensorMapL2promotion, CUtensorMapFloatOOBfill);

static void make_map(EncodeTiledFn fn, CUtensorMap* tm, const void* ptr, uint64_t rows, uint64_t cols, uint32_t box_rows,
                     uint32_t box_cols, CUtensorMapSwizzle sw) {
  cuuint64_t dims[2] = {cols, rows};
  cuuint64_t strides[1] = {cols * 2};
  cuuint32_t box[2] = {box_cols, box_rows};
  cuuint32_t es[2] = {1, 1};
  fn(tm, CU_TENSOR_MAP_DATA_TYPE_BFLOAT16, 2, const_cast<void*>(ptr), dims, strides, box, es, CU_TENSOR_MAP_INTERLEAVE_NONE, sw,
     CU_TENSOR_MAP_L2_PROMOTION_L2_256B, CU_TENSOR_MAP_FLOAT_OOB_FILL_NONE);
}

template <typename... KArgs, typename... Args>
static void launch(void (*kern)(KArgs...), int grid, int block, int smem, int cluster, bool pdl, Args... args) {
  cudaLaunchConfig_t cfg = {};
  cfg.gridDim = dim3(grid);
  cfg.blockDim = dim3(block);
  cfg.dynamicSmemBytes = smem;
  cfg.stream = cudaStreamPerThread;
  cudaLaunchAttribute at[2];
  int n = 0;
  if (cluster > 1) {
    at[n].id = cudaLaunchAttributeClusterDimension;
    at[n].val.clusterDim.x = cluster; at[n].val.clusterDim.y = 1; at[n].val.clusterDim.z = 1;
    n++;
  }
  if (pdl) {
    at[n].id = cudaLaunchAttributeProgrammaticStreamSerialization;
    at[n].val.programmaticStreamSerializationAllowed = 1;
    n++;
  }
  cfg.attrs = at;
  cfg.numAttrs = n;
  cudaLaunchKernelEx(&cfg, kern, KArgs(args)...);
}

extern "C" void kernel_launch(void* const* d_in, const int* in_sizes, int n_in, void* d_out, int out_size) {
  const bf16* x = (const bf16*)d_in[0];
  const bf16* wqkv = (const bf16*)d_in[1];
  const bf16* wo = (const bf16*)d_in[2];
  const bf16* wg = (const bf16*)d_in[4];
  const bf16* wu = (const bf16*)d_in[5];
  const bf16* wd = (const bf16*)d_in[6];
  bf16* out = (bf16*)d_out;

  static EncodeTiledFn enc = nullptr;
  static void *p_o = nullptr, *p_h = nullptr, *p_hh = nullptr, *p_xn = nullptr;
  if (!enc) {
    void* fn = nullptr;
    cudaDriverEntryPointQueryResult qr;
    cudaGetDriverEntryPoint("cuTensorMapEncodeTiled", &fn, cudaEnableDefault, &qr);
    enc = (EncodeTiledFn)fn;
    cudaGetSymbolAddress(&p_o, g_o);
    cudaGetSymbolAddress(&p_h, g_h);
    cudaGetSymbolAddress(&p_hh, g_hh);
    cudaGetSymbolAddress(&p_xn, g_xn);
    cudaFuncSetAttribute(qkv_kernel, cudaFuncAttributeMaxDynamicSharedMemorySize, KA_SMEM);
    cudaFuncSetAttribute(mlp_kernel, cudaFuncAttributeMaxDynamicSharedMemorySize, KC_SMEM);
    cudaFuncSetAttribute(attn_kernel, cudaFuncAttributeMaxDynamicSharedMemorySize, AT_SMEM);
  }
  CUtensorMap tm_wqkv, tm_wg, tm_wu, tm_wo64, tm_wo16, tm_wd64, tm_wd16, tm_o, tm_h, tm_hh, tm_hhs, tm_xn, tm_hs, tm_out;
  make_map(enc, &tm_wqkv, wqkv, DM, 3 * DM, 32, 64, CU_TENSOR_MAP_SWIZZLE_128B);
  make_map(enc, &tm_wg, wg, DM, FF, 32, 64, CU_TENSOR_MAP_SWIZZLE_128B);
  make_map(enc, &tm_wu, wu, DM, FF, 32, 64, CU_TENSOR_MAP_SWIZZLE_128B);
  make_map(enc, &tm_wo64, wo, DM, DM, 32, 64, CU_TENSOR_MAP_SWIZZLE_128B);
  make_map(enc, &tm_wo16, wo, DM, DM, 32, 16, CU_TENSOR_MAP_SWIZZLE_32B);
  make_map(enc, &tm_wd64, wd, FF, DM, 32, 64, CU_TENSOR_MAP_SWIZZLE_128B);
  make_map(enc, &tm_wd16, wd, FF, DM, 32, 16, CU_TENSOR_MAP_SWIZZLE_32B);
  make_map(enc, &tm_o, p_o, SEQ, DM, 128, 64, CU_TENSOR_MAP_SWIZZLE_128B);
  make_map(enc, &tm_h, p_h, SEQ, DM, 128, 32, CU_TENSOR_MAP_SWIZZLE_64B);
  make_map(enc, &tm_hh, p_hh, SEQ, FF, 128, 64, CU_TENSOR_MAP_SWIZZLE_128B);
  make_map(enc, &tm_hhs, p_hh, SEQ, FF, 64, 64, CU_TENSOR_MAP_SWIZZLE_128B);
  make_map(enc, &tm_xn, p_xn, SEQ, DM, 128, 32, CU_TENSOR_MAP_SWIZZLE_64B);
  make_map(enc, &tm_hs, p_h, SEQ, DM, 64, 80, CU_TENSOR_MAP_SWIZZLE_NONE);
  make_map(enc, &tm_out, out, SEQ, DM, 64, 80, CU_TENSOR_MAP_SWIZZLE_NONE);

  launch(qkv_kernel, 128, GT, KA_SMEM, 2, false, tm_xn, tm_wqkv, x);
  launch(attn_kernel, 132, AT_THREADS, AT_SMEM, 1, true, wo, wg, wu, wd);
  launch(mlp_kernel, 128, GT, KC_SMEM, 2, true, tm_o, tm_wo64, tm_wo16, tm_h, tm_wg, tm_wu, tm_hhs, tm_hh, tm_wd64, tm_wd16, tm_hs, tm_out, x);
}
```

```cpp
#include <cuda_runtime.h>
#include <cuda_bf16.h>
#include <cuda.h>
#include <stdint.h>

typedef __nv_bfloat16 bf16;

constexpr int SEQ = 2048, DM = 640, NH = 32, DH = 20, FF = 1536;
constexpr float ATT_SCALE_LOG2E = 0.22360679774997896f * 1.4426950408889634f;
constexpr int IMG_HEAD_ELEMS = (SEQ / 8) * 192;

__device__ __align__(1024) bf16 g_img[3 * NH * IMG_HEAD_ELEMS];
__device__ __align__(1024) bf16 g_o[SEQ * DM];
__device__ __align__(1024) bf16 g_h[SEQ * DM];
__device__ __align__(1024) bf16 g_xn[SEQ * DM];
__device__ float2 g_stats[SEQ * 8];
__device__ float g_cs[2 * FF];
__device__ int g_flag[32 + 128];
__device__ __align__(1024) bf16 g_hh[SEQ * FF];

#define TS(k, i)
#define PH(w, t, i)
__device__ __forceinline__ uint32_t smem_u32(const void* p) { return (uint32_t)__cvta_generic_to_shared(p); }
__device__ __forceinline__ void mbar_init(uint32_t bar, uint32_t cnt) {
  asm volatile("mbarrier.init.shared::cta.b64 [%0], %1;" ::"r"(bar), "r"(cnt) : "memory");
}
__device__ __forceinline__ void mbar_expect_tx(uint32_t bar, uint32_t bytes) {
  asm volatile("mbarrier.arrive.expect_tx.shared::cta.b64 _, [%0], %1;" ::"r"(bar), "r"(bytes) : "memory");
}
__device__ __forceinline__ void mbar_arrive(uint32_t bar) {
  asm volatile("mbarrier.arrive.shared::cta.b64 _, [%0];" ::"r"(bar) : "memory");
}
__device__ __forceinline__ void mbar_arrive_cluster(uint32_t bar, uint32_t cta) {
  asm volatile(
      "{\n.reg .b32 r;\nmapa.shared::cluster.u32 r, %0, %1;\n"
      "mbarrier.arrive.shared::cluster.b64 _, [r];\n}\n" ::"r"(bar), "r"(cta)
      : "memory");
}
__device__ __forceinline__ void mbar_wait(uint32_t bar, uint32_t parity) {
  asm volatile(
      "{\n.reg .pred p;\nLAB_WAIT:\n"
      "mbarrier.try_wait.parity.shared::cta.b64 p, [%0], %1;\n"
      "@p bra DONE;\nbra LAB_WAIT;\nDONE:\n}\n" ::"r"(bar), "r"(parity)
      : "memory");
}
__device__ __forceinline__ void mbar_wait_cluster(uint32_t bar, uint32_t parity) {
  asm volatile(
      "{\n.reg .pred p;\nLAB_WAIT:\n"
      "mbarrier.try_wait.parity.acquire.cluster.shared::cta.b64 p, [%0], %1;\n"
      "@p bra DONE;\nbra LAB_WAIT;\nDONE:\n}\n" ::"r"(bar), "r"(parity)
      : "memory");
}
__device__ __forceinline__ void fence_mbar_init() { asm volatile("fence.mbarrier_init.release.cluster;" ::: "memory"); }
__device__ __forceinline__ void fence_proxy_async() { asm volatile("fence.proxy.async.shared::cta;" ::: "memory"); }
__device__ __forceinline__ void cluster_sync_all() {
  asm volatile("barrier.cluster.arrive.release.aligned;\nbarrier.cluster.wait.acquire.aligned;" ::: "memory");
}
__device__ __forceinline__ void cluster_sync_relaxed() {
  asm volatile("barrier.cluster.arrive.relaxed.aligned;\nbarrier.cluster.wait.aligned;" ::: "memory");
}
__device__ __forceinline__ void named_bar_sync(int id, int n) { asm volatile("bar.sync %0, %1;" ::"r"(id), "r"(n) : "memory"); }
__device__ __forceinline__ bool wg_any(bool pred, int id) {
  uint32_t r;
  asm volatile("{\n.reg .pred p, q;\nsetp.ne.u32 p, %1, 0;\nbar.red.or.pred q, %2, 128, p;\nselp.u32 %0, 1, 0, q;\n}\n" : "=r"(r) : "r"((uint32_t)pred), "r"(id) : "memory");
  return r != 0;
}
__device__ __forceinline__ void fence_proxy_async_all() { asm volatile("fence.proxy.async;" ::: "memory"); }
__device__ __forceinline__ void flag_signal(int* f) {
  __threadfence();
  atomicAdd(f, 1);
}
__device__ __forceinline__ void flag_wait(const int* f, int target) {
  int v;
  unsigned spins = 0;
  do {
    asm volatile("ld.acquire.gpu.global.s32 %0, [%1];" : "=r"(v) : "l"(f) : "memory");
    if (++spins > (1u << 24)) __trap();
  } while (v < target);
}
__device__ __forceinline__ void pdl_launch() { asm volatile("griddepcontrol.launch_dependents;" ::: "memory"); }
__device__ __forceinline__ void pdl_wait() { asm volatile("griddepcontrol.wait;" ::: "memory"); }

__device__ __forceinline__ void tma_load_2d(uint32_t dst, const CUtensorMap* tm, int c0, int c1, uint32_t bar) {
  asm volatile(
      "cp.async.bulk.tensor.2d.shared::cluster.global.mbarrier::complete_tx::bytes [%0], [%1, {%3, %4}], [%2];" ::"r"(dst),
      "l"((uint64_t)tm), "r"(bar), "r"(c0), "r"(c1)
      : "memory");
}
__device__ __forceinline__ void tma_load_2d_mc(uint32_t dst, const CUtensorMap* tm, int c0, int c1, uint32_t bar, uint16_t mask) {
  asm volatile(
      "cp.async.bulk.tensor.2d.shared::cluster.global.mbarrier::complete_tx::bytes.multicast::cluster [%0], [%1, {%3, %4}], [%2], %5;" ::"r"(dst),
      "l"((uint64_t)tm), "r"(bar), "r"(c0), "r"(c1), "h"(mask)
      : "memory");
}
__device__ __forceinline__ void bulk_g2s(uint32_t dst, const void* src, uint32_t bytes, uint32_t bar) {
  asm volatile("cp.async.bulk.shared::cluster.global.mbarrier::complete_tx::bytes [%0], [%1], %2, [%3];" ::"r"(dst), "l"(src),
               "r"(bytes), "r"(bar)
               : "memory");
}
__device__ __forceinline__ void bulk_s2g(void* dst, uint32_t src, uint32_t bytes) {
  asm volatile("cp.async.bulk.global.shared::cta.bulk_group [%0], [%1], %2;" ::"l"(dst), "r"(src), "r"(bytes) : "memory");
}
__device__ __forceinline__ void tma_store_2d(const CUtensorMap* tm, uint32_t src, int c0, int c1) {
  asm volatile("cp.async.bulk.tensor.2d.global.shared::cta.bulk_group [%0, {%2, %3}], [%1];" ::"l"((uint64_t)tm), "r"(src), "r"(c0), "r"(c1) : "memory");
}
__device__ __forceinline__ void bulk_commit() { asm volatile("cp.async.bulk.commit_group;" ::: "memory"); }
__device__ __forceinline__ void bulk_wait_read() { asm volatile("cp.async.bulk.wait_group.read 0;" ::: "memory"); }
__device__ __forceinline__ void prefetch_l2(const void* p, uint32_t bytes) {
  asm volatile("cp.async.bulk.prefetch.L2.global [%0], %1;" ::"l"(p), "r"(bytes) : "memory");
}
__device__ __forceinline__ void bulk_wait_all() { asm volatile("cp.async.bulk.wait_group 0;" ::: "memory"); }
__device__ __forceinline__ void st_shared_b32(uint32_t addr, uint32_t v) { asm volatile("st.shared.b32 [%0], %1;" ::"r"(addr), "r"(v) : "memory"); }
__device__ __forceinline__ void st_shared_v2(uint32_t addr, uint32_t a, uint32_t b) { asm volatile("st.shared.v2.b32 [%0], {%1, %2};" ::"r"(addr), "r"(a), "r"(b) : "memory"); }
__device__ __forceinline__ void prefetch_tmap(const CUtensorMap* tm) {
  asm volatile("prefetch.tensormap [%0];" ::"l"((uint64_t)tm) : "memory");
}
__device__ __forceinline__ void wgmma_fence() { asm volatile("wgmma.fence.sync.aligned;" ::: "memory"); }
__device__ __forceinline__ void wgmma_commit() { asm volatile("wgmma.commit_group.sync.aligned;" ::: "memory"); }
template <int N>
__device__ __forceinline__ void wgmma_wait() { asm volatile("wgmma.wait_group.sync.aligned %0;" ::"n"(N) : "memory"); }

template <int N>
__device__ __forceinline__ void fence_regs(float (&r)[N]) {
#pragma unroll
  for (int i = 0; i < N; i++) asm volatile("" : "+f"(r[i])::"memory");
}
template <int N>
__device__ __forceinline__ void fence_regs(uint32_t (&r)[N]) {
#pragma unroll
  for (int i = 0; i < N; i++) asm volatile("" : "+r"(r[i])::"memory");
}
__device__ __forceinline__ uint64_t make_desc(uint32_t addr, uint32_t lbo, uint32_t sbo, uint32_t layout) {
  return (uint64_t)((addr & 0x3FFFF) >> 4) | ((uint64_t)((lbo & 0x3FFFF) >> 4) << 16) | ((uint64_t)((sbo & 0x3FFFF) >> 4) << 32) |
         ((uint64_t)layout << 62);
}
__device__ __forceinline__ uint32_t pack_bf16(float lo, float hi) {
  uint32_t r;
  asm("cvt.rn.bf16x2.f32 %0, %1, %2;" : "=r"(r) : "f"(hi), "f"(lo));
  return r;
}
__device__ __forceinline__ float bf16_round(float x) { return __bfloat162float(__float2bfloat16_rn(x)); }
__device__ __forceinline__ float bf_lo(uint32_t u) { return __uint_as_float(u << 16); }
__device__ __forceinline__ float bf_hi(uint32_t u) { return __uint_as_float(u & 0xffff0000u); }
__device__ __forceinline__ float ex2(float x) {
  float y;
  asm("ex2.approx.ftz.f32 %0, %1;" : "=f"(y) : "f"(x));
  return y;
}

__device__ __forceinline__ void wgmma_ss_n240_tb(float (&d)[120], uint64_t descA, uint64_t descB, int scaleD) {
  asm volatile("{\n.reg .pred p;\nsetp.ne.b32 p, %122, 0;\n"
    "wgmma.mma_async.sync.aligned.m64n240k16.f32.bf16.bf16 {%0, %1, %2, %3, %4, %5, %6, %7, %8, %9, %10, %11, %12, %13, %14, %15, %16, %17, %18, %19, %20, %21, %22, %23, %24, %25, %26, %27, %28, %29, %30, %31, %32, %33, %34, %35, %36, %37, %38, %39, %40, %41, %42, %43, %44, %45, %46, %47, %48, %49, %50, %51, %52, %53, %54, %55, %56, %57, %58, %59, %60, %61, %62, %63, %64, %65, %66, %67, %68, %69, %70, %71, %72, %73, %74, %75, %76, %77, %78, %79, %80, %81, %82, %83, %84, %85, %86, %87, %88, %89, %90, %91, %92, %93, %94, %95, %96, %97, %98, %99, %100, %101, %102, %103, %104, %105, %106, %107, %108, %109, %110, %111, %112, %113, %114, %115, %116, %117, %118, %119}, %120, %121, p, 1, 1, 0, 1;\n}\n"
    : "+f"(d[0]), "+f"(d[1]), "+f"(d[2]), "+f"(d[3]), "+f"(d[4]), "+f"(d[5]), "+f"(d[6]), "+f"(d[7]), "+f"(d[8]), "+f"(d[9]), "+f"(d[10]), "+f"(d[11]), "+f"(d[12]), "+f"(d[13]), "+f"(d[14]), "+f"(d[15]), "+f"(d[16]), "+f"(d[17]), "+f"(d[18]), "+f"(d[19]), "+f"(d[20]), "+f"(d[21]), "+f"(d[22]), "+f"(d[23]), "+f"(d[24]), "+f"(d[25]), "+f"(d[26]), "+f"(d[27]), "+f"(d[28]), "+f"(d[29]), "+f"(d[30]), "+f"(d[31]), "+f"(d[32]), "+f"(d[33]), "+f"(d[34]), "+f"(d[35]), "+f"(d[36]), "+f"(d[37]), "+f"(d[38]), "+f"(d[39]), "+f"(d[40]), "+f"(d[41]), "+f"(d[42]), "+f"(d[43]), "+f"(d[44]), "+f"(d[45]), "+f"(d[46]), "+f"(d[47]), "+f"(d[48]), "+f"(d[49]), "+f"(d[50]), "+f"(d[51]), "+f"(d[52]), "+f"(d[53]), "+f"(d[54]), "+f"(d[55]), "+f"(d[56]), "+f"(d[57]), "+f"(d[58]), "+f"(d[59]), "+f"(d[60]), "+f"(d[61]), "+f"(d[62]), "+f"(d[63]), "+f"(d[64]), "+f"(d[65]), "+f"(d[66]), "+f"(d[67]), "+f"(d[68]), "+f"(d[69]), "+f"(d[70]), "+f"(d[71]), "+f"(d[72]), "+f"(d[73]), "+f"(d[74]), "+f"(d[75]), "+f"(d[76]), "+f"(d[77]), "+f"(d[78]), "+f"(d[79]), "+f"(d[80]), "+f"(d[81]), "+f"(d[82]), "+f"(d[83]), "+f"(d[84]), "+f"(d[85]), "+f"(d[86]), "+f"(d[87]), "+f"(d[88]), "+f"(d[89]), "+f"(d[90]), "+f"(d[91]), "+f"(d[92]), "+f"(d[93]), "+f"(d[94]), "+f"(d[95]), "+f"(d[96]), "+f"(d[97]), "+f"(d[98]), "+f"(d[99]), "+f"(d[100]), "+f"(d[101]), "+f"(d[102]), "+f"(d[103]), "+f"(d[104]), "+f"(d[105]), "+f"(d[106]), "+f"(d[107]), "+f"(d[108]), "+f"(d[109]), "+f"(d[110]), "+f"(d[111]), "+f"(d[112]), "+f"(d[113]), "+f"(d[114]), "+f"(d[115]), "+f"(d[116]), "+f"(d[117]), "+f"(d[118]), "+f"(d[119])
    : "l"(descA), "l"(descB), "r"(scaleD));
}
__device__ __forceinline__ void wgmma_ss_n192_tb(float (&d)[96], uint64_t descA, uint64_t descB, int scaleD) {
  asm volatile("{\n.reg .pred p;\nsetp.ne.b32 p, %98, 0;\n"
    "wgmma.mma_async.sync.aligned.m64n192k16.f32.bf16.bf16 {%0, %1, %2, %3, %4, %5, %6, %7, %8, %9, %10, %11, %12, %13, %14, %15, %16, %17, %18, %19, %20, %21, %22, %23, %24, %25, %26, %27, %28, %29, %30, %31, %32, %33, %34, %35, %36, %37, %38, %39, %40, %41, %42, %43, %44, %45, %46, %47, %48, %49, %50, %51, %52, %53, %54, %55, %56, %57, %58, %59, %60, %61, %62, %63, %64, %65, %66, %67, %68, %69, %70, %71, %72, %73, %74, %75, %76, %77, %78, %79, %80, %81, %82, %83, %84, %85, %86, %87, %88, %89, %90, %91, %92, %93, %94, %95}, %96, %97, p, 1, 1, 0, 1;\n}\n"
    : "+f"(d[0]), "+f"(d[1]), "+f"(d[2]), "+f"(d[3]), "+f"(d[4]), "+f"(d[5]), "+f"(d[6]), "+f"(d[7]), "+f"(d[8]), "+f"(d[9]), "+f"(d[10]), "+f"(d[11]), "+f"(d[12]), "+f"(d[13]), "+f"(d[14]), "+f"(d[15]), "+f"(d[16]), "+f"(d[17]), "+f"(d[18]), "+f"(d[19]), "+f"(d[20]), "+f"(d[21]), "+f"(d[22]), "+f"(d[23]), "+f"(d[24]), "+f"(d[25]), "+f"(d[26]), "+f"(d[27]), "+f"(d[28]), "+f"(d[29]), "+f"(d[30]), "+f"(d[31]), "+f"(d[32]), "+f"(d[33]), "+f"(d[34]), "+f"(d[35]), "+f"(d[36]), "+f"(d[37]), "+f"(d[38]), "+f"(d[39]), "+f"(d[40]), "+f"(d[41]), "+f"(d[42]), "+f"(d[43]), "+f"(d[44]), "+f"(d[45]), "+f"(d[46]), "+f"(d[47]), "+f"(d[48]), "+f"(d[49]), "+f"(d[50]), "+f"(d[51]), "+f"(d[52]), "+f"(d[53]), "+f"(d[54]), "+f"(d[55]), "+f"(d[56]), "+f"(d[57]), "+f"(d[58]), "+f"(d[59]), "+f"(d[60]), "+f"(d[61]), "+f"(d[62]), "+f"(d[63]), "+f"(d[64]), "+f"(d[65]), "+f"(d[66]), "+f"(d[67]), "+f"(d[68]), "+f"(d[69]), "+f"(d[70]), "+f"(d[71]), "+f"(d[72]), "+f"(d[73]), "+f"(d[74]), "+f"(d[75]), "+f"(d[76]), "+f"(d[77]), "+f"(d[78]), "+f"(d[79]), "+f"(d[80]), "+f"(d[81]), "+f"(d[82]), "+f"(d[83]), "+f"(d[84]), "+f"(d[85]), "+f"(d[86]), "+f"(d[87]), "+f"(d[88]), "+f"(d[89]), "+f"(d[90]), "+f"(d[91]), "+f"(d[92]), "+f"(d[93]), "+f"(d[94]), "+f"(d[95])
    : "l"(descA), "l"(descB), "r"(scaleD));
}
__device__ __forceinline__ void wgmma_ss_n64_tb(float (&d)[32], uint64_t descA, uint64_t descB, int scaleD) {
  asm volatile("{\n.reg .pred p;\nsetp.ne.b32 p, %34, 0;\n"
    "wgmma.mma_async.sync.aligned.m64n64k16.f32.bf16.bf16 {%0, %1, %2, %3, %4, %5, %6, %7, %8, %9, %10, %11, %12, %13, %14, %15, %16, %17, %18, %19, %20, %21, %22, %23, %24, %25, %26, %27, %28, %29, %30, %31}, %32, %33, p, 1, 1, 0, 1;\n}\n"
    : "+f"(d[0]), "+f"(d[1]), "+f"(d[2]), "+f"(d[3]), "+f"(d[4]), "+f"(d[5]), "+f"(d[6]), "+f"(d[7]), "+f"(d[8]), "+f"(d[9]), "+f"(d[10]), "+f"(d[11]), "+f"(d[12]), "+f"(d[13]), "+f"(d[14]), "+f"(d[15]), "+f"(d[16]), "+f"(d[17]), "+f"(d[18]), "+f"(d[19]), "+f"(d[20]), "+f"(d[21]), "+f"(d[22]), "+f"(d[23]), "+f"(d[24]), "+f"(d[25]), "+f"(d[26]), "+f"(d[27]), "+f"(d[28]), "+f"(d[29]), "+f"(d[30]), "+f"(d[31])
    : "l"(descA), "l"(descB), "r"(scaleD));
}
__device__ __forceinline__ void wgmma_ss_n16_tb(float (&d)[8], uint64_t descA, uint64_t descB, int scaleD) {
  asm volatile("{\n.reg .pred p;\nsetp.ne.b32 p, %10, 0;\n"
    "wgmma.mma_async.sync.aligned.m64n16k16.f32.bf16.bf16 {%0, %1, %2, %3, %4, %5, %6, %7}, %8, %9, p, 1, 1, 0, 1;\n}\n"
    : "+f"(d[0]), "+f"(d[1]), "+f"(d[2]), "+f"(d[3]), "+f"(d[4]), "+f"(d[5]), "+f"(d[6]), "+f"(d[7])
    : "l"(descA), "l"(descB), "r"(scaleD));
}
__device__ __forceinline__ void wgmma_rs_n128(float (&d)[64], uint32_t a0, uint32_t a1, uint32_t a2, uint32_t a3, uint64_t descB, int scaleD) {
  asm volatile("{\n.reg .pred p;\nsetp.ne.b32 p, %69, 0;\n"
    "wgmma.mma_async.sync.aligned.m64n128k16.f32.bf16.bf16 {%0, %1, %2, %3, %4, %5, %6, %7, %8, %9, %10, %11, %12, %13, %14, %15, %16, %17, %18, %19, %20, %21, %22, %23, %24, %25, %26, %27, %28, %29, %30, %31, %32, %33, %34, %35, %36, %37, %38, %39, %40, %41, %42, %43, %44, %45, %46, %47, %48, %49, %50, %51, %52, %53, %54, %55, %56, %57, %58, %59, %60, %61, %62, %63}, {%64, %65, %66, %67}, %68, p, 1, 1, 0;\n}\n"
    : "+f"(d[0]), "+f"(d[1]), "+f"(d[2]), "+f"(d[3]), "+f"(d[4]), "+f"(d[5]), "+f"(d[6]), "+f"(d[7]), "+f"(d[8]), "+f"(d[9]), "+f"(d[10]), "+f"(d[11]), "+f"(d[12]), "+f"(d[13]), "+f"(d[14]), "+f"(d[15]), "+f"(d[16]), "+f"(d[17]), "+f"(d[18]), "+f"(d[19]), "+f"(d[20]), "+f"(d[21]), "+f"(d[22]), "+f"(d[23]), "+f"(d[24]), "+f"(d[25]), "+f"(d[26]), "+f"(d[27]), "+f"(d[28]), "+f"(d[29]), "+f"(d[30]), "+f"(d[31]), "+f"(d[32]), "+f"(d[33]), "+f"(d[34]), "+f"(d[35]), "+f"(d[36]), "+f"(d[37]), "+f"(d[38]), "+f"(d[39]), "+f"(d[40]), "+f"(d[41]), "+f"(d[42]), "+f"(d[43]), "+f"(d[44]), "+f"(d[45]), "+f"(d[46]), "+f"(d[47]), "+f"(d[48]), "+f"(d[49]), "+f"(d[50]), "+f"(d[51]), "+f"(d[52]), "+f"(d[53]), "+f"(d[54]), "+f"(d[55]), "+f"(d[56]), "+f"(d[57]), "+f"(d[58]), "+f"(d[59]), "+f"(d[60]), "+f"(d[61]), "+f"(d[62]), "+f"(d[63])
    : "r"(a0), "r"(a1), "r"(a2), "r"(a3), "l"(descB), "r"(scaleD));
}
__device__ __forceinline__ void wgmma_rs_n64(float (&d)[32], uint32_t a0, uint32_t a1, uint32_t a2, uint32_t a3, uint64_t descB, int scaleD) {
  asm volatile("{\n.reg .pred p;\nsetp.ne.b32 p, %37, 0;\n"
    "wgmma.mma_async.sync.aligned.m64n64k16.f32.bf16.bf16 {%0, %1, %2, %3, %4, %5, %6, %7, %8, %9, %10, %11, %12, %13, %14, %15, %16, %17, %18, %19, %20, %21, %22, %23, %24, %25, %26, %27, %28, %29, %30, %31}, {%32, %33, %34, %35}, %36, p, 1, 1, 0;\n}\n"
    : "+f"(d[0]), "+f"(d[1]), "+f"(d[2]), "+f"(d[3]), "+f"(d[4]), "+f"(d[5]), "+f"(d[6]), "+f"(d[7]), "+f"(d[8]), "+f"(d[9]), "+f"(d[10]), "+f"(d[11]), "+f"(d[12]), "+f"(d[13]), "+f"(d[14]), "+f"(d[15]), "+f"(d[16]), "+f"(d[17]), "+f"(d[18]), "+f"(d[19]), "+f"(d[20]), "+f"(d[21]), "+f"(d[22]), "+f"(d[23]), "+f"(d[24]), "+f"(d[25]), "+f"(d[26]), "+f"(d[27]), "+f"(d[28]), "+f"(d[29]), "+f"(d[30]), "+f"(d[31])
    : "r"(a0), "r"(a1), "r"(a2), "r"(a3), "l"(descB), "r"(scaleD));
}
__device__ __forceinline__ void wgmma_rs_n24_tb(float (&d)[12], uint32_t a0, uint32_t a1, uint32_t a2, uint32_t a3, uint64_t descB, int scaleD) {
  asm volatile("{\n.reg .pred p;\nsetp.ne.b32 p, %17, 0;\n"
    "wgmma.mma_async.sync.aligned.m64n24k16.f32.bf16.bf16 {%0, %1, %2, %3, %4, %5, %6, %7, %8, %9, %10, %11}, {%12, %13, %14, %15}, %16, p, 1, 1, 1;\n}\n"
    : "+f"(d[0]), "+f"(d[1]), "+f"(d[2]), "+f"(d[3]), "+f"(d[4]), "+f"(d[5]), "+f"(d[6]), "+f"(d[7]), "+f"(d[8]), "+f"(d[9]), "+f"(d[10]), "+f"(d[11])
    : "r"(a0), "r"(a1), "r"(a2), "r"(a3), "l"(descB), "r"(scaleD));
}

constexpr int GT = 384;

__device__ __forceinline__ void release_stage(uint32_t bar, bool leader) {
  if (leader) {
    mbar_arrive_cluster(bar, 0);
    mbar_arrive_cluster(bar, 1);
  }
}

__device__ __forceinline__ void ln_row(const bf16* __restrict__ xin, bf16* __restrict__ xout, int l16) {
  const uint4* src = reinterpret_cast<const uint4*>(xin);
  uint4 v[5];
#pragma unroll
  for (int j = 0; j < 5; j++) v[j] = __ldg(src + j * 16 + l16);
  float s0 = 0.f, s1 = 0.f, s2 = 0.f, s3 = 0.f;
#pragma unroll
  for (int j = 0; j < 5; j++) {
    s0 += bf_lo(v[j].x) + bf_hi(v[j].x);
    s1 += bf_lo(v[j].y) + bf_hi(v[j].y);
    s2 += bf_lo(v[j].z) + bf_hi(v[j].z);
    s3 += bf_lo(v[j].w) + bf_hi(v[j].w);
  }
  float mean = (s0 + s1) + (s2 + s3);
#pragma unroll
  for (int o = 1; o < 16; o <<= 1) mean += __shfl_xor_sync(0xffffffffu, mean, o);
  mean *= (1.0f / DM);
  s0 = s1 = s2 = s3 = 0.f;
#pragma unroll
  for (int j = 0; j < 5; j++) {
    float d;
    d = bf_lo(v[j].x) - mean; s0 = fmaf(d, d, s0);
    d = bf_hi(v[j].x) - mean; s1 = fmaf(d, d, s1);
    d = bf_lo(v[j].y) - mean; s2 = fmaf(d, d, s2);
    d = bf_hi(v[j].y) - mean; s3 = fmaf(d, d, s3);
    d = bf_lo(v[j].z) - mean; s0 = fmaf(d, d, s0);
    d = bf_hi(v[j].z) - mean; s1 = fmaf(d, d, s1);
    d = bf_lo(v[j].w) - mean; s2 = fmaf(d, d, s2);
    d = bf_hi(v[j].w) - mean; s3 = fmaf(d, d, s3);
  }
  float sq = (s0 + s1) + (s2 + s3);
#pragma unroll
  for (int o = 1; o < 16; o <<= 1) sq += __shfl_xor_sync(0xffffffffu, sq, o);
  const float var_b = bf16_round(sq * (1.0f / DM));
  const float den = bf16_round(sqrtf(bf16_round(var_b + 1e-5f)));
  const float iv = __frcp_rn(den);
  const float mb = bf16_round(mean);
  uint4* dst = reinterpret_cast<uint4*>(xout);
#pragma unroll
  for (int j = 0; j < 5; j++) {
    uint4 w;
    uint32_t t;
    t = pack_bf16(bf_lo(v[j].x) - mb, bf_hi(v[j].x) - mb); w.x = pack_bf16(bf_lo(t) * iv, bf_hi(t) * iv);
    t = pack_bf16(bf_lo(v[j].y) - mb, bf_hi(v[j].y) - mb); w.y = pack_bf16(bf_lo(t) * iv, bf_hi(t) * iv);
    t = pack_bf16(bf_lo(v[j].z) - mb, bf_hi(v[j].z) - mb); w.z = pack_bf16(bf_lo(t) * iv, bf_hi(t) * iv);
    t = pack_bf16(bf_lo(v[j].w) - mb, bf_hi(v[j].w) - mb); w.w = pack_bf16(bf_lo(t) * iv, bf_hi(t) * iv);
    dst[j * 16 + l16] = w;
  }
}

constexpr int LG_STAGES = 5;
constexpr int QKV_STAGE = 8192 + 4 * 4096;
constexpr int GLU_STAGE = 8192 + 6 * 4096;

template <int WG>
__device__ __forceinline__ void qkv_mainloop(float (&acc)[120], uint32_t sbase, uint32_t sBar, bool leader) {
  constexpr int STAGE_BYTES = QKV_STAGE, NST = LG_STAGES;
  const uint64_t da_base = make_desc(sbase + WG * 4096, 16, 512, 2);
  const uint64_t db_base = make_desc(sbase + 8192, 4096, 1024, 1);
#pragma unroll 1
  for (int r = 0; r < 20 / NST; r++) {
#pragma unroll
    for (int s = 0; s < NST; s++) {
      mbar_wait(sBar + 8 * s, r & 1);
      wgmma_fence();
#pragma unroll
      for (int ks = 0; ks < 2; ks++)
        wgmma_ss_n240_tb(acc, da_base + (uint64_t)((s * STAGE_BYTES + ks * 32) >> 4), db_base + (uint64_t)((s * STAGE_BYTES + ks * 2048) >> 4), 1);
      wgmma_commit();
      wgmma_wait<1>();
      release_stage(sBar + 8 * (NST + (s + NST - 1) % NST), leader && (s > 0 || r > 0));
    }
  }
}
template <int WG>
__device__ __forceinline__ void glu_mainloop(float (&accg)[96], float (&accu)[96], uint32_t sbase, uint32_t sBar, bool leader) {
  constexpr int STAGE_BYTES = GLU_STAGE, NST = LG_STAGES;
  const uint64_t da_base = make_desc(sbase + WG * 4096, 16, 512, 2);
  const uint64_t db_base = make_desc(sbase + 8192, 4096, 1024, 1);
#pragma unroll 1
  for (int r = 0; r < 20 / NST; r++) {
#pragma unroll
    for (int s = 0; s < NST; s++) {
      mbar_wait(sBar + 8 * s, r & 1);
      wgmma_fence();
#pragma unroll
      for (int ks = 0; ks < 2; ks++) {
        const uint64_t da = da_base + (uint64_t)((s * STAGE_BYTES + ks * 32) >> 4);
        wgmma_ss_n192_tb(accg, da, db_base + (uint64_t)((s * STAGE_BYTES + ks * 2048) >> 4), 1);
        wgmma_ss_n192_tb(accu, da, db_base + (uint64_t)((s * STAGE_BYTES + 3 * 4096 + ks * 2048) >> 4), 1);
      }
      wgmma_commit();
      wgmma_wait<1>();
      release_stage(sBar + 8 * (NST + (s + NST - 1) % NST), leader && (s > 0 || r > 0));
    }
  }
}
constexpr int RG_STAGE_BYTES = 16384 + 8192 + 2048;
template <int NKB, int NST, int WG>
__device__ __forceinline__ void res_mainloop(float (&acc0)[32], float (&acc1)[8], uint32_t sbase, uint32_t sBar, bool leader) {
  const uint64_t da_base = make_desc(sbase + WG * 8192, 16, 1024, 1);
  const uint64_t db0_base = make_desc(sbase + 16384, 8192, 1024, 1);
  const uint64_t db1_base = make_desc(sbase + 16384 + 8192, 2048, 256, 3);
#pragma unroll 1
  for (int r = 0; r < NKB / NST; r++) {
#pragma unroll
    for (int s = 0; s < NST; s++) {
      const uint64_t so = (uint64_t)(s * (RG_STAGE_BYTES >> 4));
      mbar_wait(sBar + 8 * s, r & 1);
      wgmma_fence();
#pragma unroll
      for (int ks = 0; ks < 4; ks++) {
        wgmma_ss_n64_tb(acc0, da_base + so + ks * 2, db0_base + so + ks * 128, 1);
        wgmma_ss_n16_tb(acc1, da_base + so + ks * 2, db1_base + so + ks * 32, 1);
      }
      wgmma_commit();
      wgmma_wait<1>();
      release_stage(sBar + 8 * (NST + (s + NST - 1) % NST), leader && (s > 0 || r > 0));
    }
  }
}

constexpr int KA_SMEM = LG_STAGES * QKV_STAGE + 128 + 1024;

__global__ void __launch_bounds__(GT, 1)
qkv_kernel(const __grid_constant__ CUtensorMap tmA, const __grid_constant__ CUtensorMap tmB, const bf16* __restrict__ x) {
  constexpr int STAGE_BYTES = QKV_STAGE, NST = LG_STAGES, NKB = 20;
  extern __shared__ uint8_t smem_raw[];
  const uint32_t sbase = (smem_u32(smem_raw) + 1023u) & ~1023u;
  const uint32_t sBar = sbase + NST * STAGE_BYTES;
  const int tid = threadIdx.x, warp = tid >> 5, lane = tid & 31;
  const int rank = blockIdx.x & 1;
  const int pair = blockIdx.x >> 1;
  const int n_blk = pair & 7;
  const int m_blk = (pair >> 3) * 2 + rank;
  TS(0, 0);
  if (tid == 256) {
    prefetch_tmap(&tmA);
    prefetch_tmap(&tmB);
  }
  if (tid == 0) {
    for (int s = 0; s < NST; s++) {
      mbar_init(sBar + 8 * s, 1);
      mbar_init(sBar + 8 * (NST + s), 4);
    }
    fence_mbar_init();
    if (blockIdx.x < 16) g_flag[16 + blockIdx.x] = 0;
    g_flag[32 + blockIdx.x] = 0;
  }
  pdl_launch();
  cluster_sync_all();

  if (warp >= 8) {
    asm volatile("setmaxnreg.dec.sync.aligned.u32 40;");
    if (warp == 9) {
      named_bar_sync(5, 288);
      if (lane == 0) flag_signal(&g_flag[m_blk]);
    }
    if (tid == 256) {
      auto issue_b = [&](int kb) {
        const int s = kb % NST;
        const uint32_t full = sBar + 8 * s;
        mbar_expect_tx(full, STAGE_BYTES);
        const uint32_t dst = sbase + s * STAGE_BYTES + 8192;
#pragma unroll
        for (int j = 0; j < 2; j++) {
          const int sl = rank * 2 + j;
          tma_load_2d_mc(dst + sl * 4096, &tmB, n_blk * 240 + sl * 64, kb * 32, full, (uint16_t)3);
        }
      };
      for (int kb = 0; kb < NST; kb++) issue_b(kb);
      flag_wait(&g_flag[m_blk], 8);
      fence_proxy_async_all();
      for (int kb = 0; kb < NKB; kb++) {
        const int s = kb % NST;
        if (kb >= NST) {
          mbar_wait(sBar + 8 * (NST + s), ((kb / NST) & 1) ^ 1);
          issue_b(kb);
        }
        tma_load_2d(sbase + s * STAGE_BYTES, &tmA, kb * 32, m_blk * 128, sBar + 8 * s);
      }
    }
  } else {
    asm volatile("setmaxnreg.inc.sync.aligned.u32 232;");
    const int wg = __shfl_sync(0xffffffffu, warp >> 2, 0);
    const int wwarp = warp & 3;
    {
      const int row = m_blk * 128 + n_blk * 16 + warp * 2 + (lane >> 4);
      ln_row(x + (size_t)row * DM, g_xn + (size_t)row * DM, lane & 15);
      asm volatile("bar.arrive 5, 288;" ::: "memory");
    }
    TS(0, 1);
    mbar_wait(sBar, 0);
    TS(0, 3);
    float acc[120];
#pragma unroll
    for (int i = 0; i < 120; i++) acc[i] = 0.f;
    if (wg == 0) qkv_mainloop<0>(acc, sbase, sBar, (tid & 127) == 0);
    else qkv_mainloop<1>(acc, sbase, sBar, (tid & 127) == 0);
    wgmma_wait<0>();
    fence_regs(acc);
    TS(0, 4);
    named_bar_sync(3, 256);
    const int g = lane >> 2, c4 = lane & 3;
    const uint32_t stg = sbase + wg * (12 * 3072) + (wwarp * 2) * 384 + g * 16;
    const int hbase = n_blk * 12;
#pragma unroll
    for (int j = 0; j < 30; j++) {
      const int cb = (j * 8) % 20;
      const int hb = (j * 8) / 20;
      int d = cb + c4 * 2;
      int hl = hb;
      if (cb == 16 && c4 >= 2) { d -= 20; hl += 1; }
      const uint32_t a0 = stg + hl * 3072 + (d >> 3) * 128 + (d & 7) * 2;
      const int hg = hbase + hl;
      const float sc = hg < 32 ? ATT_SCALE_LOG2E : 1.0f;
      st_shared_b32(a0, pack_bf16(acc[4 * j] * sc, acc[4 * j + 1] * sc));
      st_shared_b32(a0 + 384, pack_bf16(acc[4 * j + 2] * sc, acc[4 * j + 3] * sc));
      if (d == 18) {
        const uint32_t pad0 = hg < 32 ? 0u : (hg < 64 ? 0x3f803f80u : 0x00003f80u);
        const uint32_t pad1 = (hg >= 32 && hg < 64) ? 0x00003f80u : 0u;
        st_shared_v2(a0 + 4, pad0, pad1);
        st_shared_v2(a0 + 388, pad0, pad1);
      }
      if (j % 10 == 9) {
        fence_proxy_async();
        named_bar_sync(1 + wg, 128);
        if ((tid & 127) < 4) {
          const int hs = (j / 10) * 4 + (tid & 127);
          bf16* dst = g_img + (size_t)(hbase + hs) * IMG_HEAD_ELEMS + (size_t)(m_blk * 16 + wg * 8) * 192;
          bulk_s2g(dst, sbase + wg * (12 * 3072) + hs * 3072, 3072);
          bulk_commit();
        }
      }
    }
    if ((tid & 127) < 4) bulk_wait_read();
  }
  __syncwarp();
  TS(0, 5);
  cluster_sync_relaxed();
  TS(0, 6);
}

constexpr int KC_NST1 = 5, KC_NST3 = 6;
constexpr int KC_STAGING = 160 * 1024;
constexpr int KC_BAR = KC_STAGING + 48 * 1024;
constexpr int KC_CS = KC_BAR + 512;
constexpr int KC_SMEM = KC_CS + 1536 + 1024;

__global__ void __launch_bounds__(GT, 1)
mlp_kernel(const __grid_constant__ CUtensorMap tmO, const __grid_constant__ CUtensorMap tmWo64, const __grid_constant__ CUtensorMap tmWo16,
           const __grid_constant__ CUtensorMap tmH, const __grid_constant__ CUtensorMap tmWg, const __grid_constant__ CUtensorMap tmWu,
           const __grid_constant__ CUtensorMap tmHHs, const __grid_constant__ CUtensorMap tmHH, const __grid_constant__ CUtensorMap tmWd64,
           const __grid_constant__ CUtensorMap tmWd16, const __grid_constant__ CUtensorMap tmHs, const __grid_constant__ CUtensorMap tmOut,
           const bf16* __restrict__ x) {
  extern __shared__ uint8_t smem_raw[];
  const uint32_t sbase = (smem_u32(smem_raw) + 1023u) & ~1023u;
  const uint32_t bar1 = sbase + KC_BAR;
  const uint32_t bar2 = bar1 + 128;
  const uint32_t bar3 = bar2 + 128;
  const uint32_t barD = bar3 + 128;
  const int tid = threadIdx.x, warp = tid >> 5, lane = tid & 31;
  const int rank = blockIdx.x & 1;
  const int pair = blockIdx.x >> 1;
  const int j_blk = pair & 7;
  const int m_blk = (pair >> 3) * 2 + rank;
  const int n0 = j_blk * 80;
  TS(2, 0);
  if (tid == 256) {
    prefetch_tmap(&tmO); prefetch_tmap(&tmWo64); prefetch_tmap(&tmWo16); prefetch_tmap(&tmH); prefetch_tmap(&tmWg);
    prefetch_tmap(&tmWu); prefetch_tmap(&tmHHs); prefetch_tmap(&tmHH); prefetch_tmap(&tmWd64); prefetch_tmap(&tmWd16);
    prefetch_tmap(&tmHs); prefetch_tmap(&tmOut);
  }
  if (tid == 0) {
    for (int s = 0; s < 5; s++) {
      mbar_init(bar1 + 8 * s, 1); mbar_init(bar1 + 8 * (5 + s), 4);
      mbar_init(bar2 + 8 * s, 1); mbar_init(bar2 + 8 * (5 + s), 4);
    }
    for (int s = 0; s < 6; s++) { mbar_init(bar3 + 8 * s, 1); mbar_init(bar3 + 8 * (6 + s), 4); }
    mbar_init(barD, 4); mbar_init(barD + 8, 4); mbar_init(barD + 16, 2);
    fence_mbar_init();
  }
  cluster_sync_all();

  if (warp >= 8) {
    asm volatile("setmaxnreg.dec.sync.aligned.u32 40;");
    if (tid == 256) {
      auto issue_b80 = [&](const CUtensorMap* t64, const CUtensorMap* t16, uint32_t bars, int nst, int kb) {
        const int s = kb % nst;
        const uint32_t full = bars + 8 * s;
        const uint32_t st = sbase + s * RG_STAGE_BYTES;
        mbar_expect_tx(full, RG_STAGE_BYTES);
        tma_load_2d_mc(st + 16384 + rank * 4096, t64, n0, kb * 64 + rank * 32, full, (uint16_t)3);
        tma_load_2d_mc(st + 16384 + 8192 + rank * 1024, t16, n0 + 64, kb * 64 + rank * 32, full, (uint16_t)3);
      };
      for (int kb = 0; kb < KC_NST1; kb++) issue_b80(&tmWo64, &tmWo16, bar1, KC_NST1, kb);
      pdl_wait();
      for (int kb = 0; kb < 10; kb++) {
        const int s = kb % KC_NST1;
        if (kb >= KC_NST1) {
          mbar_wait(bar1 + 8 * (KC_NST1 + s), ((kb / KC_NST1) & 1) ^ 1);
          issue_b80(&tmWo64, &tmWo16, bar1, KC_NST1, kb);
        }
        tma_load_2d(sbase + s * RG_STAGE_BYTES, &tmO, kb * 64, m_blk * 128, bar1 + 8 * s);
      }
      auto issue_bglu = [&](int kb) {
        const int s = kb % LG_STAGES;
        const uint32_t full = bar2 + 8 * s;
        mbar_expect_tx(full, GLU_STAGE);
        const uint32_t dst = sbase + s * GLU_STAGE + 8192;
#pragma unroll
        for (int j = 0; j < 3; j++)
          tma_load_2d_mc(dst + (rank * 3 + j) * 4096, rank == 0 ? &tmWg : &tmWu, j_blk * 192 + j * 64, kb * 32, full, (uint16_t)3);
      };
      mbar_wait(barD, 0);
      for (int kb = 0; kb < LG_STAGES; kb++) issue_bglu(kb);
      flag_wait(&g_flag[16 + m_blk], 16);
      fence_proxy_async_all();
      for (int kb = 0; kb < 20; kb++) {
        const int s = kb % LG_STAGES;
        if (kb >= LG_STAGES) {
          mbar_wait(bar2 + 8 * (LG_STAGES + s), ((kb / LG_STAGES) & 1) ^ 1);
          issue_bglu(kb);
        }
        tma_load_2d(sbase + s * GLU_STAGE, &tmH, kb * 32, m_blk * 128, bar2 + 8 * s);
      }
      mbar_wait(barD + 8, 0);
      auto issue_b3 = [&](int it) {
        const int kb = (j_blk * 3 + it) % 24;
        const int s = it % KC_NST3;
        const uint32_t full = bar3 + 8 * s;
        const uint32_t st = sbase + s * RG_STAGE_BYTES;
        mbar_expect_tx(full, RG_STAGE_BYTES);
        tma_load_2d_mc(st + 16384 + rank * 4096, &tmWd64, n0, kb * 64 + rank * 32, full, (uint16_t)3);
        tma_load_2d_mc(st + 16384 + 8192 + rank * 1024, &tmWd16, n0 + 64, kb * 64 + rank * 32, full, (uint16_t)3);
      };
      for (int it = 0; it < KC_NST3; it++) issue_b3(it);
      for (int it = 0; it < 24; it++) {
        const int s = it % KC_NST3;
        if (it >= KC_NST3) {
          mbar_wait(bar3 + 8 * (KC_NST3 + s), ((it / KC_NST3) & 1) ^ 1);
          issue_b3(it);
        }
        if (it == 0) {
          mbar_wait(barD + 16, 0);
          fence_proxy_async_all();
        } else if (it == 3) {
          for (int jj = 1; jj < 8; jj++) flag_wait(&g_flag[32 + m_blk * 8 + (j_blk + jj) % 8], 2);
          fence_proxy_async_all();
        }
        tma_load_2d(sbase + s * RG_STAGE_BYTES, &tmHH, ((j_blk * 3 + it) % 24) * 64, m_blk * 128, bar3 + 8 * s);
      }
    }
  } else {
    asm volatile("setmaxnreg.inc.sync.aligned.u32 232;");
    const int wg = __shfl_sync(0xffffffffu, warp >> 2, 0);
    const int wwarp = warp & 3;
    const int g = lane >> 2, c4 = lane & 3;
    const int row0 = m_blk * 128 + wg * 64 + wwarp * 16 + g;
    const bool leader = (tid & 127) == 0;
    const uint32_t stg80_base = sbase + KC_STAGING + wg * 24576;
    const uint32_t stg80 = stg80_base + (wwarp * 16 + g) * 160 + c4 * 4;
    {
      uint32_t res[20];
#pragma unroll
      for (int j = 0; j < 10; j++) {
        res[2 * j] = __ldg(reinterpret_cast<const uint32_t*>(x + (size_t)row0 * DM + n0 + j * 8 + c4 * 2));
        res[2 * j + 1] = __ldg(reinterpret_cast<const uint32_t*>(x + (size_t)(row0 + 8) * DM + n0 + j * 8 + c4 * 2));
      }
      float acc0[32], acc1[8];
#pragma unroll
      for (int i = 0; i < 32; i++) acc0[i] = 0.f;
#pragma unroll
      for (int i = 0; i < 8; i++) acc1[i] = 0.f;
      TS(2, 1);
      if (wg == 0) res_mainloop<10, KC_NST1, 0>(acc0, acc1, sbase, bar1, leader);
      else res_mainloop<10, KC_NST1, 1>(acc0, acc1, sbase, bar1, leader);
      wgmma_wait<0>();
      fence_regs(acc0); fence_regs(acc1);
      release_stage(barD, leader);
      TS(2, 4);
      float sum0 = 0.f, sum1 = 0.f;
#pragma unroll
      for (int j = 0; j < 10; j++) {
        const uint32_t a01 = j < 8 ? pack_bf16(acc0[4 * j], acc0[4 * j + 1]) : pack_bf16(acc1[4 * (j - 8)], acc1[4 * (j - 8) + 1]);
        const uint32_t a23 = j < 8 ? pack_bf16(acc0[4 * j + 2], acc0[4 * j + 3]) : pack_bf16(acc1[4 * (j - 8) + 2], acc1[4 * (j - 8) + 3]);
        res[2 * j] = pack_bf16(bf_lo(res[2 * j]) + bf_lo(a01), bf_hi(res[2 * j]) + bf_hi(a01));
        res[2 * j + 1] = pack_bf16(bf_lo(res[2 * j + 1]) + bf_lo(a23), bf_hi(res[2 * j + 1]) + bf_hi(a23));
        st_shared_b32(stg80 + j * 16, res[2 * j]);
        st_shared_b32(stg80 + 8 * 160 + j * 16, res[2 * j + 1]);
        sum0 += bf_lo(res[2 * j]) + bf_hi(res[2 * j]);
        sum1 += bf_lo(res[2 * j + 1]) + bf_hi(res[2 * j + 1]);
      }
      sum0 += __shfl_xor_sync(0xffffffffu, sum0, 1); sum1 += __shfl_xor_sync(0xffffffffu, sum1, 1);
      sum0 += __shfl_xor_sync(0xffffffffu, sum0, 2); sum1 += __shfl_xor_sync(0xffffffffu, sum1, 2);
      const float mu0 = sum0 * (1.0f / 80.0f), mu1 = sum1 * (1.0f / 80.0f);
      float q0 = 0.f, q1 = 0.f;
#pragma unroll
      for (int j = 0; j < 10; j++) {
        float d;
        d = bf_lo(res[2 * j]) - mu0; q0 = fmaf(d, d, q0);
        d = bf_hi(res[2 * j]) - mu0; q0 = fmaf(d, d, q0);
        d = bf_lo(res[2 * j + 1]) - mu1; q1 = fmaf(d, d, q1);
        d = bf_hi(res[2 * j + 1]) - mu1; q1 = fmaf(d, d, q1);
      }
      q0 += __shfl_xor_sync(0xffffffffu, q0, 1); q1 += __shfl_xor_sync(0xffffffffu, q1, 1);
      q0 += __shfl_xor_sync(0xffffffffu, q0, 2); q1 += __shfl_xor_sync(0xffffffffu, q1, 2);
      if (c4 == 0) {
        g_stats[row0 * 8 + j_blk] = make_float2(mu0, q0);
        g_stats[(row0 + 8) * 8 + j_blk] = make_float2(mu1, q1);
      }
      fence_proxy_async();
      named_bar_sync(1 + wg, 128);
      if (leader) {
        tma_store_2d(&tmHs, stg80_base, n0, m_blk * 128 + wg * 64);
        bulk_commit();
        bulk_wait_all();
        fence_proxy_async_all();
        flag_signal(&g_flag[16 + m_blk]);
      }
      TS(2, 5);
    }
    {
      pdl_wait();
      {
        float* cs_s = reinterpret_cast<float*>(smem_raw + (sbase - smem_u32(smem_raw)) + KC_CS);
        for (int i = tid; i < 384; i += 256) cs_s[i] = g_cs[(i >= 192 ? FF - 192 : 0) + j_blk * 192 + i];
        named_bar_sync(3, 256);
      }
      flag_wait(&g_flag[16 + m_blk], 16);
      float mb[2], iv[2];
#pragma unroll
      for (int h = 0; h < 2; h++) {
        const float4* sp = reinterpret_cast<const float4*>(g_stats + (row0 + 8 * h) * 8);
        const float4 p0 = sp[0], p1 = sp[1], p2 = sp[2], p3 = sp[3];
        const float mean = (((p0.x + p0.z) + (p1.x + p1.z)) + ((p2.x + p2.z) + (p3.x + p3.z))) * 0.125f;
        float m2 = ((p0.y + p0.w) + (p1.y + p1.w)) + ((p2.y + p2.w) + (p3.y + p3.w));
        float dd = 0.f, d;
        d = p0.x - mean; dd = fmaf(d, d, dd); d = p0.z - mean; dd = fmaf(d, d, dd);
        d = p1.x - mean; dd = fmaf(d, d, dd); d = p1.z - mean; dd = fmaf(d, d, dd);
        d = p2.x - mean; dd = fmaf(d, d, dd); d = p2.z - mean; dd = fmaf(d, d, dd);
        d = p3.x - mean; dd = fmaf(d, d, dd); d = p3.z - mean; dd = fmaf(d, d, dd);
        m2 = fmaf(dd, 80.0f, m2);
        const float var_b = bf16_round(m2 * (1.0f / DM));
        const float den = bf16_round(sqrtf(bf16_round(var_b + 1e-5f)));
        iv[h] = __frcp_rn(den);
        mb[h] = bf16_round(mean);
      }
      float accg[96], accu[96];
#pragma unroll
      for (int i = 0; i < 96; i++) { accg[i] = 0.f; accu[i] = 0.f; }
      TS(3, 3);
      if (wg == 0) glu_mainloop<0>(accg, accu, sbase, bar2, leader);
      else glu_mainloop<1>(accg, accu, sbase, bar2, leader);
      wgmma_wait<0>();
      fence_regs(accg); fence_regs(accu);
      release_stage(barD + 8, leader);
      TS(3, 4);
      const uint32_t stg = sbase + KC_STAGING + wg * 24576 + (wwarp * 16 + g) * 128 + c4 * 4;
      const float* csg = reinterpret_cast<const float*>(smem_raw + (sbase - smem_u32(smem_raw)) + KC_CS) + c4 * 2;
      const float nm0 = -mb[0] * iv[0], nm1 = -mb[1] * iv[1];
#pragma unroll
      for (int sl = 0; sl < 3; sl++) {
        float2 cgv[4], cuv[4];
#pragma unroll
        for (int jj = 0; jj < 8; jj++) {
          const int j = sl * 8 + jj;
          if ((jj & 3) == 0) {
#pragma unroll
            for (int q = 0; q < 4; q++) {
              cgv[q] = *reinterpret_cast<const float2*>(csg + (j + q) * 8);
              cuv[q] = *reinterpret_cast<const float2*>(csg + 192 + (j + q) * 8);
            }
          }
          const float2 cg = cgv[jj & 3], cu = cuv[jj & 3];
          const float r0 = fmaxf(fmaf(accg[4 * j], iv[0], nm0 * cg.x), 0.f) * fmaf(accu[4 * j], iv[0], nm0 * cu.x);
          const float r1 = fmaxf(fmaf(accg[4 * j + 1], iv[0], nm0 * cg.y), 0.f) * fmaf(accu[4 * j + 1], iv[0], nm0 * cu.y);
          const float r2 = fmaxf(fmaf(accg[4 * j + 2], iv[1], nm1 * cg.x), 0.f) * fmaf(accu[4 * j + 2], iv[1], nm1 * cu.x);
          const float r3 = fmaxf(fmaf(accg[4 * j + 3], iv[1], nm1 * cg.y), 0.f) * fmaf(accu[4 * j + 3], iv[1], nm1 * cu.y);
          const uint32_t a0 = stg + sl * 8192 + ((jj ^ g) << 4);
          st_shared_b32(a0, pack_bf16(r0, r1));
          st_shared_b32(a0 + 1024, pack_bf16(r2, r3));
        }
        fence_proxy_async();
        named_bar_sync(1 + wg, 128);
        if (leader) {
          tma_store_2d(&tmHHs, sbase + KC_STAGING + wg * 24576 + sl * 8192, j_blk * 192 + sl * 64, m_blk * 128 + wg * 64);
          bulk_commit();
        }
      }
      TS(3, 7);
      if (leader) {
        bulk_wait_all();
        TS(3, 8);
        fence_proxy_async_all();
        mbar_arrive(barD + 16);
        flag_signal(&g_flag[32 + m_blk * 8 + j_blk]);
      }
      TS(3, 9);
    }
    {
      uint32_t res[20];
#pragma unroll
      for (int j = 0; j < 10; j++) {
        res[2 * j] = *reinterpret_cast<const uint32_t*>(g_h + (size_t)row0 * DM + n0 + j * 8 + c4 * 2);
        res[2 * j + 1] = *reinterpret_cast<const uint32_t*>(g_h + (size_t)(row0 + 8) * DM + n0 + j * 8 + c4 * 2);
      }
      float acc0[32], acc1[8];
#pragma unroll
      for (int i = 0; i < 32; i++) acc0[i] = 0.f;
#pragma unroll
      for (int i = 0; i < 8; i++) acc1[i] = 0.f;
      mbar_wait(bar3, 0);
      TS(4, 3);
      if (wg == 0) res_mainloop<24, KC_NST3, 0>(acc0, acc1, sbase, bar3, leader);
      else res_mainloop<24, KC_NST3, 1>(acc0, acc1, sbase, bar3, leader);
      wgmma_wait<0>();
      fence_regs(acc0); fence_regs(acc1);
      TS(4, 4);
#pragma unroll
      for (int j = 0; j < 10; j++) {
        const uint32_t a01 = j < 8 ? pack_bf16(acc0[4 * j], acc0[4 * j + 1]) : pack_bf16(acc1[4 * (j - 8)], acc1[4 * (j - 8) + 1]);
        const uint32_t a23 = j < 8 ? pack_bf16(acc0[4 * j + 2], acc0[4 * j + 3]) : pack_bf16(acc1[4 * (j - 8) + 2], acc1[4 * (j - 8) + 3]);
        st_shared_b32(stg80 + j * 16, pack_bf16(bf_lo(res[2 * j]) + bf_lo(a01), bf_hi(res[2 * j]) + bf_hi(a01)));
        st_shared_b32(stg80 + 8 * 160 + j * 16, pack_bf16(bf_lo(res[2 * j + 1]) + bf_lo(a23), bf_hi(res[2 * j + 1]) + bf_hi(a23)));
      }
      fence_proxy_async();
      named_bar_sync(1 + wg, 128);
      if (leader) {
        tma_store_2d(&tmOut, stg80_base, n0, m_blk * 128 + wg * 64);
        bulk_commit();
        bulk_wait_read();
      }
      TS(4, 5);
    }
  }
  __syncwarp();
  cluster_sync_relaxed();
  TS(4, 6);
}

constexpr int AT_THREADS = 512;
constexpr int AT_WGS = AT_THREADS / 128;
constexpr int AT_KV_BYTES = IMG_HEAD_ELEMS * 2;
constexpr int AT_SMEM = 2 * AT_KV_BYTES + 256 + 1024;
constexpr int AT_CHUNKS = 8;

__device__ __forceinline__ float exp2_poly(float x) {
  const float u = __saturatef(fmaf(x, 1.0f / 64.0f, 62.0f / 64.0f));
  const float MAGIC = 12582912.0f - 62.0f;
  const float r = fmaf(u, 64.0f, MAGIC);
  const float q = MAGIC - r;
  const float fr = fmaf(u, 64.0f, q);
  float p = fmaf(fr, 0.009570102207362652f, 0.05591785907745361f);
  p = fmaf(p, fr, 0.240247443318367f);
  p = fmaf(p, fr, 0.6931217908859253f);
  p = fmaf(p, fr, 0.9999992847442627f);
  return __uint_as_float(__float_as_uint(p) + (__float_as_uint(r) << 23));
}
__device__ __forceinline__ bool use_poly(int e) { return (e & 7) == 1; }

struct AttnState {
  uint32_t qa0, qa1, qa2, qa3, qa4, qa5;
  float M0, M1;
};

__device__ __forceinline__ bool attn_exp_fast(const float (&s)[32], uint32_t (&p)[16]) {
#pragma unroll
  for (int j = 0; j < 16; j++) {
    const float e0 = use_poly(2 * j) ? exp2_poly(s[2 * j]) : ex2(s[2 * j]);
    const float e1 = use_poly(2 * j + 1) ? exp2_poly(s[2 * j + 1]) : ex2(s[2 * j + 1]);
    p[j] = pack_bf16(e0, e1);
  }
  uint32_t acc_or = 0;
#pragma unroll
  for (int j = 0; j < 16; j++) acc_or |= p[j];
  return __any_sync(0xffffffffu, (acc_or & 0x40004000u) != 0);
}
__device__ __forceinline__ void attn_exp_exact(const float (&s)[32], uint32_t (&p)[16], float (&o)[12], AttnState& st, bool first, int c4) {
  float mx0 = fmaxf(s[0], s[1]), mx1 = fmaxf(s[2], s[3]);
#pragma unroll
  for (int j = 1; j < 8; j++) {
    mx0 = fmaxf(mx0, fmaxf(s[4 * j], s[4 * j + 1]));
    mx1 = fmaxf(mx1, fmaxf(s[4 * j + 2], s[4 * j + 3]));
  }
  mx0 = fmaxf(mx0, __shfl_xor_sync(0xffffffffu, mx0, 1));
  mx1 = fmaxf(mx1, __shfl_xor_sync(0xffffffffu, mx1, 1));
  mx0 = fmaxf(mx0, __shfl_xor_sync(0xffffffffu, mx0, 2));
  mx1 = fmaxf(mx1, __shfl_xor_sync(0xffffffffu, mx1, 2));
  float d0 = mx0 + 7.0f, d1 = mx1 + 7.0f;
  if (!first) { d0 = fmaxf(d0, 0.f); d1 = fmaxf(d1, 0.f); }
  const float T0 = st.M0 + d0, T1 = st.M1 + d1;
  const float h0 = bf16_round(T0), h1 = bf16_round(T1);
  const float i0 = bf16_round(T0 - h0), i1 = bf16_round(T1 - h1);
  const float l0 = bf16_round((T0 - h0) - i0), l1 = bf16_round((T1 - h1) - i1);
  const float N0 = (h0 + i0) + l0, N1 = (h1 + i1) + l1;
  d0 = N0 - st.M0; d1 = N1 - st.M1;
  st.M0 = N0; st.M1 = N1;
  if (c4 == 2) { st.qa4 = pack_bf16(-h0, -i0); st.qa5 = pack_bf16(-h1, -i1); }
  if (c4 == 3) { st.qa4 = pack_bf16(-l0, 0.f); st.qa5 = pack_bf16(-l1, 0.f); }
  if (!first) {
    const float al0 = ex2(-d0), al1 = ex2(-d1);
#pragma unroll
    for (int j = 0; j < 3; j++) {
      o[4 * j] *= al0; o[4 * j + 1] *= al0;
      o[4 * j + 2] *= al1; o[4 * j + 3] *= al1;
    }
  }
#pragma unroll
  for (int j = 0; j < 8; j++) {
    p[2 * j] = pack_bf16(ex2(s[4 * j] - d0), ex2(s[4 * j + 1] - d0));
    p[2 * j + 1] = pack_bf16(ex2(s[4 * j + 2] - d1), ex2(s[4 * j + 3] - d1));
  }
}
__device__ __forceinline__ void attn_step(float (&s)[32], const uint32_t (&pp)[16], uint32_t (&pn)[16], float (&o)[12], AttnState& st,
                                          uint32_t k_addr, uint32_t v_addr_prev, int keep, int c4, int wgdbg = 0, int tdbg = 0) {
  PH(wgdbg, tdbg, 0);
  const uint64_t dk = make_desc(k_addr, 128, 384, 0);
  const uint64_t dv_prev = make_desc(v_addr_prev, 384, 128, 0);
  wgmma_fence();
  wgmma_rs_n64(s, st.qa0, st.qa1, st.qa2, st.qa3, dk, 0);
  wgmma_rs_n64(s, st.qa4, st.qa5, 0u, 0u, dk + 16, 1);
  wgmma_commit();
#pragma unroll
  for (int kk = 0; kk < 4; kk++) wgmma_rs_n24_tb(o, pp[4 * kk], pp[4 * kk + 1], pp[4 * kk + 2], pp[4 * kk + 3], dv_prev + kk * 48, kk == 0 ? keep : 1);
  wgmma_commit();
  wgmma_wait<1>();
  fence_regs(s);
  PH(wgdbg, tdbg, 1);
  const bool redo = attn_exp_fast(s, pn);
  PH(wgdbg, tdbg, 2);
  wgmma_wait<0>();
  fence_regs(o);
  if (redo) attn_exp_exact(s, pn, o, st, false, c4);
}

__global__ void __launch_bounds__(AT_THREADS, 1) attn_kernel(const bf16* __restrict__ wo, const bf16* __restrict__ wgt, const bf16* __restrict__ wup, const bf16* __restrict__ wdn) {
  extern __shared__ uint8_t smem_raw[];
  const uint32_t sbase = (smem_u32(smem_raw) + 1023u) & ~1023u;
  const uint32_t sK = sbase, sV = sbase + AT_KV_BYTES;
  const uint32_t sBar = sV + AT_KV_BYTES;
  const int tid = threadIdx.x, warp = tid >> 5, lane = tid & 31;
  const int head = blockIdx.x >> 2, quarter = blockIdx.x & 3;
  if (blockIdx.x >= 128) {
    pdl_launch();
    const int b = blockIdx.x - 128;
    const bf16* w = (b >> 1) ? wup : wgt;
    const int cgrp = tid % 96, rgrp = tid / 96;
    float acc[8];
#pragma unroll
    for (int i = 0; i < 8; i++) acc[i] = 0.f;
    float* red = reinterpret_cast<float*>(smem_raw);
    if (rgrp < 5) {
      const uint4* src = reinterpret_cast<const uint4*>(w + (size_t)(rgrp * 128) * FF + (b & 1) * 768 + cgrp * 8);
#pragma unroll 8
      for (int r = 0; r < 128; r++) {
        const uint4 v = __ldg(src + (size_t)r * (FF / 8));
        acc[0] += bf_lo(v.x); acc[1] += bf_hi(v.x); acc[2] += bf_lo(v.y); acc[3] += bf_hi(v.y);
        acc[4] += bf_lo(v.z); acc[5] += bf_hi(v.z); acc[6] += bf_lo(v.w); acc[7] += bf_hi(v.w);
      }
#pragma unroll
      for (int i = 0; i < 8; i++) red[rgrp * 768 + cgrp * 8 + i] = acc[i];
    }
    __syncthreads();
    pdl_wait();
    for (int c = tid; c < 768; c += AT_THREADS)
      g_cs[(b >> 1) * FF + (b & 1) * 768 + c] = ((red[c] + red[768 + c]) + (red[1536 + c] + red[2304 + c])) + red[3072 + c];
    if (b == 0 && tid < 16) g_flag[tid] = 0;
    return;
  }
  TS(1, 0);
  if (tid == 0) {
    for (int i = 0; i < AT_CHUNKS; i++) mbar_init(sBar + 8 * i, 1);
    fence_mbar_init();
  }
  pdl_launch();
  if (tid == 32) {
    prefetch_l2(reinterpret_cast<const uint8_t*>(wo) + blockIdx.x * 6400, 6400);
    prefetch_l2(reinterpret_cast<const uint8_t*>(wgt) + blockIdx.x * 15360, 15360);
    prefetch_l2(reinterpret_cast<const uint8_t*>(wup) + blockIdx.x * 15360, 15360);
    prefetch_l2(reinterpret_cast<const uint8_t*>(wdn) + blockIdx.x * 15360, 15360);
  }
  __syncthreads();
  TS(1, 1);
  pdl_wait();
  TS(1, 2);
  if (tid == 0) {
    const uint8_t* kg = reinterpret_cast<const uint8_t*>(g_img + (size_t)(32 + head) * IMG_HEAD_ELEMS);
    const uint8_t* vg = reinterpret_cast<const uint8_t*>(g_img + (size_t)(64 + head) * IMG_HEAD_ELEMS);
    constexpr int CB = AT_KV_BYTES / AT_CHUNKS;
    for (int i = 0; i < AT_CHUNKS; i++) {
      mbar_expect_tx(sBar + 8 * i, 2 * CB);
      bulk_g2s(sK + i * CB, kg + i * CB, CB, sBar + 8 * i);
      bulk_g2s(sV + i * CB, vg + i * CB, CB, sBar + 8 * i);
    }
  }
  const int wg = warp >> 2, wwarp = warp & 3;
  const int g = lane >> 2, c4 = lane & 3;
  const uint64_t dk_base = make_desc(sK, 128, 384, 0);
  const uint64_t dv_base = make_desc(sV, 384, 128, 0);

  uint32_t qn[6];
  {
    const bf16* q0 = g_img + (size_t)head * IMG_HEAD_ELEMS + (size_t)((quarter * 512 + wg * 64 + wwarp * 16) >> 3) * 192 + g * 8 + c4 * 2;
    qn[0] = *reinterpret_cast<const uint32_t*>(q0);
    qn[1] = *reinterpret_cast<const uint32_t*>(q0 + 192);
    qn[2] = *reinterpret_cast<const uint32_t*>(q0 + 64);
    qn[3] = *reinterpret_cast<const uint32_t*>(q0 + 192 + 64);
    qn[4] = *reinterpret_cast<const uint32_t*>(q0 + 128);
    qn[5] = *reinterpret_cast<const uint32_t*>(q0 + 192 + 128);
  }
#pragma unroll 1
  for (int rep = 0; rep < 8 / AT_WGS; rep++) {
    const int row0 = quarter * 512 + (rep * AT_WGS + wg) * 64 + wwarp * 16 + g;
    AttnState st;
    st.qa0 = qn[0]; st.qa1 = qn[1]; st.qa2 = qn[2]; st.qa3 = qn[3]; st.qa4 = qn[4]; st.qa5 = qn[5];
    if (rep + 1 < 8 / AT_WGS) {
      const bf16* q0 = g_img + (size_t)head * IMG_HEAD_ELEMS + (size_t)((row0 + AT_WGS * 64) >> 3) * 192 + g * 8 + c4 * 2;
      qn[0] = *reinterpret_cast<const uint32_t*>(q0);
      qn[1] = *reinterpret_cast<const uint32_t*>(q0 + 192);
      qn[2] = *reinterpret_cast<const uint32_t*>(q0 + 64);
      qn[3] = *reinterpret_cast<const uint32_t*>(q0 + 192 + 64);
      qn[4] = *reinterpret_cast<const uint32_t*>(q0 + 128);
      qn[5] = *reinterpret_cast<const uint32_t*>(q0 + 192 + 128);
    }
    float o[12];
    float s[32];
    uint32_t pa[16], pb[16];
    st.M0 = st.M1 = 0.f;
    if (rep == 0) mbar_wait(sBar, 0);
    wgmma_fence();
    wgmma_rs_n64(s, st.qa0, st.qa1, st.qa2, st.qa3, dk_base, 0);
    wgmma_rs_n64(s, st.qa4, st.qa5, 0u, 0u, dk_base + 16, 1);
    wgmma_commit();
    wgmma_wait<0>();
    fence_regs(s);
    attn_exp_exact(s, pa, o, st, true, c4);
    attn_step(s, pa, pb, o, st, sK + 3072, sV, 0, c4);
#pragma unroll 1
    for (int tt = 1; tt < 16; tt++) {
      if (rep == 0 && !(tt & 1)) mbar_wait(sBar + 8 * (tt >> 1), 0);
      attn_step(s, pb, pa, o, st, sK + tt * 6144, sV + tt * 6144 - 3072, 1, c4, wg, rep * 32 + tt * 2);
      attn_step(s, pa, pb, o, st, sK + tt * 6144 + 3072, sV + tt * 6144, 1, c4, wg, rep * 32 + tt * 2 + 1);
    }
    wgmma_fence();
#pragma unroll
    for (int kk = 0; kk < 4; kk++) wgmma_rs_n24_tb(o, pb[4 * kk], pb[4 * kk + 1], pb[4 * kk + 2], pb[4 * kk + 3], dv_base + 31 * 192 + kk * 48, 1);
    wgmma_commit();
    wgmma_wait<0>();
    fence_regs(o);
    TS(1, 3 + rep);
    const float l0 = __shfl_sync(0xffffffffu, o[8], (lane & ~3) | 2);
    const float l1 = __shfl_sync(0xffffffffu, o[10], (lane & ~3) | 2);
    const float i0 = 1.0f / l0, i1 = 1.0f / l1;
    bf16* o0 = g_o + (size_t)row0 * DM + head * DH;
    bf16* o1 = o0 + 8 * DM;
#pragma unroll
    for (int j = 0; j < 3; j++) {
      if (j < 2 || c4 < 2) {
        *reinterpret_cast<uint32_t*>(o0 + j * 8 + c4 * 2) = pack_bf16(o[4 * j] * i0, o[4 * j + 1] * i0);
        *reinterpret_cast<uint32_t*>(o1 + j * 8 + c4 * 2) = pack_bf16(o[4 * j + 2] * i1, o[4 * j + 3] * i1);
      }
    }
  }
}

typedef CUresult (*EncodeTiledFn)(CUtensorMap*, CUtensorMapDataType, cuuint32_t, void*, const cuuint64_t*, const cuuint64_t*,
                                  const cuuint32_t*, const cuuint32_t*, CUtensorMapInterleave, CUtensorMapSwizzle,
                                  CUtensorMapL2promotion, CUtensorMapFloatOOBfill);

static void make_map(EncodeTiledFn fn, CUtensorMap* tm, const void* ptr, uint64_t rows, uint64_t cols, uint32_t box_rows,
                     uint32_t box_cols, CUtensorMapSwizzle sw) {
  cuuint64_t dims[2] = {cols, rows};
  cuuint64_t strides[1] = {cols * 2};
  cuuint32_t box[2] = {box_cols, box_rows};
  cuuint32_t es[2] = {1, 1};
  fn(tm, CU_TENSOR_MAP_DATA_TYPE_BFLOAT16, 2, const_cast<void*>(ptr), dims, strides, box, es, CU_TENSOR_MAP_INTERLEAVE_NONE, sw,
     CU_TENSOR_MAP_L2_PROMOTION_L2_256B, CU_TENSOR_MAP_FLOAT_OOB_FILL_NONE);
}

template <typename... KArgs, typename... Args>
static void launch(void (*kern)(KArgs...), int grid, int block, int smem, int cluster, bool pdl, Args... args) {
  cudaLaunchConfig_t cfg = {};
  cfg.gridDim = dim3(grid);
  cfg.blockDim = dim3(block);
  cfg.dynamicSmemBytes = smem;
  cfg.stream = cudaStreamPerThread;
  cudaLaunchAttribute at[2];
  int n = 0;
  if (cluster > 1) {
    at[n].id = cudaLaunchAttributeClusterDimension;
    at[n].val.clusterDim.x = cluster; at[n].val.clusterDim.y = 1; at[n].val.clusterDim.z = 1;
    n++;
  }
  if (pdl) {
    at[n].id = cudaLaunchAttributeProgrammaticStreamSerialization;
    at[n].val.programmaticStreamSerializationAllowed = 1;
    n++;
  }
  cfg.attrs = at;
  cfg.numAttrs = n;
  cudaLaunchKernelEx(&cfg, kern, KArgs(args)...);
}

extern "C" void kernel_launch(void* const* d_in, const int* in_sizes, int n_in, void* d_out, int out_size) {
  const bf16* x = (const bf16*)d_in[0];
  const bf16* wqkv = (const bf16*)d_in[1];
  const bf16* wo = (const bf16*)d_in[2];
  const bf16* wg = (const bf16*)d_in[4];
  const bf16* wu = (const bf16*)d_in[5];
  const bf16* wd = (const bf16*)d_in[6];
  bf16* out = (bf16*)d_out;

  static EncodeTiledFn enc = nullptr;
  static void *p_o = nullptr, *p_h = nullptr, *p_hh = nullptr, *p_xn = nullptr;
  if (!enc) {
    void* fn = nullptr;
    cudaDriverEntryPointQueryResult qr;
    cudaGetDriverEntryPoint("cuTensorMapEncodeTiled", &fn, cudaEnableDefault, &qr);
    enc = (EncodeTiledFn)fn;
    cudaGetSymbolAddress(&p_o, g_o);
    cudaGetSymbolAddress(&p_h, g_h);
    cudaGetSymbolAddress(&p_hh, g_hh);
    cudaGetSymbolAddress(&p_xn, g_xn);
    cudaFuncSetAttribute(qkv_kernel, cudaFuncAttributeMaxDynamicSharedMemorySize, KA_SMEM);
    cudaFuncSetAttribute(mlp_kernel, cudaFuncAttributeMaxDynamicSharedMemorySize, KC_SMEM);
    cudaFuncSetAttribute(attn_kernel, cudaFuncAttributeMaxDynamicSharedMemorySize, AT_SMEM);
  }
  CUtensorMap tm_wqkv, tm_wg, tm_wu, tm_wo64, tm_wo16, tm_wd64, tm_wd16, tm_o, tm_h, tm_hh, tm_hhs, tm_xn, tm_hs, tm_out;
  make_map(enc, &tm_wqkv, wqkv, DM, 3 * DM, 32, 64, CU_TENSOR_MAP_SWIZZLE_128B);
  make_map(enc, &tm_wg, wg, DM, FF, 32, 64, CU_TENSOR_MAP_SWIZZLE_128B);
  make_map(enc, &tm_wu, wu, DM, FF, 32, 64, CU_TENSOR_MAP_SWIZZLE_128B);
  make_map(enc, &tm_wo64, wo, DM, DM, 32, 64, CU_TENSOR_MAP_SWIZZLE_128B);
  make_map(enc, &tm_wo16, wo, DM, DM, 32, 16, CU_TENSOR_MAP_SWIZZLE_32B);
  make_map(enc, &tm_wd64, wd, FF, DM, 32, 64, CU_TENSOR_MAP_SWIZZLE_128B);
  make_map(enc, &tm_wd16, wd, FF, DM, 32, 16, CU_TENSOR_MAP_SWIZZLE_32B);
  make_map(enc, &tm_o, p_o, SEQ, DM, 128, 64, CU_TENSOR_MAP_SWIZZLE_128B);
  make_map(enc, &tm_h, p_h, SEQ, DM, 128, 32, CU_TENSOR_MAP_SWIZZLE_64B);
  make_map(enc, &tm_hh, p_hh, SEQ, FF, 128, 64, CU_TENSOR_MAP_SWIZZLE_128B);
  make_map(enc, &tm_hhs, p_hh, SEQ, FF, 64, 64, CU_TENSOR_MAP_SWIZZLE_128B);
  make_map(enc, &tm_xn, p_xn, SEQ, DM, 128, 32, CU_TENSOR_MAP_SWIZZLE_64B);
  make_map(enc, &tm_hs, p_h, SEQ, DM, 64, 80, CU_TENSOR_MAP_SWIZZLE_NONE);
  make_map(enc, &tm_out, out, SEQ, DM, 64, 80, CU_TENSOR_MAP_SWIZZLE_NONE);

  launch(qkv_kernel, 128, GT, KA_SMEM, 2, false, tm_xn, tm_wqkv, x);
  launch(attn_kernel, 132, AT_THREADS, AT_SMEM, 1, true, wo, wg, wu, wd);
  launch(mlp_kernel, 128, GT, KC_SMEM, 2, true, tm_o, tm_wo64, tm_wo16, tm_h, tm_wg, tm_wu, tm_hhs, tm_hh, tm_wd64, tm_wd16, tm_hs, tm_out, x);
}
```

```cpp
#include <cuda_runtime.h>
#include <cuda_bf16.h>
#include <cuda.h>
#include <stdint.h>

typedef __nv_bfloat16 bf16;

constexpr int SEQ = 2048, DM = 640, NH = 32, DH = 20, FF = 1536;
constexpr float ATT_SCALE_LOG2E = 0.22360679774997896f * 1.4426950408889634f;
constexpr int IMG_HEAD_ELEMS = (SEQ / 8) * 192;

__device__ __align__(1024) bf16 g_img[3 * NH * IMG_HEAD_ELEMS];
__device__ __align__(1024) bf16 g_o[SEQ * DM];
__device__ __align__(1024) bf16 g_h[SEQ * DM];
__device__ __align__(1024) bf16 g_xn[SEQ * DM];
__device__ float2 g_stats[SEQ * 8];
__device__ float g_cs[2 * FF];
__device__ int g_flag[3 * 16];
__device__ __align__(1024) bf16 g_hh[SEQ * FF];

#define TS(k, i)
#define PH(w, t, i)
__device__ __forceinline__ uint32_t smem_u32(const void* p) { return (uint32_t)__cvta_generic_to_shared(p); }
__device__ __forceinline__ void mbar_init(uint32_t bar, uint32_t cnt) {
  asm volatile("mbarrier.init.shared::cta.b64 [%0], %1;" ::"r"(bar), "r"(cnt) : "memory");
}
__device__ __forceinline__ void mbar_expect_tx(uint32_t bar, uint32_t bytes) {
  asm volatile("mbarrier.arrive.expect_tx.shared::cta.b64 _, [%0], %1;" ::"r"(bar), "r"(bytes) : "memory");
}
__device__ __forceinline__ void mbar_arrive(uint32_t bar) {
  asm volatile("mbarrier.arrive.shared::cta.b64 _, [%0];" ::"r"(bar) : "memory");
}
__device__ __forceinline__ void mbar_arrive_cluster(uint32_t bar, uint32_t cta) {
  asm volatile(
      "{\n.reg .b32 r;\nmapa.shared::cluster.u32 r, %0, %1;\n"
      "mbarrier.arrive.shared::cluster.b64 _, [r];\n}\n" ::"r"(bar), "r"(cta)
      : "memory");
}
__device__ __forceinline__ void mbar_wait(uint32_t bar, uint32_t parity) {
  asm volatile(
      "{\n.reg .pred p;\nLAB_WAIT:\n"
      "mbarrier.try_wait.parity.shared::cta.b64 p, [%0], %1;\n"
      "@p bra DONE;\nbra LAB_WAIT;\nDONE:\n}\n" ::"r"(bar), "r"(parity)
      : "memory");
}
__device__ __forceinline__ void mbar_wait_cluster(uint32_t bar, uint32_t parity) {
  asm volatile(
      "{\n.reg .pred p;\nLAB_WAIT:\n"
      "mbarrier.try_wait.parity.acquire.cluster.shared::cta.b64 p, [%0], %1;\n"
      "@p bra DONE;\nbra LAB_WAIT;\nDONE:\n}\n" ::"r"(bar), "r"(parity)
      : "memory");
}
__device__ __forceinline__ void fence_mbar_init() { asm volatile("fence.mbarrier_init.release.cluster;" ::: "memory"); }
__device__ __forceinline__ void fence_proxy_async() { asm volatile("fence.proxy.async.shared::cta;" ::: "memory"); }
__device__ __forceinline__ void cluster_sync_all() {
  asm volatile("barrier.cluster.arrive.release.aligned;\nbarrier.cluster.wait.acquire.aligned;" ::: "memory");
}
__device__ __forceinline__ void cluster_sync_relaxed() {
  asm volatile("barrier.cluster.arrive.relaxed.aligned;\nbarrier.cluster.wait.aligned;" ::: "memory");
}
__device__ __forceinline__ void named_bar_sync(int id, int n) { asm volatile("bar.sync %0, %1;" ::"r"(id), "r"(n) : "memory"); }
__device__ __forceinline__ bool wg_any(bool pred, int id) {
  uint32_t r;
  asm volatile("{\n.reg .pred p, q;\nsetp.ne.u32 p, %1, 0;\nbar.red.or.pred q, %2, 128, p;\nselp.u32 %0, 1, 0, q;\n}\n" : "=r"(r) : "r"((uint32_t)pred), "r"(id) : "memory");
  return r != 0;
}
__device__ __forceinline__ void fence_proxy_async_all() { asm volatile("fence.proxy.async;" ::: "memory"); }
__device__ __forceinline__ void flag_signal(int* f) {
  __threadfence();
  atomicAdd(f, 1);
}
__device__ __forceinline__ void flag_wait(const int* f, int target) {
  int v;
  unsigned spins = 0;
  do {
    asm volatile("ld.acquire.gpu.global.s32 %0, [%1];" : "=r"(v) : "l"(f) : "memory");
    if (++spins > (1u << 24)) __trap();
  } while (v < target);
}
__device__ __forceinline__ void pdl_launch() { asm volatile("griddepcontrol.launch_dependents;" ::: "memory"); }
__device__ __forceinline__ void pdl_wait() { asm volatile("griddepcontrol.wait;" ::: "memory"); }

__device__ __forceinline__ void tma_load_2d(uint32_t dst, const CUtensorMap* tm, int c0, int c1, uint32_t bar) {
  asm volatile(
      "cp.async.bulk.tensor.2d.shared::cluster.global.mbarrier::complete_tx::bytes [%0], [%1, {%3, %4}], [%2];" ::"r"(dst),
      "l"((uint64_t)tm), "r"(bar), "r"(c0), "r"(c1)
      : "memory");
}
__device__ __forceinline__ void tma_load_2d_mc(uint32_t dst, const CUtensorMap* tm, int c0, int c1, uint32_t bar, uint16_t mask) {
  asm volatile(
      "cp.async.bulk.tensor.2d.shared::cluster.global.mbarrier::complete_tx::bytes.multicast::cluster [%0], [%1, {%3, %4}], [%2], %5;" ::"r"(dst),
      "l"((uint64_t)tm), "r"(bar), "r"(c0), "r"(c1), "h"(mask)
      : "memory");
}
__device__ __forceinline__ void bulk_g2s(uint32_t dst, const void* src, uint32_t bytes, uint32_t bar) {
  asm volatile("cp.async.bulk.shared::cluster.global.mbarrier::complete_tx::bytes [%0], [%1], %2, [%3];" ::"r"(dst), "l"(src),
               "r"(bytes), "r"(bar)
               : "memory");
}
__device__ __forceinline__ void bulk_s2g(void* dst, uint32_t src, uint32_t bytes) {
  asm volatile("cp.async.bulk.global.shared::cta.bulk_group [%0], [%1], %2;" ::"l"(dst), "r"(src), "r"(bytes) : "memory");
}
__device__ __forceinline__ void tma_store_2d(const CUtensorMap* tm, uint32_t src, int c0, int c1) {
  asm volatile("cp.async.bulk.tensor.2d.global.shared::cta.bulk_group [%0, {%2, %3}], [%1];" ::"l"((uint64_t)tm), "r"(src), "r"(c0), "r"(c1) : "memory");
}
__device__ __forceinline__ void bulk_commit() { asm volatile("cp.async.bulk.commit_group;" ::: "memory"); }
__device__ __forceinline__ void bulk_wait_read() { asm volatile("cp.async.bulk.wait_group.read 0;" ::: "memory"); }
__device__ __forceinline__ void prefetch_l2(const void* p, uint32_t bytes) {
  asm volatile("cp.async.bulk.prefetch.L2.global [%0], %1;" ::"l"(p), "r"(bytes) : "memory");
}
__device__ __forceinline__ void bulk_wait_all() { asm volatile("cp.async.bulk.wait_group 0;" ::: "memory"); }
__device__ __forceinline__ void st_shared_b32(uint32_t addr, uint32_t v) { asm volatile("st.shared.b32 [%0], %1;" ::"r"(addr), "r"(v) : "memory"); }
__device__ __forceinline__ void st_shared_v2(uint32_t addr, uint32_t a, uint32_t b) { asm volatile("st.shared.v2.b32 [%0], {%1, %2};" ::"r"(addr), "r"(a), "r"(b) : "memory"); }
__device__ __forceinline__ void prefetch_tmap(const CUtensorMap* tm) {
  asm volatile("prefetch.tensormap [%0];" ::"l"((uint64_t)tm) : "memory");
}
__device__ __forceinline__ void wgmma_fence() { asm volatile("wgmma.fence.sync.aligned;" ::: "memory"); }
__device__ __forceinline__ void wgmma_commit() { asm volatile("wgmma.commit_group.sync.aligned;" ::: "memory"); }
template <int N>
__device__ __forceinline__ void wgmma_wait() { asm volatile("wgmma.wait_group.sync.aligned %0;" ::"n"(N) : "memory"); }

template <int N>
__device__ __forceinline__ void fence_regs(float (&r)[N]) {
#pragma unroll
  for (int i = 0; i < N; i++) asm volatile("" : "+f"(r[i])::"memory");
}
template <int N>
__device__ __forceinline__ void fence_regs(uint32_t (&r)[N]) {
#pragma unroll
  for (int i = 0; i < N; i++) asm volatile("" : "+r"(r[i])::"memory");
}
__device__ __forceinline__ uint64_t make_desc(uint32_t addr, uint32_t lbo, uint32_t sbo, uint32_t layout) {
  return (uint64_t)((addr & 0x3FFFF) >> 4) | ((uint64_t)((lbo & 0x3FFFF) >> 4) << 16) | ((uint64_t)((sbo & 0x3FFFF) >> 4) << 32) |
         ((uint64_t)layout << 62);
}
__device__ __forceinline__ uint32_t pack_bf16(float lo, float hi) {
  uint32_t r;
  asm("cvt.rn.bf16x2.f32 %0, %1, %2;" : "=r"(r) : "f"(hi), "f"(lo));
  return r;
}
__device__ __forceinline__ float bf16_round(float x) { return __bfloat162float(__float2bfloat16_rn(x)); }
__device__ __forceinline__ float bf_lo(uint32_t u) { return __uint_as_float(u << 16); }
__device__ __forceinline__ float bf_hi(uint32_t u) { return __uint_as_float(u & 0xffff0000u); }
__device__ __forceinline__ float ex2(float x) {
  float y;
  asm("ex2.approx.ftz.f32 %0, %1;" : "=f"(y) : "f"(x));
  return y;
}

__device__ __forceinline__ void wgmma_ss_n240_tb(float (&d)[120], uint64_t descA, uint64_t descB, int scaleD) {
  asm volatile("{\n.reg .pred p;\nsetp.ne.b32 p, %122, 0;\n"
    "wgmma.mma_async.sync.aligned.m64n240k16.f32.bf16.bf16 {%0, %1, %2, %3, %4, %5, %6, %7, %8, %9, %10, %11, %12, %13, %14, %15, %16, %17, %18, %19, %20, %21, %22, %23, %24, %25, %26, %27, %28, %29, %30, %31, %32, %33, %34, %35, %36, %37, %38, %39, %40, %41, %42, %43, %44, %45, %46, %47, %48, %49, %50, %51, %52, %53, %54, %55, %56, %57, %58, %59, %60, %61, %62, %63, %64, %65, %66, %67, %68, %69, %70, %71, %72, %73, %74, %75, %76, %77, %78, %79, %80, %81, %82, %83, %84, %85, %86, %87, %88, %89, %90, %91, %92, %93, %94, %95, %96, %97, %98, %99, %100, %101, %102, %103, %104, %105, %106, %107, %108, %109, %110, %111, %112, %113, %114, %115, %116, %117, %118, %119}, %120, %121, p, 1, 1, 0, 1;\n}\n"
    : "+f"(d[0]), "+f"(d[1]), "+f"(d[2]), "+f"(d[3]), "+f"(d[4]), "+f"(d[5]), "+f"(d[6]), "+f"(d[7]), "+f"(d[8]), "+f"(d[9]), "+f"(d[10]), "+f"(d[11]), "+f"(d[12]), "+f"(d[13]), "+f"(d[14]), "+f"(d[15]), "+f"(d[16]), "+f"(d[17]), "+f"(d[18]), "+f"(d[19]), "+f"(d[20]), "+f"(d[21]), "+f"(d[22]), "+f"(d[23]), "+f"(d[24]), "+f"(d[25]), "+f"(d[26]), "+f"(d[27]), "+f"(d[28]), "+f"(d[29]), "+f"(d[30]), "+f"(d[31]), "+f"(d[32]), "+f"(d[33]), "+f"(d[34]), "+f"(d[35]), "+f"(d[36]), "+f"(d[37]), "+f"(d[38]), "+f"(d[39]), "+f"(d[40]), "+f"(d[41]), "+f"(d[42]), "+f"(d[43]), "+f"(d[44]), "+f"(d[45]), "+f"(d[46]), "+f"(d[47]), "+f"(d[48]), "+f"(d[49]), "+f"(d[50]), "+f"(d[51]), "+f"(d[52]), "+f"(d[53]), "+f"(d[54]), "+f"(d[55]), "+f"(d[56]), "+f"(d[57]), "+f"(d[58]), "+f"(d[59]), "+f"(d[60]), "+f"(d[61]), "+f"(d[62]), "+f"(d[63]), "+f"(d[64]), "+f"(d[65]), "+f"(d[66]), "+f"(d[67]), "+f"(d[68]), "+f"(d[69]), "+f"(d[70]), "+f"(d[71]), "+f"(d[72]), "+f"(d[73]), "+f"(d[74]), "+f"(d[75]), "+f"(d[76]), "+f"(d[77]), "+f"(d[78]), "+f"(d[79]), "+f"(d[80]), "+f"(d[81]), "+f"(d[82]), "+f"(d[83]), "+f"(d[84]), "+f"(d[85]), "+f"(d[86]), "+f"(d[87]), "+f"(d[88]), "+f"(d[89]), "+f"(d[90]), "+f"(d[91]), "+f"(d[92]), "+f"(d[93]), "+f"(d[94]), "+f"(d[95]), "+f"(d[96]), "+f"(d[97]), "+f"(d[98]), "+f"(d[99]), "+f"(d[100]), "+f"(d[101]), "+f"(d[102]), "+f"(d[103]), "+f"(d[104]), "+f"(d[105]), "+f"(d[106]), "+f"(d[107]), "+f"(d[108]), "+f"(d[109]), "+f"(d[110]), "+f"(d[111]), "+f"(d[112]), "+f"(d[113]), "+f"(d[114]), "+f"(d[115]), "+f"(d[116]), "+f"(d[117]), "+f"(d[118]), "+f"(d[119])
    : "l"(descA), "l"(descB), "r"(scaleD));
}
__device__ __forceinline__ void wgmma_ss_n192_tb(float (&d)[96], uint64_t descA, uint64_t descB, int scaleD) {
  asm volatile("{\n.reg .pred p;\nsetp.ne.b32 p, %98, 0;\n"
    "wgmma.mma_async.sync.aligned.m64n192k16.f32.bf16.bf16 {%0, %1, %2, %3, %4, %5, %6, %7, %8, %9, %10, %11, %12, %13, %14, %15, %16, %17, %18, %19, %20, %21, %22, %23, %24, %25, %26, %27, %28, %29, %30, %31, %32, %33, %34, %35, %36, %37, %38, %39, %40, %41, %42, %43, %44, %45, %46, %47, %48, %49, %50, %51, %52, %53, %54, %55, %56, %57, %58, %59, %60, %61, %62, %63, %64, %65, %66, %67, %68, %69, %70, %71, %72, %73, %74, %75, %76, %77, %78, %79, %80, %81, %82, %83, %84, %85, %86, %87, %88, %89, %90, %91, %92, %93, %94, %95}, %96, %97, p, 1, 1, 0, 1;\n}\n"
    : "+f"(d[0]), "+f"(d[1]), "+f"(d[2]), "+f"(d[3]), "+f"(d[4]), "+f"(d[5]), "+f"(d[6]), "+f"(d[7]), "+f"(d[8]), "+f"(d[9]), "+f"(d[10]), "+f"(d[11]), "+f"(d[12]), "+f"(d[13]), "+f"(d[14]), "+f"(d[15]), "+f"(d[16]), "+f"(d[17]), "+f"(d[18]), "+f"(d[19]), "+f"(d[20]), "+f"(d[21]), "+f"(d[22]), "+f"(d[23]), "+f"(d[24]), "+f"(d[25]), "+f"(d[26]), "+f"(d[27]), "+f"(d[28]), "+f"(d[29]), "+f"(d[30]), "+f"(d[31]), "+f"(d[32]), "+f"(d[33]), "+f"(d[34]), "+f"(d[35]), "+f"(d[36]), "+f"(d[37]), "+f"(d[38]), "+f"(d[39]), "+f"(d[40]), "+f"(d[41]), "+f"(d[42]), "+f"(d[43]), "+f"(d[44]), "+f"(d[45]), "+f"(d[46]), "+f"(d[47]), "+f"(d[48]), "+f"(d[49]), "+f"(d[50]), "+f"(d[51]), "+f"(d[52]), "+f"(d[53]), "+f"(d[54]), "+f"(d[55]), "+f"(d[56]), "+f"(d[57]), "+f"(d[58]), "+f"(d[59]), "+f"(d[60]), "+f"(d[61]), "+f"(d[62]), "+f"(d[63]), "+f"(d[64]), "+f"(d[65]), "+f"(d[66]), "+f"(d[67]), "+f"(d[68]), "+f"(d[69]), "+f"(d[70]), "+f"(d[71]), "+f"(d[72]), "+f"(d[73]), "+f"(d[74]), "+f"(d[75]), "+f"(d[76]), "+f"(d[77]), "+f"(d[78]), "+f"(d[79]), "+f"(d[80]), "+f"(d[81]), "+f"(d[82]), "+f"(d[83]), "+f"(d[84]), "+f"(d[85]), "+f"(d[86]), "+f"(d[87]), "+f"(d[88]), "+f"(d[89]), "+f"(d[90]), "+f"(d[91]), "+f"(d[92]), "+f"(d[93]), "+f"(d[94]), "+f"(d[95])
    : "l"(descA), "l"(descB), "r"(scaleD));
}
__device__ __forceinline__ void wgmma_ss_n64_tb(float (&d)[32], uint64_t descA, uint64_t descB, int scaleD) {
  asm volatile("{\n.reg .pred p;\nsetp.ne.b32 p, %34, 0;\n"
    "wgmma.mma_async.sync.aligned.m64n64k16.f32.bf16.bf16 {%0, %1, %2, %3, %4, %5, %6, %7, %8, %9, %10, %11, %12, %13, %14, %15, %16, %17, %18, %19, %20, %21, %22, %23, %24, %25, %26, %27, %28, %29, %30, %31}, %32, %33, p, 1, 1, 0, 1;\n}\n"
    : "+f"(d[0]), "+f"(d[1]), "+f"(d[2]), "+f"(d[3]), "+f"(d[4]), "+f"(d[5]), "+f"(d[6]), "+f"(d[7]), "+f"(d[8]), "+f"(d[9]), "+f"(d[10]), "+f"(d[11]), "+f"(d[12]), "+f"(d[13]), "+f"(d[14]), "+f"(d[15]), "+f"(d[16]), "+f"(d[17]), "+f"(d[18]), "+f"(d[19]), "+f"(d[20]), "+f"(d[21]), "+f"(d[22]), "+f"(d[23]), "+f"(d[24]), "+f"(d[25]), "+f"(d[26]), "+f"(d[27]), "+f"(d[28]), "+f"(d[29]), "+f"(d[30]), "+f"(d[31])
    : "l"(descA), "l"(descB), "r"(scaleD));
}
__device__ __forceinline__ void wgmma_ss_n16_tb(float (&d)[8], uint64_t descA, uint64_t descB, int scaleD) {
  asm volatile("{\n.reg .pred p;\nsetp.ne.b32 p, %10, 0;\n"
    "wgmma.mma_async.sync.aligned.m64n16k16.f32.bf16.bf16 {%0, %1, %2, %3, %4, %5, %6, %7}, %8, %9, p, 1, 1, 0, 1;\n}\n"
    : "+f"(d[0]), "+f"(d[1]), "+f"(d[2]), "+f"(d[3]), "+f"(d[4]), "+f"(d[5]), "+f"(d[6]), "+f"(d[7])
    : "l"(descA), "l"(descB), "r"(scaleD));
}
__device__ __forceinline__ void wgmma_rs_n128(float (&d)[64], uint32_t a0, uint32_t a1, uint32_t a2, uint32_t a3, uint64_t descB, int scaleD) {
  asm volatile("{\n.reg .pred p;\nsetp.ne.b32 p, %69, 0;\n"
    "wgmma.mma_async.sync.aligned.m64n128k16.f32.bf16.bf16 {%0, %1, %2, %3, %4, %5, %6, %7, %8, %9, %10, %11, %12, %13, %14, %15, %16, %17, %18, %19, %20, %21, %22, %23, %24, %25, %26, %27, %28, %29, %30, %31, %32, %33, %34, %35, %36, %37, %38, %39, %40, %41, %42, %43, %44, %45, %46, %47, %48, %49, %50, %51, %52, %53, %54, %55, %56, %57, %58, %59, %60, %61, %62, %63}, {%64, %65, %66, %67}, %68, p, 1, 1, 0;\n}\n"
    : "+f"(d[0]), "+f"(d[1]), "+f"(d[2]), "+f"(d[3]), "+f"(d[4]), "+f"(d[5]), "+f"(d[6]), "+f"(d[7]), "+f"(d[8]), "+f"(d[9]), "+f"(d[10]), "+f"(d[11]), "+f"(d[12]), "+f"(d[13]), "+f"(d[14]), "+f"(d[15]), "+f"(d[16]), "+f"(d[17]), "+f"(d[18]), "+f"(d[19]), "+f"(d[20]), "+f"(d[21]), "+f"(d[22]), "+f"(d[23]), "+f"(d[24]), "+f"(d[25]), "+f"(d[26]), "+f"(d[27]), "+f"(d[28]), "+f"(d[29]), "+f"(d[30]), "+f"(d[31]), "+f"(d[32]), "+f"(d[33]), "+f"(d[34]), "+f"(d[35]), "+f"(d[36]), "+f"(d[37]), "+f"(d[38]), "+f"(d[39]), "+f"(d[40]), "+f"(d[41]), "+f"(d[42]), "+f"(d[43]), "+f"(d[44]), "+f"(d[45]), "+f"(d[46]), "+f"(d[47]), "+f"(d[48]), "+f"(d[49]), "+f"(d[50]), "+f"(d[51]), "+f"(d[52]), "+f"(d[53]), "+f"(d[54]), "+f"(d[55]), "+f"(d[56]), "+f"(d[57]), "+f"(d[58]), "+f"(d[59]), "+f"(d[60]), "+f"(d[61]), "+f"(d[62]), "+f"(d[63])
    : "r"(a0), "r"(a1), "r"(a2), "r"(a3), "l"(descB), "r"(scaleD));
}
__device__ __forceinline__ void wgmma_rs_n64(float (&d)[32], uint32_t a0, uint32_t a1, uint32_t a2, uint32_t a3, uint64_t descB, int scaleD) {
  asm volatile("{\n.reg .pred p;\nsetp.ne.b32 p, %37, 0;\n"
    "wgmma.mma_async.sync.aligned.m64n64k16.f32.bf16.bf16 {%0, %1, %2, %3, %4, %5, %6, %7, %8, %9, %10, %11, %12, %13, %14, %15, %16, %17, %18, %19, %20, %21, %22, %23, %24, %25, %26, %27, %28, %29, %30, %31}, {%32, %33, %34, %35}, %36, p, 1, 1, 0;\n}\n"
    : "+f"(d[0]), "+f"(d[1]), "+f"(d[2]), "+f"(d[3]), "+f"(d[4]), "+f"(d[5]), "+f"(d[6]), "+f"(d[7]), "+f"(d[8]), "+f"(d[9]), "+f"(d[10]), "+f"(d[11]), "+f"(d[12]), "+f"(d[13]), "+f"(d[14]), "+f"(d[15]), "+f"(d[16]), "+f"(d[17]), "+f"(d[18]), "+f"(d[19]), "+f"(d[20]), "+f"(d[21]), "+f"(d[22]), "+f"(d[23]), "+f"(d[24]), "+f"(d[25]), "+f"(d[26]), "+f"(d[27]), "+f"(d[28]), "+f"(d[29]), "+f"(d[30]), "+f"(d[31])
    : "r"(a0), "r"(a1), "r"(a2), "r"(a3), "l"(descB), "r"(scaleD));
}
__device__ __forceinline__ void wgmma_rs_n24_tb(float (&d)[12], uint32_t a0, uint32_t a1, uint32_t a2, uint32_t a3, uint64_t descB, int scaleD) {
  asm volatile("{\n.reg .pred p;\nsetp.ne.b32 p, %17, 0;\n"
    "wgmma.mma_async.sync.aligned.m64n24k16.f32.bf16.bf16 {%0, %1, %2, %3, %4, %5, %6, %7, %8, %9, %10, %11}, {%12, %13, %14, %15}, %16, p, 1, 1, 1;\n}\n"
    : "+f"(d[0]), "+f"(d[1]), "+f"(d[2]), "+f"(d[3]), "+f"(d[4]), "+f"(d[5]), "+f"(d[6]), "+f"(d[7]), "+f"(d[8]), "+f"(d[9]), "+f"(d[10]), "+f"(d[11])
    : "r"(a0), "r"(a1), "r"(a2), "r"(a3), "l"(descB), "r"(scaleD));
}

constexpr int GT = 384;

__device__ __forceinline__ void release_stage(uint32_t bar, bool leader) {
  if (leader) {
    mbar_arrive_cluster(bar, 0);
    mbar_arrive_cluster(bar, 1);
  }
}

__device__ __forceinline__ void ln_row(const bf16* __restrict__ xin, bf16* __restrict__ xout, int l16) {
  const uint4* src = reinterpret_cast<const uint4*>(xin);
  uint4 v[5];
#pragma unroll
  for (int j = 0; j < 5; j++) v[j] = __ldg(src + j * 16 + l16);
  float s0 = 0.f, s1 = 0.f, s2 = 0.f, s3 = 0.f;
#pragma unroll
  for (int j = 0; j < 5; j++) {
    s0 += bf_lo(v[j].x) + bf_hi(v[j].x);
    s1 += bf_lo(v[j].y) + bf_hi(v[j].y);
    s2 += bf_lo(v[j].z) + bf_hi(v[j].z);
    s3 += bf_lo(v[j].w) + bf_hi(v[j].w);
  }
  float mean = (s0 + s1) + (s2 + s3);
#pragma unroll
  for (int o = 1; o < 16; o <<= 1) mean += __shfl_xor_sync(0xffffffffu, mean, o);
  mean *= (1.0f / DM);
  s0 = s1 = s2 = s3 = 0.f;
#pragma unroll
  for (int j = 0; j < 5; j++) {
    float d;
    d = bf_lo(v[j].x) - mean; s0 = fmaf(d, d, s0);
    d = bf_hi(v[j].x) - mean; s1 = fmaf(d, d, s1);
    d = bf_lo(v[j].y) - mean; s2 = fmaf(d, d, s2);
    d = bf_hi(v[j].y) - mean; s3 = fmaf(d, d, s3);
    d = bf_lo(v[j].z) - mean; s0 = fmaf(d, d, s0);
    d = bf_hi(v[j].z) - mean; s1 = fmaf(d, d, s1);
    d = bf_lo(v[j].w) - mean; s2 = fmaf(d, d, s2);
    d = bf_hi(v[j].w) - mean; s3 = fmaf(d, d, s3);
  }
  float sq = (s0 + s1) + (s2 + s3);
#pragma unroll
  for (int o = 1; o < 16; o <<= 1) sq += __shfl_xor_sync(0xffffffffu, sq, o);
  const float var_b = bf16_round(sq * (1.0f / DM));
  const float den = bf16_round(sqrtf(bf16_round(var_b + 1e-5f)));
  const float iv = __frcp_rn(den);
  const float mb = bf16_round(mean);
  uint4* dst = reinterpret_cast<uint4*>(xout);
#pragma unroll
  for (int j = 0; j < 5; j++) {
    uint4 w;
    uint32_t t;
    t = pack_bf16(bf_lo(v[j].x) - mb, bf_hi(v[j].x) - mb); w.x = pack_bf16(bf_lo(t) * iv, bf_hi(t) * iv);
    t = pack_bf16(bf_lo(v[j].y) - mb, bf_hi(v[j].y) - mb); w.y = pack_bf16(bf_lo(t) * iv, bf_hi(t) * iv);
    t = pack_bf16(bf_lo(v[j].z) - mb, bf_hi(v[j].z) - mb); w.z = pack_bf16(bf_lo(t) * iv, bf_hi(t) * iv);
    t = pack_bf16(bf_lo(v[j].w) - mb, bf_hi(v[j].w) - mb); w.w = pack_bf16(bf_lo(t) * iv, bf_hi(t) * iv);
    dst[j * 16 + l16] = w;
  }
}

constexpr int LG_STAGES = 5;
constexpr int QKV_STAGE = 8192 + 4 * 4096;
constexpr int GLU_STAGE = 8192 + 6 * 4096;

template <int WG>
__device__ __forceinline__ void qkv_mainloop(float (&acc)[120], uint32_t sbase, uint32_t sBar, bool leader) {
  constexpr int STAGE_BYTES = QKV_STAGE, NST = LG_STAGES;
  const uint64_t da_base = make_desc(sbase + WG * 4096, 16, 512, 2);
  const uint64_t db_base = make_desc(sbase + 8192, 4096, 1024, 1);
#pragma unroll 1
  for (int r = 0; r < 20 / NST; r++) {
#pragma unroll
    for (int s = 0; s < NST; s++) {
      mbar_wait(sBar + 8 * s, r & 1);
      wgmma_fence();
#pragma unroll
      for (int ks = 0; ks < 2; ks++)
        wgmma_ss_n240_tb(acc, da_base + (uint64_t)((s * STAGE_BYTES + ks * 32) >> 4), db_base + (uint64_t)((s * STAGE_BYTES + ks * 2048) >> 4), 1);
      wgmma_commit();
      wgmma_wait<1>();
      release_stage(sBar + 8 * (NST + (s + NST - 1) % NST), leader && (s > 0 || r > 0));
    }
  }
}
template <int WG>
__device__ __forceinline__ void glu_mainloop(float (&accg)[96], float (&accu)[96], uint32_t sbase, uint32_t sBar, bool leader) {
  constexpr int STAGE_BYTES = GLU_STAGE, NST = LG_STAGES;
  const uint64_t da_base = make_desc(sbase + WG * 4096, 16, 512, 2);
  const uint64_t db_base = make_desc(sbase + 8192, 4096, 1024, 1);
#pragma unroll 1
  for (int r = 0; r < 20 / NST; r++) {
#pragma unroll
    for (int s = 0; s < NST; s++) {
      mbar_wait(sBar + 8 * s, r & 1);
      wgmma_fence();
#pragma unroll
      for (int ks = 0; ks < 2; ks++) {
        const uint64_t da = da_base + (uint64_t)((s * STAGE_BYTES + ks * 32) >> 4);
        wgmma_ss_n192_tb(accg, da, db_base + (uint64_t)((s * STAGE_BYTES + ks * 2048) >> 4), 1);
        wgmma_ss_n192_tb(accu, da, db_base + (uint64_t)((s * STAGE_BYTES + 3 * 4096 + ks * 2048) >> 4), 1);
      }
      wgmma_commit();
      wgmma_wait<1>();
      release_stage(sBar + 8 * (NST + (s + NST - 1) % NST), leader && (s > 0 || r > 0));
    }
  }
}
constexpr int RG_STAGE_BYTES = 16384 + 8192 + 2048;
template <int NKB, int NST, int WG>
__device__ __forceinline__ void res_mainloop(float (&acc0)[32], float (&acc1)[8], uint32_t sbase, uint32_t sBar, bool leader) {
  const uint64_t da_base = make_desc(sbase + WG * 8192, 16, 1024, 1);
  const uint64_t db0_base = make_desc(sbase + 16384, 8192, 1024, 1);
  const uint64_t db1_base = make_desc(sbase + 16384 + 8192, 2048, 256, 3);
#pragma unroll 1
  for (int r = 0; r < NKB / NST; r++) {
#pragma unroll
    for (int s = 0; s < NST; s++) {
      const uint64_t so = (uint64_t)(s * (RG_STAGE_BYTES >> 4));
      mbar_wait(sBar + 8 * s, r & 1);
      wgmma_fence();
#pragma unroll
      for (int ks = 0; ks < 4; ks++) {
        wgmma_ss_n64_tb(acc0, da_base + so + ks * 2, db0_base + so + ks * 128, 1);
        wgmma_ss_n16_tb(acc1, da_base + so + ks * 2, db1_base + so + ks * 32, 1);
      }
      wgmma_commit();
      wgmma_wait<1>();
      release_stage(sBar + 8 * (NST + (s + NST - 1) % NST), leader && (s > 0 || r > 0));
    }
  }
}

constexpr int KA_SMEM = LG_STAGES * QKV_STAGE + 128 + 1024;

__global__ void __launch_bounds__(GT, 1)
qkv_kernel(const __grid_constant__ CUtensorMap tmA, const __grid_constant__ CUtensorMap tmB, const bf16* __restrict__ x) {
  constexpr int STAGE_BYTES = QKV_STAGE, NST = LG_STAGES, NKB = 20;
  extern __shared__ uint8_t smem_raw[];
  const uint32_t sbase = (smem_u32(smem_raw) + 1023u) & ~1023u;
  const uint32_t sBar = sbase + NST * STAGE_BYTES;
  const int tid = threadIdx.x, warp = tid >> 5, lane = tid & 31;
  const int rank = blockIdx.x & 1;
  const int pair = blockIdx.x >> 1;
  const int n_blk = pair & 7;
  const int m_blk = (pair >> 3) * 2 + rank;
  TS(0, 0);
  if (tid == 256) {
    prefetch_tmap(&tmA);
    prefetch_tmap(&tmB);
  }
  if (tid == 0) {
    for (int s = 0; s < NST; s++) {
      mbar_init(sBar + 8 * s, 1);
      mbar_init(sBar + 8 * (NST + s), 4);
    }
    fence_mbar_init();
    if (blockIdx.x < 32) g_flag[16 + blockIdx.x] = 0;
  }
  pdl_launch();
  asm volatile("barrier.cluster.arrive.release.aligned;" ::: "memory");

  if (warp >= 8) {
    asm volatile("setmaxnreg.dec.sync.aligned.u32 40;");
    asm volatile("barrier.cluster.wait.acquire.aligned;" ::: "memory");
    if (warp == 9) {
      named_bar_sync(5, 288);
      if (lane == 0) flag_signal(&g_flag[m_blk]);
    }
    if (tid == 256) {
      auto issue_b = [&](int kb) {
        const int s = kb % NST;
        const uint32_t full = sBar + 8 * s;
        mbar_expect_tx(full, STAGE_BYTES);
        const uint32_t dst = sbase + s * STAGE_BYTES + 8192;
#pragma unroll
        for (int j = 0; j < 2; j++) {
          const int sl = rank * 2 + j;
          tma_load_2d_mc(dst + sl * 4096, &tmB, n_blk * 240 + sl * 64, kb * 32, full, (uint16_t)3);
        }
      };
      for (int kb = 0; kb < NST; kb++) issue_b(kb);
      flag_wait(&g_flag[m_blk], 8);
      fence_proxy_async_all();
      for (int kb = 0; kb < NKB; kb++) {
        const int s = kb % NST;
        if (kb >= NST) {
          mbar_wait(sBar + 8 * (NST + s), ((kb / NST) & 1) ^ 1);
          issue_b(kb);
        }
        tma_load_2d(sbase + s * STAGE_BYTES, &tmA, kb * 32, m_blk * 128, sBar + 8 * s);
      }
    }
  } else {
    asm volatile("setmaxnreg.inc.sync.aligned.u32 232;");
    const int wg = __shfl_sync(0xffffffffu, warp >> 2, 0);
    const int wwarp = warp & 3;
    {
      const int row = m_blk * 128 + n_blk * 16 + warp * 2 + (lane >> 4);
      ln_row(x + (size_t)row * DM, g_xn + (size_t)row * DM, lane & 15);
      asm volatile("bar.arrive 5, 288;" ::: "memory");
    }
    asm volatile("barrier.cluster.wait.acquire.aligned;" ::: "memory");
    TS(0, 1);
    mbar_wait(sBar, 0);
    TS(0, 3);
    float acc[120];
#pragma unroll
    for (int i = 0; i < 120; i++) acc[i] = 0.f;
    if (wg == 0) qkv_mainloop<0>(acc, sbase, sBar, (tid & 127) == 0);
    else qkv_mainloop<1>(acc, sbase, sBar, (tid & 127) == 0);
    wgmma_wait<0>();
    fence_regs(acc);
    TS(0, 4);
    named_bar_sync(3, 256);
    const int g = lane >> 2, c4 = lane & 3;
    const uint32_t stg = sbase + wg * (12 * 3072) + (wwarp * 2) * 384 + g * 16;
    const int hbase = n_blk * 12;
#pragma unroll
    for (int j = 0; j < 30; j++) {
      const int cb = (j * 8) % 20;
      const int hb = (j * 8) / 20;
      int d = cb + c4 * 2;
      int hl = hb;
      if (cb == 16 && c4 >= 2) { d -= 20; hl += 1; }
      const uint32_t a0 = stg + hl * 3072 + (d >> 3) * 128 + (d & 7) * 2;
      const int hg = hbase + hl;
      const float sc = hg < 32 ? ATT_SCALE_LOG2E : 1.0f;
      st_shared_b32(a0, pack_bf16(acc[4 * j] * sc, acc[4 * j + 1] * sc));
      st_shared_b32(a0 + 384, pack_bf16(acc[4 * j + 2] * sc, acc[4 * j + 3] * sc));
      if (d == 18) {
        const uint32_t pad0 = hg < 32 ? 0u : (hg < 64 ? 0x3f803f80u : 0x00003f80u);
        const uint32_t pad1 = (hg >= 32 && hg < 64) ? 0x00003f80u : 0u;
        st_shared_v2(a0 + 4, pad0, pad1);
        st_shared_v2(a0 + 388, pad0, pad1);
      }
      if (j % 10 == 9) {
        fence_proxy_async();
        named_bar_sync(1 + wg, 128);
        if ((tid & 127) < 4) {
          const int hs = (j / 10) * 4 + (tid & 127);
          bf16* dst = g_img + (size_t)(hbase + hs) * IMG_HEAD_ELEMS + (size_t)(m_blk * 16 + wg * 8) * 192;
          bulk_s2g(dst, sbase + wg * (12 * 3072) + hs * 3072, 3072);
          bulk_commit();
        }
      }
    }
    if ((tid & 127) < 4) bulk_wait_read();
  }
  __syncwarp();
  TS(0, 5);
  cluster_sync_relaxed();
  TS(0, 6);
}

constexpr int KC_NST1 = 5, KC_NST3 = 6;
constexpr int KC_STAGING = 160 * 1024;
constexpr int KC_BAR = KC_STAGING + 48 * 1024;
constexpr int KC_CS = KC_BAR + 512;
constexpr int KC_SMEM = KC_CS + 1536 + 1024;

__global__ void __launch_bounds__(GT, 1)
mlp_kernel(const __grid_constant__ CUtensorMap tmO, const __grid_constant__ CUtensorMap tmWo64, const __grid_constant__ CUtensorMap tmWo16,
           const __grid_constant__ CUtensorMap tmH, const __grid_constant__ CUtensorMap tmWg, const __grid_constant__ CUtensorMap tmWu,
           const __grid_constant__ CUtensorMap tmHHs, const __grid_constant__ CUtensorMap tmHH, const __grid_constant__ CUtensorMap tmWd64,
           const __grid_constant__ CUtensorMap tmWd16, const __grid_constant__ CUtensorMap tmHs, const __grid_constant__ CUtensorMap tmOut,
           const bf16* __restrict__ x) {
  extern __shared__ uint8_t smem_raw[];
  const uint32_t sbase = (smem_u32(smem_raw) + 1023u) & ~1023u;
  const uint32_t bar1 = sbase + KC_BAR;
  const uint32_t bar2 = bar1 + 128;
  const uint32_t bar3 = bar2 + 128;
  const uint32_t barD = bar3 + 128;
  const int tid = threadIdx.x, warp = tid >> 5, lane = tid & 31;
  const int rank = blockIdx.x & 1;
  const int pair = blockIdx.x >> 1;
  const int j_blk = pair & 7;
  const int m_blk = (pair >> 3) * 2 + rank;
  const int m13 = pair >> 2;
  const int j13 = (pair & 3) * 2 + rank;
  const int n0 = j13 * 80;
  TS(2, 0);
  if (tid == 256) {
    prefetch_tmap(&tmO); prefetch_tmap(&tmWo64); prefetch_tmap(&tmWo16); prefetch_tmap(&tmH); prefetch_tmap(&tmWg);
    prefetch_tmap(&tmWu); prefetch_tmap(&tmHHs); prefetch_tmap(&tmHH); prefetch_tmap(&tmWd64); prefetch_tmap(&tmWd16);
    prefetch_tmap(&tmHs); prefetch_tmap(&tmOut);
  }
  if (tid == 0) {
    for (int s = 0; s < 5; s++) {
      mbar_init(bar1 + 8 * s, 1); mbar_init(bar1 + 8 * (5 + s), 4);
      mbar_init(bar2 + 8 * s, 1); mbar_init(bar2 + 8 * (5 + s), 4);
    }
    for (int s = 0; s < 6; s++) { mbar_init(bar3 + 8 * s, 1); mbar_init(bar3 + 8 * (6 + s), 4); }
    mbar_init(barD, 4); mbar_init(barD + 8, 4);
    fence_mbar_init();
  }
  cluster_sync_all();

  if (warp >= 8) {
    asm volatile("setmaxnreg.dec.sync.aligned.u32 40;");
    if (tid == 256) {
      auto issue_b80 = [&](const CUtensorMap* t64, const CUtensorMap* t16, uint32_t bars, int nst, int kb) {
        const int s = kb % nst;
        const uint32_t full = bars + 8 * s;
        const uint32_t st = sbase + s * RG_STAGE_BYTES;
        mbar_expect_tx(full, RG_STAGE_BYTES);
        tma_load_2d(st + 16384, t64, n0, kb * 64, full);
        tma_load_2d(st + 16384 + 8192, t16, n0 + 64, kb * 64, full);
      };
      for (int kb = 0; kb < KC_NST1; kb++) issue_b80(&tmWo64, &tmWo16, bar1, KC_NST1, kb);
      pdl_wait();
      for (int kb = 0; kb < 10; kb++) {
        const int s = kb % KC_NST1;
        if (kb >= KC_NST1) {
          mbar_wait(bar1 + 8 * (KC_NST1 + s), ((kb / KC_NST1) & 1) ^ 1);
          issue_b80(&tmWo64, &tmWo16, bar1, KC_NST1, kb);
        }
        tma_load_2d_mc(sbase + s * RG_STAGE_BYTES + rank * 8192, &tmO, kb * 64, m13 * 128 + rank * 64, bar1 + 8 * s, (uint16_t)3);
      }
      auto issue_bglu = [&](int kb) {
        const int s = kb % LG_STAGES;
        const uint32_t full = bar2 + 8 * s;
        mbar_expect_tx(full, GLU_STAGE);
        const uint32_t dst = sbase + s * GLU_STAGE + 8192;
#pragma unroll
        for (int j = 0; j < 3; j++)
          tma_load_2d_mc(dst + (rank * 3 + j) * 4096, rank == 0 ? &tmWg : &tmWu, j_blk * 192 + j * 64, kb * 32, full, (uint16_t)3);
      };
      mbar_wait(barD, 0);
      for (int kb = 0; kb < LG_STAGES; kb++) issue_bglu(kb);
      flag_wait(&g_flag[16 + m_blk], 16);
      fence_proxy_async_all();
      for (int kb = 0; kb < 20; kb++) {
        const int s = kb % LG_STAGES;
        if (kb >= LG_STAGES) {
          mbar_wait(bar2 + 8 * (LG_STAGES + s), ((kb / LG_STAGES) & 1) ^ 1);
          issue_bglu(kb);
        }
        tma_load_2d(sbase + s * GLU_STAGE, &tmH, kb * 32, m_blk * 128, bar2 + 8 * s);
      }
      mbar_wait(barD + 8, 0);
      for (int kb = 0; kb < KC_NST3; kb++) issue_b80(&tmWd64, &tmWd16, bar3, KC_NST3, kb);
      flag_wait(&g_flag[32 + m13], 16);
      fence_proxy_async_all();
      for (int kb = 0; kb < 24; kb++) {
        const int s = kb % KC_NST3;
        if (kb >= KC_NST3) {
          mbar_wait(bar3 + 8 * (KC_NST3 + s), ((kb / KC_NST3) & 1) ^ 1);
          issue_b80(&tmWd64, &tmWd16, bar3, KC_NST3, kb);
        }
        tma_load_2d_mc(sbase + s * RG_STAGE_BYTES + rank * 8192, &tmHH, kb * 64, m13 * 128 + rank * 64, bar3 + 8 * s, (uint16_t)3);
      }
    }
  } else {
    asm volatile("setmaxnreg.inc.sync.aligned.u32 232;");
    const int wg = __shfl_sync(0xffffffffu, warp >> 2, 0);
    const int wwarp = warp & 3;
    const int g = lane >> 2, c4 = lane & 3;
    const int row0 = m13 * 128 + wg * 64 + wwarp * 16 + g;
    const int row2 = m_blk * 128 + wg * 64 + wwarp * 16 + g;
    const bool leader = (tid & 127) == 0;
    const uint32_t stg80_base = sbase + KC_STAGING + wg * 24576;
    const uint32_t stg80 = stg80_base + (wwarp * 16 + g) * 160 + c4 * 4;
    {
      uint32_t res[20];
#pragma unroll
      for (int j = 0; j < 10; j++) {
        res[2 * j] = __ldg(reinterpret_cast<const uint32_t*>(x + (size_t)row0 * DM + n0 + j * 8 + c4 * 2));
        res[2 * j + 1] = __ldg(reinterpret_cast<const uint32_t*>(x + (size_t)(row0 + 8) * DM + n0 + j * 8 + c4 * 2));
      }
      float acc0[32], acc1[8];
#pragma unroll
      for (int i = 0; i < 32; i++) acc0[i] = 0.f;
#pragma unroll
      for (int i = 0; i < 8; i++) acc1[i] = 0.f;
      TS(2, 1);
      if (wg == 0) res_mainloop<10, KC_NST1, 0>(acc0, acc1, sbase, bar1, leader);
      else res_mainloop<10, KC_NST1, 1>(acc0, acc1, sbase, bar1, leader);
      wgmma_wait<0>();
      fence_regs(acc0); fence_regs(acc1);
      release_stage(barD, leader);
      TS(2, 4);
      float sum0 = 0.f, sum1 = 0.f;
#pragma unroll
      for (int j = 0; j < 10; j++) {
        const uint32_t a01 = j < 8 ? pack_bf16(acc0[4 * j], acc0[4 * j + 1]) : pack_bf16(acc1[4 * (j - 8)], acc1[4 * (j - 8) + 1]);
        const uint32_t a23 = j < 8 ? pack_bf16(acc0[4 * j + 2], acc0[4 * j + 3]) : pack_bf16(acc1[4 * (j - 8) + 2], acc1[4 * (j - 8) + 3]);
        res[2 * j] = pack_bf16(bf_lo(res[2 * j]) + bf_lo(a01), bf_hi(res[2 * j]) + bf_hi(a01));
        res[2 * j + 1] = pack_bf16(bf_lo(res[2 * j + 1]) + bf_lo(a23), bf_hi(res[2 * j + 1]) + bf_hi(a23));
        st_shared_b32(stg80 + j * 16, res[2 * j]);
        st_shared_b32(stg80 + 8 * 160 + j * 16, res[2 * j + 1]);
        sum0 += bf_lo(res[2 * j]) + bf_hi(res[2 * j]);
        sum1 += bf_lo(res[2 * j + 1]) + bf_hi(res[2 * j + 1]);
      }
      sum0 += __shfl_xor_sync(0xffffffffu, sum0, 1); sum1 += __shfl_xor_sync(0xffffffffu, sum1, 1);
      sum0 += __shfl_xor_sync(0xffffffffu, sum0, 2); sum1 += __shfl_xor_sync(0xffffffffu, sum1, 2);
      const float mu0 = sum0 * (1.0f / 80.0f), mu1 = sum1 * (1.0f / 80.0f);
      float q0 = 0.f, q1 = 0.f;
#pragma unroll
      for (int j = 0; j < 10; j++) {
        float d;
        d = bf_lo(res[2 * j]) - mu0; q0 = fmaf(d, d, q0);
        d = bf_hi(res[2 * j]) - mu0; q0 = fmaf(d, d, q0);
        d = bf_lo(res[2 * j + 1]) - mu1; q1 = fmaf(d, d, q1);
        d = bf_hi(res[2 * j + 1]) - mu1; q1 = fmaf(d, d, q1);
      }
      q0 += __shfl_xor_sync(0xffffffffu, q0, 1); q1 += __shfl_xor_sync(0xffffffffu, q1, 1);
      q0 += __shfl_xor_sync(0xffffffffu, q0, 2); q1 += __shfl_xor_sync(0xffffffffu, q1, 2);
      if (c4 == 0) {
        g_stats[row0 * 8 + j13] = make_float2(mu0, q0);
        g_stats[(row0 + 8) * 8 + j13] = make_float2(mu1, q1);
      }
      fence_proxy_async();
      named_bar_sync(1 + wg, 128);
      if (leader) {
        tma_store_2d(&tmHs, stg80_base, n0, m13 * 128 + wg * 64);
        bulk_commit();
        bulk_wait_all();
        fence_proxy_async_all();
        flag_signal(&g_flag[16 + m13]);
      }
      TS(2, 5);
    }
    {
      pdl_wait();
      {
        float* cs_s = reinterpret_cast<float*>(smem_raw + (sbase - smem_u32(smem_raw)) + KC_CS);
        for (int i = tid; i < 384; i += 256) cs_s[i] = g_cs[(i >= 192 ? FF - 192 : 0) + j_blk * 192 + i];
        named_bar_sync(3, 256);
      }
      flag_wait(&g_flag[16 + m_blk], 16);
      float mb[2], iv[2];
#pragma unroll
      for (int h = 0; h < 2; h++) {
        const float4* sp = reinterpret_cast<const float4*>(g_stats + (row2 + 8 * h) * 8);
        const float4 p0 = sp[0], p1 = sp[1], p2 = sp[2], p3 = sp[3];
        const float mean = (((p0.x + p0.z) + (p1.x + p1.z)) + ((p2.x + p2.z) + (p3.x + p3.z))) * 0.125f;
        float m2 = ((p0.y + p0.w) + (p1.y + p1.w)) + ((p2.y + p2.w) + (p3.y + p3.w));
        float dd = 0.f, d;
        d = p0.x - mean; dd = fmaf(d, d, dd); d = p0.z - mean; dd = fmaf(d, d, dd);
        d = p1.x - mean; dd = fmaf(d, d, dd); d = p1.z - mean; dd = fmaf(d, d, dd);
        d = p2.x - mean; dd = fmaf(d, d, dd); d = p2.z - mean; dd = fmaf(d, d, dd);
        d = p3.x - mean; dd = fmaf(d, d, dd); d = p3.z - mean; dd = fmaf(d, d, dd);
        m2 = fmaf(dd, 80.0f, m2);
        const float var_b = bf16_round(m2 * (1.0f / DM));
        const float den = bf16_round(sqrtf(bf16_round(var_b + 1e-5f)));
        iv[h] = __frcp_rn(den);
        mb[h] = bf16_round(mean);
      }
      float accg[96], accu[96];
#pragma unroll
      for (int i = 0; i < 96; i++) { accg[i] = 0.f; accu[i] = 0.f; }
      TS(3, 3);
      if (wg == 0) glu_mainloop<0>(accg, accu, sbase, bar2, leader);
      else glu_mainloop<1>(accg, accu, sbase, bar2, leader);
      wgmma_wait<0>();
      fence_regs(accg); fence_regs(accu);
      release_stage(barD + 8, leader);
      TS(3, 4);
      const uint32_t stg = sbase + KC_STAGING + wg * 24576 + (wwarp * 16 + g) * 128 + c4 * 4;
      const float* csg = reinterpret_cast<const float*>(smem_raw + (sbase - smem_u32(smem_raw)) + KC_CS) + c4 * 2;
      const float nm0 = -mb[0] * iv[0], nm1 = -mb[1] * iv[1];
#pragma unroll
      for (int sl = 0; sl < 3; sl++) {
        float2 cgv[4], cuv[4];
#pragma unroll
        for (int jj = 0; jj < 8; jj++) {
          const int j = sl * 8 + jj;
          if ((jj & 3) == 0) {
#pragma unroll
            for (int q = 0; q < 4; q++) {
              cgv[q] = *reinterpret_cast<const float2*>(csg + (j + q) * 8);
              cuv[q] = *reinterpret_cast<const float2*>(csg + 192 + (j + q) * 8);
            }
          }
          const float2 cg = cgv[jj & 3], cu = cuv[jj & 3];
          const float r0 = fmaxf(fmaf(accg[4 * j], iv[0], nm0 * cg.x), 0.f) * fmaf(accu[4 * j], iv[0], nm0 * cu.x);
          const float r1 = fmaxf(fmaf(accg[4 * j + 1], iv[0], nm0 * cg.y), 0.f) * fmaf(accu[4 * j + 1], iv[0], nm0 * cu.y);
          const float r2 = fmaxf(fmaf(accg[4 * j + 2], iv[1], nm1 * cg.x), 0.f) * fmaf(accu[4 * j + 2], iv[1], nm1 * cu.x);
          const float r3 = fmaxf(fmaf(accg[4 * j + 3], iv[1], nm1 * cg.y), 0.f) * fmaf(accu[4 * j + 3], iv[1], nm1 * cu.y);
          const uint32_t a0 = stg + sl * 8192 + ((jj ^ g) << 4);
          st_shared_b32(a0, pack_bf16(r0, r1));
          st_shared_b32(a0 + 1024, pack_bf16(r2, r3));
        }
        fence_proxy_async();
        named_bar_sync(1 + wg, 128);
        if (leader) {
          tma_store_2d(&tmHHs, sbase + KC_STAGING + wg * 24576 + sl * 8192, j_blk * 192 + sl * 64, m_blk * 128 + wg * 64);
          bulk_commit();
        }
      }
      TS(3, 7);
      if (leader) {
        bulk_wait_all();
        TS(3, 8);
        fence_proxy_async_all();
        flag_signal(&g_flag[32 + m_blk]);
      }
      TS(3, 9);
    }
    {
      uint32_t res[20];
#pragma unroll
      for (int j = 0; j < 10; j++) {
        res[2 * j] = *reinterpret_cast<const uint32_t*>(g_h + (size_t)row0 * DM + n0 + j * 8 + c4 * 2);
        res[2 * j + 1] = *reinterpret_cast<const uint32_t*>(g_h + (size_t)(row0 + 8) * DM + n0 + j * 8 + c4 * 2);
      }
      float acc0[32], acc1[8];
#pragma unroll
      for (int i = 0; i < 32; i++) acc0[i] = 0.f;
#pragma unroll
      for (int i = 0; i < 8; i++) acc1[i] = 0.f;
      mbar_wait(bar3, 0);
      TS(4, 3);
      if (wg == 0) res_mainloop<24, KC_NST3, 0>(acc0, acc1, sbase, bar3, leader);
      else res_mainloop<24, KC_NST3, 1>(acc0, acc1, sbase, bar3, leader);
      wgmma_wait<0>();
      fence_regs(acc0); fence_regs(acc1);
      TS(4, 4);
#pragma unroll
      for (int j = 0; j < 10; j++) {
        const uint32_t a01 = j < 8 ? pack_bf16(acc0[4 * j], acc0[4 * j + 1]) : pack_bf16(acc1[4 * (j - 8)], acc1[4 * (j - 8) + 1]);
        const uint32_t a23 = j < 8 ? pack_bf16(acc0[4 * j + 2], acc0[4 * j + 3]) : pack_bf16(acc1[4 * (j - 8) + 2], acc1[4 * (j - 8) + 3]);
        st_shared_b32(stg80 + j * 16, pack_bf16(bf_lo(res[2 * j]) + bf_lo(a01), bf_hi(res[2 * j]) + bf_hi(a01)));
        st_shared_b32(stg80 + 8 * 160 + j * 16, pack_bf16(bf_lo(res[2 * j + 1]) + bf_lo(a23), bf_hi(res[2 * j + 1]) + bf_hi(a23)));
      }
      fence_proxy_async();
      named_bar_sync(1 + wg, 128);
      if (leader) {
        tma_store_2d(&tmOut, stg80_base, n0, m13 * 128 + wg * 64);
        bulk_commit();
        bulk_wait_read();
      }
      TS(4, 5);
    }
  }
  __syncwarp();
  cluster_sync_relaxed();
  TS(4, 6);
}

constexpr int AT_THREADS = 512;
constexpr int AT_WGS = AT_THREADS / 128;
constexpr int AT_KV_BYTES = IMG_HEAD_ELEMS * 2;
constexpr int AT_SMEM = 2 * AT_KV_BYTES + 256 + 1024;
constexpr int AT_CHUNKS = 8;

__device__ __forceinline__ float exp2_poly(float x) {
  const float u = __saturatef(fmaf(x, 1.0f / 64.0f, 62.0f / 64.0f));
  const float MAGIC = 12582912.0f - 62.0f;
  const float r = fmaf(u, 64.0f, MAGIC);
  const float q = MAGIC - r;
  const float fr = fmaf(u, 64.0f, q);
  float p = fmaf(fr, 0.009570102207362652f, 0.05591785907745361f);
  p = fmaf(p, fr, 0.240247443318367f);
  p = fmaf(p, fr, 0.6931217908859253f);
  p = fmaf(p, fr, 0.9999992847442627f);
  return __uint_as_float(__float_as_uint(p) + (__float_as_uint(r) << 23));
}
__device__ __forceinline__ bool use_poly(int e) { return (e & 7) == 1; }

struct AttnState {
  uint32_t qa0, qa1, qa2, qa3, qa4, qa5;
  float M0, M1;
};

__device__ __forceinline__ bool attn_exp_fast(const float (&s)[32], uint32_t (&p)[16]) {
#pragma unroll
  for (int j = 0; j < 16; j++) {
    const float e0 = use_poly(2 * j) ? exp2_poly(s[2 * j]) : ex2(s[2 * j]);
    const float e1 = use_poly(2 * j + 1) ? exp2_poly(s[2 * j + 1]) : ex2(s[2 * j + 1]);
    p[j] = pack_bf16(e0, e1);
  }
  uint32_t acc_or = 0;
#pragma unroll
  for (int j = 0; j < 16; j++) acc_or |= p[j];
  return __any_sync(0xffffffffu, (acc_or & 0x40004000u) != 0);
}
__device__ __forceinline__ void attn_exp_exact(const float (&s)[32], uint32_t (&p)[16], float (&o)[12], AttnState& st, bool first, int c4) {
  float mx0 = fmaxf(s[0], s[1]), mx1 = fmaxf(s[2], s[3]);
#pragma unroll
  for (int j = 1; j < 8; j++) {
    mx0 = fmaxf(mx0, fmaxf(s[4 * j], s[4 * j + 1]));
    mx1 = fmaxf(mx1, fmaxf(s[4 * j + 2], s[4 * j + 3]));
  }
  mx0 = fmaxf(mx0, __shfl_xor_sync(0xffffffffu, mx0, 1));
  mx1 = fmaxf(mx1, __shfl_xor_sync(0xffffffffu, mx1, 1));
  mx0 = fmaxf(mx0, __shfl_xor_sync(0xffffffffu, mx0, 2));
  mx1 = fmaxf(mx1, __shfl_xor_sync(0xffffffffu, mx1, 2));
  float d0 = mx0 + 7.0f, d1 = mx1 + 7.0f;
  if (!first) { d0 = fmaxf(d0, 0.f); d1 = fmaxf(d1, 0.f); }
  const float T0 = st.M0 + d0, T1 = st.M1 + d1;
  const float h0 = bf16_round(T0), h1 = bf16_round(T1);
  const float i0 = bf16_round(T0 - h0), i1 = bf16_round(T1 - h1);
  const float l0 = bf16_round((T0 - h0) - i0), l1 = bf16_round((T1 - h1) - i1);
  const float N0 = (h0 + i0) + l0, N1 = (h1 + i1) + l1;
  d0 = N0 - st.M0; d1 = N1 - st.M1;
  st.M0 = N0; st.M1 = N1;
  if (c4 == 2) { st.qa4 = pack_bf16(-h0, -i0); st.qa5 = pack_bf16(-h1, -i1); }
  if (c4 == 3) { st.qa4 = pack_bf16(-l0, 0.f); st.qa5 = pack_bf16(-l1, 0.f); }
  if (!first) {
    const float al0 = ex2(-d0), al1 = ex2(-d1);
#pragma unroll
    for (int j = 0; j < 3; j++) {
      o[4 * j] *= al0; o[4 * j + 1] *= al0;
      o[4 * j + 2] *= al1; o[4 * j + 3] *= al1;
    }
  }
#pragma unroll
  for (int j = 0; j < 8; j++) {
    p[2 * j] = pack_bf16(ex2(s[4 * j] - d0), ex2(s[4 * j + 1] - d0));
    p[2 * j + 1] = pack_bf16(ex2(s[4 * j + 2] - d1), ex2(s[4 * j + 3] - d1));
  }
}
__device__ __forceinline__ void attn_step(float (&s)[32], const uint32_t (&pp)[16], uint32_t (&pn)[16], float (&o)[12], AttnState& st,
                                          uint32_t k_addr, uint32_t v_addr_prev, int keep, int c4, int wgdbg = 0, int tdbg = 0) {
  PH(wgdbg, tdbg, 0);
  const uint64_t dk = make_desc(k_addr, 128, 384, 0);
  const uint64_t dv_prev = make_desc(v_addr_prev, 384, 128, 0);
  wgmma_fence();
  wgmma_rs_n64(s, st.qa0, st.qa1, st.qa2, st.qa3, dk, 0);
  wgmma_rs_n64(s, st.qa4, st.qa5, 0u, 0u, dk + 16, 1);
  wgmma_commit();
#pragma unroll
  for (int kk = 0; kk < 4; kk++) wgmma_rs_n24_tb(o, pp[4 * kk], pp[4 * kk + 1], pp[4 * kk + 2], pp[4 * kk + 3], dv_prev + kk * 48, kk == 0 ? keep : 1);
  wgmma_commit();
  wgmma_wait<1>();
  fence_regs(s);
  PH(wgdbg, tdbg, 1);
  const bool redo = attn_exp_fast(s, pn);
  PH(wgdbg, tdbg, 2);
  wgmma_wait<0>();
  fence_regs(o);
  if (redo) attn_exp_exact(s, pn, o, st, false, c4);
}

__global__ void __launch_bounds__(AT_THREADS, 1) attn_kernel(const bf16* __restrict__ wo, const bf16* __restrict__ wgt, const bf16* __restrict__ wup, const bf16* __restrict__ wdn) {
  extern __shared__ uint8_t smem_raw[];
  const uint32_t sbase = (smem_u32(smem_raw) + 1023u) & ~1023u;
  const uint32_t sK = sbase, sV = sbase + AT_KV_BYTES;
  const uint32_t sBar = sV + AT_KV_BYTES;
  const int tid = threadIdx.x, warp = tid >> 5, lane = tid & 31;
  const int head = blockIdx.x >> 2, quarter = blockIdx.x & 3;
  if (blockIdx.x >= 128) {
    pdl_launch();
    const int b = blockIdx.x - 128;
    const bf16* w = (b >> 1) ? wup : wgt;
    const int cgrp = tid % 96, rgrp = tid / 96;
    float acc[8];
#pragma unroll
    for (int i = 0; i < 8; i++) acc[i] = 0.f;
    float* red = reinterpret_cast<float*>(smem_raw);
    if (rgrp < 5) {
      const uint4* src = reinterpret_cast<const uint4*>(w + (size_t)(rgrp * 128) * FF + (b & 1) * 768 + cgrp * 8);
#pragma unroll 8
      for (int r = 0; r < 128; r++) {
        const uint4 v = __ldg(src + (size_t)r * (FF / 8));
        acc[0] += bf_lo(v.x); acc[1] += bf_hi(v.x); acc[2] += bf_lo(v.y); acc[3] += bf_hi(v.y);
        acc[4] += bf_lo(v.z); acc[5] += bf_hi(v.z); acc[6] += bf_lo(v.w); acc[7] += bf_hi(v.w);
      }
#pragma unroll
      for (int i = 0; i < 8; i++) red[rgrp * 768 + cgrp * 8 + i] = acc[i];
    }
    __syncthreads();
    pdl_wait();
    for (int c = tid; c < 768; c += AT_THREADS)
      g_cs[(b >> 1) * FF + (b & 1) * 768 + c] = ((red[c] + red[768 + c]) + (red[1536 + c] + red[2304 + c])) + red[3072 + c];
    if (b == 0 && tid < 16) g_flag[tid] = 0;
    return;
  }
  TS(1, 0);
  if (tid == 0) {
    for (int i = 0; i < AT_CHUNKS; i++) mbar_init(sBar + 8 * i, 1);
    fence_mbar_init();
  }
  pdl_launch();
  if (tid == 32) {
    prefetch_l2(reinterpret_cast<const uint8_t*>(wo) + blockIdx.x * 6400, 6400);
    prefetch_l2(reinterpret_cast<const uint8_t*>(wgt) + blockIdx.x * 15360, 15360);
    prefetch_l2(reinterpret_cast<const uint8_t*>(wup) + blockIdx.x * 15360, 15360);
    prefetch_l2(reinterpret_cast<const uint8_t*>(wdn) + blockIdx.x * 15360, 15360);
  }
  __syncthreads();
  TS(1, 1);
  pdl_wait();
  TS(1, 2);
  if (tid == 0) {
    const uint8_t* kg = reinterpret_cast<const uint8_t*>(g_img + (size_t)(32 + head) * IMG_HEAD_ELEMS);
    const uint8_t* vg = reinterpret_cast<const uint8_t*>(g_img + (size_t)(64 + head) * IMG_HEAD_ELEMS);
    constexpr int CB = AT_KV_BYTES / AT_CHUNKS;
    for (int i = 0; i < AT_CHUNKS; i++) {
      mbar_expect_tx(sBar + 8 * i, 2 * CB);
      bulk_g2s(sK + i * CB, kg + i * CB, CB, sBar + 8 * i);
      bulk_g2s(sV + i * CB, vg + i * CB, CB, sBar + 8 * i);
    }
  }
  const int wg = warp >> 2, wwarp = warp & 3;
  const int g = lane >> 2, c4 = lane & 3;
  const uint64_t dk_base = make_desc(sK, 128, 384, 0);
  const uint64_t dv_base = make_desc(sV, 384, 128, 0);

  uint32_t qn[6];
  {
    const bf16* q0 = g_img + (size_t)head * IMG_HEAD_ELEMS + (size_t)((quarter * 512 + wg * 64 + wwarp * 16) >> 3) * 192 + g * 8 + c4 * 2;
    qn[0] = *reinterpret_cast<const uint32_t*>(q0);
    qn[1] = *reinterpret_cast<const uint32_t*>(q0 + 192);
    qn[2] = *reinterpret_cast<const uint32_t*>(q0 + 64);
    qn[3] = *reinterpret_cast<const uint32_t*>(q0 + 192 + 64);
    qn[4] = *reinterpret_cast<const uint32_t*>(q0 + 128);
    qn[5] = *reinterpret_cast<const uint32_t*>(q0 + 192 + 128);
  }
#pragma unroll 1
  for (int rep = 0; rep < 8 / AT_WGS; rep++) {
    const int row0 = quarter * 512 + (rep * AT_WGS + wg) * 64 + wwarp * 16 + g;
    AttnState st;
    st.qa0 = qn[0]; st.qa1 = qn[1]; st.qa2 = qn[2]; st.qa3 = qn[3]; st.qa4 = qn[4]; st.qa5 = qn[5];
    if (rep + 1 < 8 / AT_WGS) {
      const bf16* q0 = g_img + (size_t)head * IMG_HEAD_ELEMS + (size_t)((row0 + AT_WGS * 64) >> 3) * 192 + g * 8 + c4 * 2;
      qn[0] = *reinterpret_cast<const uint32_t*>(q0);
      qn[1] = *reinterpret_cast<const uint32_t*>(q0 + 192);
      qn[2] = *reinterpret_cast<const uint32_t*>(q0 + 64);
      qn[3] = *reinterpret_cast<const uint32_t*>(q0 + 192 + 64);
      qn[4] = *reinterpret_cast<const uint32_t*>(q0 + 128);
      qn[5] = *reinterpret_cast<const uint32_t*>(q0 + 192 + 128);
    }
    float o[12];
    float s[32];
    uint32_t pa[16], pb[16];
    st.M0 = st.M1 = 0.f;
    if (rep == 0) mbar_wait(sBar, 0);
    wgmma_fence();
    wgmma_rs_n64(s, st.qa0, st.qa1, st.qa2, st.qa3, dk_base, 0);
    wgmma_rs_n64(s, st.qa4, st.qa5, 0u, 0u, dk_base + 16, 1);
    wgmma_commit();
    wgmma_wait<0>();
    fence_regs(s);
    attn_exp_exact(s, pa, o, st, true, c4);
    attn_step(s, pa, pb, o, st, sK + 3072, sV, 0, c4);
#pragma unroll 1
    for (int tt = 1; tt < 16; tt++) {
      if (rep == 0 && !(tt & 1)) mbar_wait(sBar + 8 * (tt >> 1), 0);
      attn_step(s, pb, pa, o, st, sK + tt * 6144, sV + tt * 6144 - 3072, 1, c4, wg, rep * 32 + tt * 2);
      attn_step(s, pa, pb, o, st, sK + tt * 6144 + 3072, sV + tt * 6144, 1, c4, wg, rep * 32 + tt * 2 + 1);
    }
    wgmma_fence();
#pragma unroll
    for (int kk = 0; kk < 4; kk++) wgmma_rs_n24_tb(o, pb[4 * kk], pb[4 * kk + 1], pb[4 * kk + 2], pb[4 * kk + 3], dv_base + 31 * 192 + kk * 48, 1);
    wgmma_commit();
    wgmma_wait<0>();
    fence_regs(o);
    TS(1, 3 + rep);
    const float l0 = __shfl_sync(0xffffffffu, o[8], (lane & ~3) | 2);
    const float l1 = __shfl_sync(0xffffffffu, o[10], (lane & ~3) | 2);
    const float i0 = 1.0f / l0, i1 = 1.0f / l1;
    bf16* o0 = g_o + (size_t)row0 * DM + head * DH;
    bf16* o1 = o0 + 8 * DM;
#pragma unroll
    for (int j = 0; j < 3; j++) {
      if (j < 2 || c4 < 2) {
        *reinterpret_cast<uint32_t*>(o0 + j * 8 + c4 * 2) = pack_bf16(o[4 * j] * i0, o[4 * j + 1] * i0);
        *reinterpret_cast<uint32_t*>(o1 + j * 8 + c4 * 2) = pack_bf16(o[4 * j + 2] * i1, o[4 * j + 3] * i1);
      }
    }
  }
}

typedef CUresult (*EncodeTiledFn)(CUtensorMap*, CUtensorMapDataType, cuuint32_t, void*, const cuuint64_t*, const cuuint64_t*,
                                  const cuuint32_t*, const cuuint32_t*, CUtensorMapInterleave, CUtensorMapSwizzle,
                                  CUtensorMapL2promotion, CUtensorMapFloatOOBfill);

static void make_map(EncodeTiledFn fn, CUtensorMap* tm, const void* ptr, uint64_t rows, uint64_t cols, uint32_t box_rows,
                     uint32_t box_cols, CUtensorMapSwizzle sw) {
  cuuint64_t dims[2] = {cols, rows};
  cuuint64_t strides[1] = {cols * 2};
  cuuint32_t box[2] = {box_cols, box_rows};
  cuuint32_t es[2] = {1, 1};
  fn(tm, CU_TENSOR_MAP_DATA_TYPE_BFLOAT16, 2, const_cast<void*>(ptr), dims, strides, box, es, CU_TENSOR_MAP_INTERLEAVE_NONE, sw,
     CU_TENSOR_MAP_L2_PROMOTION_L2_256B, CU_TENSOR_MAP_FLOAT_OOB_FILL_NONE);
}

template <typename... KArgs, typename... Args>
static void launch(void (*kern)(KArgs...), int grid, int block, int smem, int cluster, bool pdl, Args... args) {
  cudaLaunchConfig_t cfg = {};
  cfg.gridDim = dim3(grid);
  cfg.blockDim = dim3(block);
  cfg.dynamicSmemBytes = smem;
  cfg.stream = cudaStreamPerThread;
  cudaLaunchAttribute at[2];
  int n = 0;
  if (cluster > 1) {
    at[n].id = cudaLaunchAttributeClusterDimension;
    at[n].val.clusterDim.x = cluster; at[n].val.clusterDim.y = 1; at[n].val.clusterDim.z = 1;
    n++;
  }
  if (pdl) {
    at[n].id = cudaLaunchAttributeProgrammaticStreamSerialization;
    at[n].val.programmaticStreamSerializationAllowed = 1;
    n++;
  }
  cfg.attrs = at;
  cfg.numAttrs = n;
  cudaLaunchKernelEx(&cfg, kern, KArgs(args)...);
}

extern "C" void kernel_launch(void* const* d_in, const int* in_sizes, int n_in, void* d_out, int out_size) {
  const bf16* x = (const bf16*)d_in[0];
  const bf16* wqkv = (const bf16*)d_in[1];
  const bf16* wo = (const bf16*)d_in[2];
  const bf16* wg = (const bf16*)d_in[4];
  const bf16* wu = (const bf16*)d_in[5];
  const bf16* wd = (const bf16*)d_in[6];
  bf16* out = (bf16*)d_out;

  static EncodeTiledFn enc = nullptr;
  static void *p_o = nullptr, *p_h = nullptr, *p_hh = nullptr, *p_xn = nullptr;
  if (!enc) {
    void* fn = nullptr;
    cudaDriverEntryPointQueryResult qr;
    cudaGetDriverEntryPoint("cuTensorMapEncodeTiled", &fn, cudaEnableDefault, &qr);
    enc = (EncodeTiledFn)fn;
    cudaGetSymbolAddress(&p_o, g_o);
    cudaGetSymbolAddress(&p_h, g_h);
    cudaGetSymbolAddress(&p_hh, g_hh);
    cudaGetSymbolAddress(&p_xn, g_xn);
    cudaFuncSetAttribute(qkv_kernel, cudaFuncAttributeMaxDynamicSharedMemorySize, KA_SMEM);
    cudaFuncSetAttribute(mlp_kernel, cudaFuncAttributeMaxDynamicSharedMemorySize, KC_SMEM);
    cudaFuncSetAttribute(attn_kernel, cudaFuncAttributeMaxDynamicSharedMemorySize, AT_SMEM);
  }
  CUtensorMap tm_wqkv, tm_wg, tm_wu, tm_wo64, tm_wo16, tm_wd64, tm_wd16, tm_o, tm_h, tm_hh, tm_hhs, tm_xn, tm_hs, tm_out;
  make_map(enc, &tm_wqkv, wqkv, DM, 3 * DM, 32, 64, CU_TENSOR_MAP_SWIZZLE_128B);
  make_map(enc, &tm_wg, wg, DM, FF, 32, 64, CU_TENSOR_MAP_SWIZZLE_128B);
  make_map(enc, &tm_wu, wu, DM, FF, 32, 64, CU_TENSOR_MAP_SWIZZLE_128B);
  make_map(enc, &tm_wo64, wo, DM, DM, 64, 64, CU_TENSOR_MAP_SWIZZLE_128B);
  make_map(enc, &tm_wo16, wo, DM, DM, 64, 16, CU_TENSOR_MAP_SWIZZLE_32B);
  make_map(enc, &tm_wd64, wd, FF, DM, 64, 64, CU_TENSOR_MAP_SWIZZLE_128B);
  make_map(enc, &tm_wd16, wd, FF, DM, 64, 16, CU_TENSOR_MAP_SWIZZLE_32B);
  make_map(enc, &tm_o, p_o, SEQ, DM, 64, 64, CU_TENSOR_MAP_SWIZZLE_128B);
  make_map(enc, &tm_h, p_h, SEQ, DM, 128, 32, CU_TENSOR_MAP_SWIZZLE_64B);
  make_map(enc, &tm_hh, p_hh, SEQ, FF, 64, 64, CU_TENSOR_MAP_SWIZZLE_128B);
  make_map(enc, &tm_hhs, p_hh, SEQ, FF, 64, 64, CU_TENSOR_MAP_SWIZZLE_128B);
  make_map(enc, &tm_xn, p_xn, SEQ, DM, 128, 32, CU_TENSOR_MAP_SWIZZLE_64B);
  make_map(enc, &tm_hs, p_h, SEQ, DM, 64, 80, CU_TENSOR_MAP_SWIZZLE_NONE);
  make_map(enc, &tm_out, out, SEQ, DM, 64, 80, CU_TENSOR_MAP_SWIZZLE_NONE);

  launch(qkv_kernel, 128, GT, KA_SMEM, 2, false, tm_xn, tm_wqkv, x);
  launch(attn_kernel, 132, AT_THREADS, AT_SMEM, 1, true, wo, wg, wu, wd);
  launch(mlp_kernel, 128, GT, KC_SMEM, 2, true, tm_o, tm_wo64, tm_wo16, tm_h, tm_wg, tm_wu, tm_hhs, tm_hh, tm_wd64, tm_wd16, tm_hs, tm_out, x);
}
```
